```python
import torch

def _softmax(x, axis=-1):
    return torch.softmax(x, dim=axis)
def _gelu(x):
    return torch.nn.functional.gelu(x, approximate="tanh")
def _silu(x):
    return torch.nn.functional.silu(x)
def _sigmoid(x):
    return torch.sigmoid(x)
def _layernorm(x, axis=-1, eps=1e-5):
    m = x.mean(dim=axis, keepdim=True)
    v = x.var(dim=axis, keepdim=True, unbiased=False)
    return (x - m) / torch.sqrt(v + eps)
def _scatter_add(tgt, idx, src, axis=0):
    return tgt.clone().index_add_(axis, idx, src)
def _segment_sum(src, seg, n):
    out = torch.zeros((n,) + src.shape[1:], dtype=src.dtype)
    return out.index_add_(0, seg, src)
def _pad(x, pw):
    flat = tuple(v for pair in reversed(pw) for v in pair)
    return torch.nn.functional.pad(x, flat)

kernel_name = 'interleave_layers__sliding_local_dilated__glu_gated_geglu__prompt'

def setup_inputs():

    _w = (lambda a: (lambda t: t.to(torch.bfloat16) if t.is_floating_point() else t)(torch.as_tensor(a)))
    def _A_setup():
        B, S, D = 1, 2048, 576
        return {
            "x": _w((lambda *s: torch.randn(*s, dtype=torch.bfloat16) * 0.05)(B, S, D)),
            "wqkv": _w((lambda *s: torch.randn(*s, dtype=torch.bfloat16) * 0.05)(D, 3 * D)),
            "wo": _w((lambda *s: torch.randn(*s, dtype=torch.bfloat16) * 0.05)(D, D)),
        }
    _A_in = _A_setup()

    def _B_setup():
        B, S, Dm, Df = 1, 2048, 576, 4608
        return {
            "x": _w((lambda *s: torch.randn(*s, dtype=torch.bfloat16) * 0.05)(B, S, Dm)),
            "w_gate": _w((lambda *s: torch.randn(*s, dtype=torch.bfloat16) * 0.8)(Dm, Df) * (Dm ** -0.5)),
            "w_up": _w((lambda *s: torch.randn(*s, dtype=torch.bfloat16) * 0.8)(Dm, Df) * (Dm ** -0.5)),
            "w_down": _w((lambda *s: torch.randn(*s, dtype=torch.bfloat16) * 0.8)(Df, Dm) * (Df ** -0.5)),
        }
    _B_in = _B_setup()

    return {
        "A_x": _A_in["x"],
        "A_wqkv": _A_in["wqkv"],
        "A_wo": _A_in["wo"],
        "B_x": _B_in["x"],
        "B_w_gate": _B_in["w_gate"],
        "B_w_up": _B_in["w_up"],
        "B_w_down": _B_in["w_down"],
    }

def reference(A_x, A_wqkv, A_wo, B_x, B_w_gate, B_w_up, B_w_down):
    def _A_ref(x, wqkv, wo):
        B, S, D = x.shape
        H = 32; Dh = D // H
        W, dil = 8, 2
        qkv = (lambda x, *d: x.permute(*d))((x @ wqkv).reshape(B, S, 3, H, Dh), 2, 0, 3, 1, 4)
        q, k, v = qkv[0], qkv[1], qkv[2]
        scale = Dh ** -0.5
        pos = torch.arange(S)
        off = torch.arange(W) * dil
        idx = pos[:, None] - off[None, :]
        mask = idx >= 0
        idx_c = torch.where(mask, idx, 0).reshape(-1)
        kg = k[:, :, idx_c, :].reshape(B, H, S, W, Dh)
        vg = v[:, :, idx_c, :].reshape(B, H, S, W, Dh)
        logits = torch.einsum("bhsd,bhswd->bhsw", q, kg) * scale
        logits = torch.where(mask[None, None, :, :], logits, -1e9)
        attn = _softmax(logits, axis=-1)
        o = torch.einsum("bhsw,bhswd->bhsd", attn, vg)
        return (lambda x, *d: x.permute(*d))(o, 0, 2, 1, 3).reshape(B, S, D) @ wo

    def _B_ref(x, w_gate, w_up, w_down):
        g = torch.einsum("bsd,df->bsf", x, w_gate)
        u = torch.einsum("bsd,df->bsf", x, w_up)
        h = _gelu(g) * u
        return torch.einsum("bsf,fd->bsd", h, w_down)

    x = A_x
    x = x + _A_ref(_layernorm(x, axis=-1), A_wqkv, A_wo)
    x = x + _B_ref(_layernorm(x, axis=-1), B_w_gate, B_w_up, B_w_down)
    x = x + _A_ref(_layernorm(x, axis=-1), A_wqkv, A_wo)
    x = x + _B_ref(_layernorm(x, axis=-1), B_w_gate, B_w_up, B_w_down)
    return x
```

```cpp
#include <cuda_runtime.h>
#include <cuda_bf16.h>
#include <cuda.h>
#include <stdint.h>

#define USE_MC 0
#define NSLOT 13
#define TIMING 0

namespace {

constexpr int SEQ = 2048, DM = 576, DFF = 4608;
constexpr int SLOT = 16384;
constexpr int PSLOT = 13824;
constexpr int NSTASH = 14 - NSLOT;
constexpr int SMEM_BARS = 14 * SLOT;
constexpr int SMEM_BYTES = SMEM_BARS + 256 + 1024;
constexpr int FSTR = 8;

__device__ uint4 g_wpack[8 * 24 * (PSLOT / 16)];
__device__ uint4 g_obuf[32 * 36 * 128];
__device__ uint4 g_x1buf[32 * 36 * 128];
__device__ uint4 g_x2buf[32 * 36 * 128];
__device__ float4 g_x1st[32 * 4 * 16 * 4];
__device__ float4 g_x2st[32 * 4 * 16 * 4];
__device__ uint4 g_hbuf[256 * 36 * 128];
__device__ uint4 g_halo[2 * 32 * 8 * 9 * 32];
__device__ unsigned g_flags[(8 + 7 * 128) * FSTR];
__device__ unsigned g_epoch[128];
enum { FL_O = 0, FL_X1 = 2, FL_P = 4, FL_X2 = 6 };

__device__ __forceinline__ uint32_t smem_u32(const void* p) { return (uint32_t)__cvta_generic_to_shared(p); }
__device__ __forceinline__ void mbar_init(uint32_t bar, uint32_t cnt) { asm volatile("mbarrier.init.shared::cta.b64 [%0], %1;" ::"r"(bar), "r"(cnt)); }
__device__ __forceinline__ void mbar_expect_tx(uint32_t bar, uint32_t bytes) { asm volatile("mbarrier.arrive.expect_tx.shared::cta.b64 _, [%0], %1;" ::"r"(bar), "r"(bytes) : "memory"); }
__device__ __forceinline__ void mbar_arrive(uint32_t bar) { asm volatile("mbarrier.arrive.shared::cta.b64 _, [%0];" ::"r"(bar) : "memory"); }
__device__ __forceinline__ void mbar_arrive_cluster(uint32_t bar, uint32_t cta) {
  asm volatile("{\n.reg .b32 ra;\nmapa.shared::cluster.u32 ra, %0, %1;\nmbarrier.arrive.shared::cluster.b64 _, [ra];\n}" ::"r"(bar), "r"(cta) : "memory");
}
__device__ __forceinline__ void mbar_wait(uint32_t bar, uint32_t parity) {
  asm volatile("{\n.reg .pred p;\n.reg .u32 n;\nmov.u32 n, 0;\nLAB_WAIT:\n"
               "mbarrier.try_wait.parity.shared::cta.b64 p, [%0], %1;\n@p bra LAB_DONE;\n"
               "add.u32 n, n, 1;\nsetp.lt.u32 p, n, 0x200000;\n@p bra LAB_WAIT;\ntrap;\nLAB_DONE:\n}" ::"r"(bar), "r"(parity) : "memory");
}
__device__ __forceinline__ void flag_wait(const unsigned* flag, unsigned target) {
  asm volatile("{\n.reg .pred p;\n.reg .u32 n, v;\nmov.u32 n, 0;\nLAB_WAIT:\n"
               "ld.acquire.gpu.global.u32 v, [%0];\nsub.u32 v, v, %1;\nsetp.ge.s32 p, v, 0;\n@p bra LAB_DONE;\n"
               "add.u32 n, n, 1;\nsetp.lt.u32 p, n, 0x400000;\n@p bra LAB_WAIT;\ntrap;\nLAB_DONE:\n}" ::"l"(flag), "r"(target) : "memory");
}
__device__ __forceinline__ void flag_signal(unsigned* flag) { asm volatile("red.release.gpu.global.add.u32 [%0], 1;" ::"l"(flag) : "memory"); }
__device__ __forceinline__ void tma_2d(uint32_t dst, const CUtensorMap* m, int c0, int c1, uint32_t bar) {
  asm volatile("cp.async.bulk.tensor.2d.shared::cluster.global.mbarrier::complete_tx::bytes [%0], [%1, {%3, %4}], [%2];"
               ::"r"(dst), "l"(m), "r"(bar), "r"(c0), "r"(c1) : "memory");
}
__device__ __forceinline__ void tma_2d_mc(uint32_t dst, const CUtensorMap* m, int c0, int c1, uint32_t bar) {
  asm volatile("cp.async.bulk.tensor.2d.shared::cluster.global.mbarrier::complete_tx::bytes.multicast::cluster [%0], [%1, {%3, %4}], [%2], %5;"
               ::"r"(dst), "l"(m), "r"(bar), "r"(c0), "r"(c1), "h"((uint16_t)3) : "memory");
}
__device__ __forceinline__ void tma_3d(uint32_t dst, const CUtensorMap* m, int c0, int c1, int c2, uint32_t bar) {
  asm volatile("cp.async.bulk.tensor.3d.shared::cluster.global.mbarrier::complete_tx::bytes [%0], [%1, {%3, %4, %5}], [%2];"
               ::"r"(dst), "l"(m), "r"(bar), "r"(c0), "r"(c1), "r"(c2) : "memory");
}
__device__ __forceinline__ void bulk_load(uint32_t dst, const void* src, uint32_t bytes, uint32_t bar) {
  asm volatile("cp.async.bulk.shared::cluster.global.mbarrier::complete_tx::bytes [%0], [%1], %2, [%3];" ::"r"(dst), "l"(src), "r"(bytes), "r"(bar) : "memory");
}
__device__ __forceinline__ void bulk_load_mc(uint32_t dst, const void* src, uint32_t bytes, uint32_t bar) {
  asm volatile("cp.async.bulk.shared::cluster.global.mbarrier::complete_tx::bytes.multicast::cluster [%0], [%1], %2, [%3], %4;"
               ::"r"(dst), "l"(src), "r"(bytes), "r"(bar), "h"((uint16_t)3) : "memory");
}
__device__ __forceinline__ void l2_prefetch(const void* src, uint32_t bytes) { asm volatile("cp.async.bulk.prefetch.L2.global [%0], %1;" ::"l"(src), "r"(bytes) : "memory"); }
__device__ __forceinline__ void wg_fence() { asm volatile("wgmma.fence.sync.aligned;" ::: "memory"); }
__device__ __forceinline__ void wg_commit() { asm volatile("wgmma.commit_group.sync.aligned;" ::: "memory"); }
template <int N> __device__ __forceinline__ void wg_wait() { asm volatile("wgmma.wait_group.sync.aligned %0;" ::"n"(N) : "memory"); }
__device__ __forceinline__ void bar_sync(int id, int n) { asm volatile("bar.sync %0, %1;" ::"r"(id), "r"(n) : "memory"); }
__device__ __forceinline__ void bar_arrive(int id, int n) { asm volatile("bar.arrive %0, %1;" ::"r"(id), "r"(n) : "memory"); }
__device__ __forceinline__ void cluster_sync_all() { asm volatile("barrier.cluster.arrive.release.aligned;\nbarrier.cluster.wait.acquire.aligned;" ::: "memory"); }
__device__ __forceinline__ uint32_t pack_bf16(float lo, float hi) { uint32_t r; asm("cvt.rn.bf16x2.f32 %0, %1, %2;" : "=r"(r) : "f"(hi), "f"(lo)); return r; }
__device__ __forceinline__ float bf_lo(uint32_t w) { return __uint_as_float(w << 16); }
__device__ __forceinline__ float bf_hi(uint32_t w) { return __uint_as_float(w & 0xffff0000u); }
__device__ __forceinline__ float bf_round(float x) { return bf_lo(pack_bf16(x, 0.f)); }
__device__ __forceinline__ uint32_t bf2_sub(uint32_t a, uint32_t b) { uint32_t r; asm("sub.rn.bf16x2 %0, %1, %2;" : "=r"(r) : "r"(a), "r"(b)); return r; }
__device__ __forceinline__ uint32_t bf2_add(uint32_t a, uint32_t b) { uint32_t r; asm("add.rn.bf16x2 %0, %1, %2;" : "=r"(r) : "r"(a), "r"(b)); return r; }
__device__ __forceinline__ uint4 ld_cg4(const uint4* p) { uint4 v; asm volatile("ld.global.cg.v4.u32 {%0,%1,%2,%3}, [%4];" : "=r"(v.x), "=r"(v.y), "=r"(v.z), "=r"(v.w) : "l"(p) : "memory"); return v; }
__device__ __forceinline__ uint2 ld_cg2(const uint2* p) { uint2 v; asm volatile("ld.global.cg.v2.u32 {%0,%1}, [%2];" : "=r"(v.x), "=r"(v.y) : "l"(p) : "memory"); return v; }
__device__ __forceinline__ void st_cg4(uint4* p, uint32_t a, uint32_t b, uint32_t c, uint32_t d) { asm volatile("st.global.cg.v4.u32 [%0], {%1,%2,%3,%4};" ::"l"(p), "r"(a), "r"(b), "r"(c), "r"(d) : "memory"); }
__device__ __forceinline__ void st_cg2(uint2* p, uint32_t a, uint32_t b) { asm volatile("st.global.cg.v2.u32 [%0], {%1,%2};" ::"l"(p), "r"(a), "r"(b) : "memory"); }
__device__ __forceinline__ void mma16816(float (&c)[4], uint32_t a0, uint32_t a1, uint32_t a2, uint32_t a3, uint32_t b0, uint32_t b1) {
  asm volatile("mma.sync.aligned.m16n8k16.row.col.f32.bf16.bf16.f32 {%0,%1,%2,%3}, {%4,%5,%6,%7}, {%8,%9}, {%0,%1,%2,%3};"
               : "+f"(c[0]), "+f"(c[1]), "+f"(c[2]), "+f"(c[3]) : "r"(a0), "r"(a1), "r"(a2), "r"(a3), "r"(b0), "r"(b1));
}
__device__ __forceinline__ void mma1688(float (&c)[4], uint32_t a0, uint32_t a1, uint32_t b0) {
  asm volatile("mma.sync.aligned.m16n8k8.row.col.f32.bf16.bf16.f32 {%0,%1,%2,%3}, {%4,%5}, {%6}, {%0,%1,%2,%3};"
               : "+f"(c[0]), "+f"(c[1]), "+f"(c[2]), "+f"(c[3]) : "r"(a0), "r"(a1), "r"(b0));
}
__device__ __forceinline__ uint32_t movm_t(uint32_t a) { uint32_t d; asm volatile("movmatrix.sync.aligned.m8n8.trans.b16 %0, %1;" : "=r"(d) : "r"(a)); return d; }
__device__ __forceinline__ float quad_sum(float v) { v += __shfl_xor_sync(0xffffffffu, v, 1); v += __shfl_xor_sync(0xffffffffu, v, 2); return v; }
__device__ __forceinline__ float quad_max(float v) { v = fmaxf(v, __shfl_xor_sync(0xffffffffu, v, 1)); v = fmaxf(v, __shfl_xor_sync(0xffffffffu, v, 2)); return v; }

__device__ __forceinline__ void wgmma_rs_n64(float (&d)[32], uint32_t a0, uint32_t a1, uint32_t a2, uint32_t a3, uint64_t desc, int scale_d) {
  asm volatile("{\n.reg .pred p;\nsetp.ne.b32 p, %37, 0;\n"
    "wgmma.mma_async.sync.aligned.m64n64k16.f32.bf16.bf16 "
    "{%0, %1, %2, %3, %4, %5, %6, %7, %8, %9, %10, %11, %12, %13, %14, %15, %16, %17, %18, %19, %20, %21, %22, %23, %24, %25, %26, %27, %28, %29, %30, %31}, "
    "{%32, %33, %34, %35}, %36, p, 1, 1, 1;\n}\n"
    : "+f"(d[0]), "+f"(d[1]), "+f"(d[2]), "+f"(d[3]), "+f"(d[4]), "+f"(d[5]), "+f"(d[6]), "+f"(d[7]), "+f"(d[8]), "+f"(d[9]), "+f"(d[10]), "+f"(d[11]), "+f"(d[12]), "+f"(d[13]), "+f"(d[14]), "+f"(d[15]), "+f"(d[16]), "+f"(d[17]), "+f"(d[18]), "+f"(d[19]), "+f"(d[20]), "+f"(d[21]), "+f"(d[22]), "+f"(d[23]), "+f"(d[24]), "+f"(d[25]), "+f"(d[26]), "+f"(d[27]), "+f"(d[28]), "+f"(d[29]), "+f"(d[30]), "+f"(d[31])
    : "r"(a0), "r"(a1), "r"(a2), "r"(a3), "l"(desc), "r"(scale_d));
}

__device__ __forceinline__ void wgmma_rs_n72(float (&d)[36], uint32_t a0, uint32_t a1, uint32_t a2, uint32_t a3, uint64_t desc, int scale_d) {
  asm volatile("{\n.reg .pred p;\nsetp.ne.b32 p, %41, 0;\n"
    "wgmma.mma_async.sync.aligned.m64n72k16.f32.bf16.bf16 "
    "{%0, %1, %2, %3, %4, %5, %6, %7, %8, %9, %10, %11, %12, %13, %14, %15, %16, %17, %18, %19, %20, %21, %22, %23, %24, %25, %26, %27, %28, %29, %30, %31, %32, %33, %34, %35}, "
    "{%36, %37, %38, %39}, %40, p, 1, 1, 1;\n}\n"
    : "+f"(d[0]), "+f"(d[1]), "+f"(d[2]), "+f"(d[3]), "+f"(d[4]), "+f"(d[5]), "+f"(d[6]), "+f"(d[7]), "+f"(d[8]), "+f"(d[9]), "+f"(d[10]), "+f"(d[11]), "+f"(d[12]), "+f"(d[13]), "+f"(d[14]), "+f"(d[15]), "+f"(d[16]), "+f"(d[17]), "+f"(d[18]), "+f"(d[19]), "+f"(d[20]), "+f"(d[21]), "+f"(d[22]), "+f"(d[23]), "+f"(d[24]), "+f"(d[25]), "+f"(d[26]), "+f"(d[27]), "+f"(d[28]), "+f"(d[29]), "+f"(d[30]), "+f"(d[31]), "+f"(d[32]), "+f"(d[33]), "+f"(d[34]), "+f"(d[35])
    : "r"(a0), "r"(a1), "r"(a2), "r"(a3), "l"(desc), "r"(scale_d));
}

__device__ __forceinline__ void wgmma_rs_n128(float (&d)[64], uint32_t a0, uint32_t a1, uint32_t a2, uint32_t a3, uint64_t desc, int scale_d) {
  asm volatile("{\n.reg .pred p;\nsetp.ne.b32 p, %69, 0;\n"
    "wgmma.mma_async.sync.aligned.m64n128k16.f32.bf16.bf16 "
    "{%0, %1, %2, %3, %4, %5, %6, %7, %8, %9, %10, %11, %12, %13, %14, %15, %16, %17, %18, %19, %20, %21, %22, %23, %24, %25, %26, %27, %28, %29, %30, %31, %32, %33, %34, %35, %36, %37, %38, %39, %40, %41, %42, %43, %44, %45, %46, %47, %48, %49, %50, %51, %52, %53, %54, %55, %56, %57, %58, %59, %60, %61, %62, %63}, "
    "{%64, %65, %66, %67}, %68, p, 1, 1, 1;\n}\n"
    : "+f"(d[0]), "+f"(d[1]), "+f"(d[2]), "+f"(d[3]), "+f"(d[4]), "+f"(d[5]), "+f"(d[6]), "+f"(d[7]), "+f"(d[8]), "+f"(d[9]), "+f"(d[10]), "+f"(d[11]), "+f"(d[12]), "+f"(d[13]), "+f"(d[14]), "+f"(d[15]), "+f"(d[16]), "+f"(d[17]), "+f"(d[18]), "+f"(d[19]), "+f"(d[20]), "+f"(d[21]), "+f"(d[22]), "+f"(d[23]), "+f"(d[24]), "+f"(d[25]), "+f"(d[26]), "+f"(d[27]), "+f"(d[28]), "+f"(d[29]), "+f"(d[30]), "+f"(d[31]), "+f"(d[32]), "+f"(d[33]), "+f"(d[34]), "+f"(d[35]), "+f"(d[36]), "+f"(d[37]), "+f"(d[38]), "+f"(d[39]), "+f"(d[40]), "+f"(d[41]), "+f"(d[42]), "+f"(d[43]), "+f"(d[44]), "+f"(d[45]), "+f"(d[46]), "+f"(d[47]), "+f"(d[48]), "+f"(d[49]), "+f"(d[50]), "+f"(d[51]), "+f"(d[52]), "+f"(d[53]), "+f"(d[54]), "+f"(d[55]), "+f"(d[56]), "+f"(d[57]), "+f"(d[58]), "+f"(d[59]), "+f"(d[60]), "+f"(d[61]), "+f"(d[62]), "+f"(d[63])
    : "r"(a0), "r"(a1), "r"(a2), "r"(a3), "l"(desc), "r"(scale_d));
}

__device__ __forceinline__ void wgmma_rs_n144(float (&d)[72], uint32_t a0, uint32_t a1, uint32_t a2, uint32_t a3, uint64_t desc, int scale_d) {
  asm volatile("{\n.reg .pred p;\nsetp.ne.b32 p, %77, 0;\n"
    "wgmma.mma_async.sync.aligned.m64n144k16.f32.bf16.bf16 "
    "{%0, %1, %2, %3, %4, %5, %6, %7, %8, %9, %10, %11, %12, %13, %14, %15, %16, %17, %18, %19, %20, %21, %22, %23, %24, %25, %26, %27, %28, %29, %30, %31, %32, %33, %34, %35, %36, %37, %38, %39, %40, %41, %42, %43, %44, %45, %46, %47, %48, %49, %50, %51, %52, %53, %54, %55, %56, %57, %58, %59, %60, %61, %62, %63, %64, %65, %66, %67, %68, %69, %70, %71}, "
    "{%72, %73, %74, %75}, %76, p, 1, 1, 1;\n}\n"
    : "+f"(d[0]), "+f"(d[1]), "+f"(d[2]), "+f"(d[3]), "+f"(d[4]), "+f"(d[5]), "+f"(d[6]), "+f"(d[7]), "+f"(d[8]), "+f"(d[9]), "+f"(d[10]), "+f"(d[11]), "+f"(d[12]), "+f"(d[13]), "+f"(d[14]), "+f"(d[15]), "+f"(d[16]), "+f"(d[17]), "+f"(d[18]), "+f"(d[19]), "+f"(d[20]), "+f"(d[21]), "+f"(d[22]), "+f"(d[23]), "+f"(d[24]), "+f"(d[25]), "+f"(d[26]), "+f"(d[27]), "+f"(d[28]), "+f"(d[29]), "+f"(d[30]), "+f"(d[31]), "+f"(d[32]), "+f"(d[33]), "+f"(d[34]), "+f"(d[35]), "+f"(d[36]), "+f"(d[37]), "+f"(d[38]), "+f"(d[39]), "+f"(d[40]), "+f"(d[41]), "+f"(d[42]), "+f"(d[43]), "+f"(d[44]), "+f"(d[45]), "+f"(d[46]), "+f"(d[47]), "+f"(d[48]), "+f"(d[49]), "+f"(d[50]), "+f"(d[51]), "+f"(d[52]), "+f"(d[53]), "+f"(d[54]), "+f"(d[55]), "+f"(d[56]), "+f"(d[57]), "+f"(d[58]), "+f"(d[59]), "+f"(d[60]), "+f"(d[61]), "+f"(d[62]), "+f"(d[63]), "+f"(d[64]), "+f"(d[65]), "+f"(d[66]), "+f"(d[67]), "+f"(d[68]), "+f"(d[69]), "+f"(d[70]), "+f"(d[71])
    : "r"(a0), "r"(a1), "r"(a2), "r"(a3), "l"(desc), "r"(scale_d));
}

template <int N> struct WG;
template <> struct WG<64>  { static __device__ __forceinline__ void f(float (&d)[32], const uint32_t* a, uint64_t ds, int s) { wgmma_rs_n64(d, a[0], a[1], a[2], a[3], ds, s); } };
template <> struct WG<72>  { static __device__ __forceinline__ void f(float (&d)[36], const uint32_t* a, uint64_t ds, int s) { wgmma_rs_n72(d, a[0], a[1], a[2], a[3], ds, s); } };
template <> struct WG<128> { static __device__ __forceinline__ void f(float (&d)[64], const uint32_t* a, uint64_t ds, int s) { wgmma_rs_n128(d, a[0], a[1], a[2], a[3], ds, s); } };
template <> struct WG<144> { static __device__ __forceinline__ void f(float (&d)[72], const uint32_t* a, uint64_t ds, int s) { wgmma_rs_n144(d, a[0], a[1], a[2], a[3], ds, s); } };

struct Ring {
  uint32_t base;
  uint32_t slot;
  uint32_t phase;
  __device__ __forceinline__ uint32_t full() const { return base + SMEM_BARS + 8 * slot; }
  __device__ __forceinline__ uint32_t empty() const { return base + SMEM_BARS + 128 + 8 * slot; }
  __device__ __forceinline__ uint32_t addr() const { return base + slot * SLOT; }
  __device__ __forceinline__ void next() { if (++slot == NSLOT) { slot = 0; phase ^= 1; } }
};
__device__ __forceinline__ void release(uint32_t bar, bool leader) {
  if (leader) {
    mbar_arrive(bar);
  }
}

constexpr uint64_t DESC_SW128 = ((uint64_t)(8192 >> 4) << 16) | ((uint64_t)(1024 >> 4) << 32) | (1ull << 62);
constexpr uint64_t DESC_KV = ((uint64_t)(128 >> 4) << 16) | ((uint64_t)(768 >> 4) << 32);
constexpr uint64_t DESC_Q = ((uint64_t)(128 >> 4) << 16) | ((uint64_t)(1536 >> 4) << 32);

template <int N, int KPS, int KSTEP, bool SUB>
__device__ __forceinline__ void mma_pass(float (&acc)[N / 2], uint32_t (&a)[144], Ring& r, uint64_t desc_hi, bool leader,
                                         uint32_t m0, uint32_t m1, int bar_id) {
  constexpr int NS = (36 + KPS - 1) / KPS;
  uint32_t prev = 0;
#pragma unroll
  for (int s = 0; s < NS; s++) {
    if (SUB) {
#pragma unroll
      for (int kk = 0; kk < KPS; kk++) {
        const int i = (s * KPS + kk) * 4;
        if (i < 144) { a[i] = bf2_sub(a[i], m0); a[i + 1] = bf2_sub(a[i + 1], m1); a[i + 2] = bf2_sub(a[i + 2], m0); a[i + 3] = bf2_sub(a[i + 3], m1); }
      }
    }
    mbar_wait(r.full(), r.phase);
    wg_fence();
    const uint64_t desc = desc_hi | (uint64_t)((r.addr() & 0x3FFFF) >> 4);
#pragma unroll
    for (int kk = 0; kk < KPS; kk++) {
      const int i = s * KPS + kk;
      if (i < 36) WG<N>::f(acc, &a[i * 4], desc + ((kk * KSTEP) >> 4), i ? 1 : 0);
    }
    wg_commit();
    if (s == NS - 1 && bar_id >= 0) bar_arrive(bar_id, 256);
    if (s > 0) { wg_wait<1>(); release(prev, leader); }
    prev = r.empty();
    r.next();
  }
  wg_wait<0>();
  release(prev, leader);
}

__device__ __forceinline__ void load_frags(uint32_t (&a)[144], const uint4* p) {
#pragma unroll
  for (int i = 0; i < 36; i++) { uint4 v = ld_cg4(p + i * 128); a[4 * i] = v.x; a[4 * i + 1] = v.y; a[4 * i + 2] = v.z; a[4 * i + 3] = v.w; }
}
__device__ __forceinline__ void ln_scalars(float s1, float s2, uint32_t& m, float& rstd) {
  const float mean = s1 * (1.f / DM);
  const float var = fmaxf(s2 * (1.f / DM) - mean * mean, 0.f);
  m = pack_bf16(mean, mean);
  rstd = 1.f / bf_round(sqrtf(bf_round(bf_round(var) + 1e-5f)));
}
__device__ __forceinline__ void load_stats(const float4* st, int g, int q, uint32_t& m0, uint32_t& m1, float& r0, float& r1) {
  uint4 u = ld_cg4((const uint4*)st + g * 4 + q), v = ld_cg4((const uint4*)st + (g + 8) * 4 + q);
  float a1 = quad_sum(__uint_as_float(u.x) + __uint_as_float(u.z)), a2 = quad_sum(__uint_as_float(u.y) + __uint_as_float(u.w));
  float b1 = quad_sum(__uint_as_float(v.x) + __uint_as_float(v.z)), b2 = quad_sum(__uint_as_float(v.y) + __uint_as_float(v.w));
  ln_scalars(a1, a2, m0, r0); ln_scalars(b1, b2, m1, r1);
}
__device__ __forceinline__ void acc_stats(uint32_t w, float& s1, float& s2) { float lo = bf_lo(w), hi = bf_hi(w); s1 += lo + hi; s2 = fmaf(lo, lo, fmaf(hi, hi, s2)); }
__device__ __forceinline__ void store_stats(float4* st, int j, int g, int q, float a1, float a2, float b1, float b2) {
  a1 = quad_sum(a1); a2 = quad_sum(a2); b1 = quad_sum(b1); b2 = quad_sum(b2);
  if (q < 2) st_cg2((uint2*)st + (g + 8 * q) * 8 + j, __float_as_uint(q ? b1 : a1), __float_as_uint(q ? b2 : a2));
}

#define TS(i) do {} while (0)

struct Params {
  const __nv_bfloat16 *x, *wqkv, *wo, *wg, *wu, *wd;
  __nv_bfloat16* out;
  unsigned zero;
};

__global__ void __launch_bounds__(384, 1)
fused_kernel(const __grid_constant__ CUtensorMap map_x, const __grid_constant__ CUtensorMap map_wg,
             const __grid_constant__ CUtensorMap map_wu, const __grid_constant__ CUtensorMap map_wd, const Params P) {
  extern __shared__ __align__(1024) uint8_t smem_raw[];
  const uint32_t base = (smem_u32(smem_raw) + 1023) & ~1023u;
  const int wg = __shfl_sync(0xffffffffu, threadIdx.x >> 7, 0);
  const int cta = blockIdx.x, rank = cta & 1, j = (cta >> 1) & 7, rb = (cta >> 4) * 2 + rank;
  Ring ring{base, 0, 0};
  if (threadIdx.x == 256) {
    for (int i = 0; i < NSLOT; i++) { mbar_init(base + SMEM_BARS + 8 * i, 1); mbar_init(base + SMEM_BARS + 128 + 8 * i, USE_MC ? 4 : 2); }
    asm volatile("fence.mbarrier_init.release.cluster;" ::: "memory");
    asm volatile("fence.proxy.async.shared::cta;" ::: "memory");
    for (int c = 0; c < 9; c++) {
      mbar_expect_tx(base + SMEM_BARS + 8 * c, SLOT);
      tma_3d(base + c * SLOT, &map_x, c * 64, 0, rb * 64, base + SMEM_BARS + 8 * c);
      tma_3d(base + c * SLOT + 8192, &map_x, c * 64, 1, rb * 64, base + SMEM_BARS + 8 * c);
    }
  }
  const unsigned epoch = *(volatile unsigned*)&g_epoch[cta];
  {
    uint4 v[4]; uint4* dst[4];
#pragma unroll
    for (int i = 0; i < 4; i++) {
      const int it = threadIdx.x + i * 384;
      const int mat = it / 324, rem = it % 324, k = rb * 36 + rem / 9, u = rem % 9;
      dst[i] = nullptr;
      if (it < 1296) {
        const __nv_bfloat16* src = mat < 3 ? P.wqkv + (size_t)k * 1728 + mat * 576 + j * 72 + u * 8 : P.wo + (size_t)k * 576 + j * 72 + u * 8;
        v[i] = __ldg((const uint4*)src);
        int off;
        if (mat == 1 || mat == 2) off = (k / 48) * 864 + (u + (mat - 1) * 9) * 48 + k % 48;
        else off = ((mat ? 18 : 12) + k / 96) * 864 + u * 96 + k % 96;
        dst[i] = g_wpack + j * 24 * 864 + off;
      }
    }
#pragma unroll
    for (int i = 0; i < 4; i++) if (dst[i]) st_cg4(dst[i], v[i].x, v[i].y, v[i].z, v[i].w);
    asm volatile("fence.proxy.async.global;" ::: "memory");
  }
  __syncthreads();

  if (wg == 2) {
    asm volatile("setmaxnreg.dec.sync.aligned.u32 24;");
    const int pw = (threadIdx.x >> 5) & 3, lane = threadIdx.x & 31;
    if (pw == 0) {
      if (lane == 0) {
        flag_signal(&g_flags[j * FSTR]);
        ring.slot = 9; ring.phase = 1;
        flag_wait(&g_flags[j * FSTR], (epoch + 1) * 16);
        asm volatile("fence.proxy.async.global;" ::: "memory");
        for (int L = 0; L < 2; L++) {
          const uint8_t* wp = (const uint8_t*)(g_wpack + j * 24 * 864);
          for (int s = 0; s < 24; s++) {
            mbar_wait(ring.empty(), ring.phase);
            mbar_expect_tx(ring.full(), PSLOT);
            bulk_load(ring.addr(), wp + s * PSLOT, PSLOT, ring.full());
            ring.next();
          }
          for (int t = 0; t < 9; t++)
            for (int k = 0; k < 9; k++) {
              mbar_wait(ring.empty(), ring.phase);
              mbar_expect_tx(ring.full(), SLOT);
              tma_2d(ring.addr(), &map_wg, j * 576 + t * 64, k * 64, ring.full());
              tma_2d(ring.addr() + 8192, &map_wu, j * 576 + t * 64, k * 64, ring.full());
              ring.next();
            }
          for (int p = 0; p < 5; p++) {
            const bool narrow = p == 2;
            const int c0 = narrow ? 512 : (p < 2 ? p : p - 1) * 128;
            const int ns = narrow ? 5 : 9;
            for (int k = 0; k < ns; k++) {
              const bool half = narrow && k == 4;
              const int ca = c0, ra = j * 576 + (narrow ? k * 128 : k * 64);
              const int cb = narrow ? c0 : c0 + 64, rb2 = narrow ? ra + 64 : ra;
              mbar_wait(ring.empty(), ring.phase);
              mbar_expect_tx(ring.full(), half ? 8192 : SLOT);
              tma_2d(ring.addr(), &map_wd, ca, ra, ring.full());
              if (!half) tma_2d(ring.addr() + 8192, &map_wd, cb, rb2, ring.full());
              ring.next();
            }
          }
        }
        g_epoch[cta] = epoch + 1;
      }
    } else if (pw == 1) {
      for (int i = lane; i < 72; i += 32) {
        const __nv_bfloat16* w = (i & 1) ? P.wu : P.wg;
        l2_prefetch(w + (size_t)(rb * 36 + (i >> 1)) * DFF + j * 576, 1152);
      }
      for (int i = lane; i < 36; i += 32) l2_prefetch(P.wd + (size_t)(j * 576 + rb * 36 + i) * DM, 1152);
    }
  } else {
    asm volatile("setmaxnreg.inc.sync.aligned.u32 240;");
    const int tid = threadIdx.x & 127, w = tid >> 5, lane = tid & 31, g = lane >> 2, q = lane & 3;
    const bool leader = tid == 0;
    const int strm = rb * 2 + wg;
    const unsigned ftgt = (epoch + 1) * 8;
    unsigned* const flags = g_flags + (8 + strm * 4 + w) * FSTR;
    const int tok0 = rb * 128 + 2 * (w * 16 + g) + wg;
    uint32_t a[144];
    TS(0);
#pragma unroll 1
    for (int L = 0; L < 2; L++) {
      uint32_t m0, m1; float r0, r1;
      if (L == 0) {
        float s10 = 0.f, s20 = 0.f, s11 = 0.f, s21 = 0.f;
        const int row = w * 16 + (lane & 15);
#pragma unroll
        for (int c = 0; c < 9; c++) {
          mbar_wait(ring.full(), ring.phase);
          const uint32_t rowaddr = ring.addr() + wg * 8192 + row * 128;
#pragma unroll
          for (int kk = 0; kk < 4; kk++) {
            const int i = c * 16 + kk * 4;
            asm volatile("ldmatrix.sync.aligned.m8n8.x4.shared.b16 {%0,%1,%2,%3}, [%4];"
                         : "=r"(a[i]), "=r"(a[i + 1]), "=r"(a[i + 2]), "=r"(a[i + 3])
                         : "r"(rowaddr + (((kk * 2 + (lane >> 4)) ^ (row & 7)) << 4)) : "memory");
          }
#pragma unroll
          for (int i = c * 16; i < c * 16 + 16; i += 2) { acc_stats(a[i], s10, s20); acc_stats(a[i + 1], s11, s21); }
          bar_sync(5 + wg, 128);
          release(ring.empty(), leader);
          ring.next();
        }
        ln_scalars(quad_sum(s10), quad_sum(s20), m0, r0);
        ln_scalars(quad_sum(s11), quad_sum(s21), m1, r1);
      } else {
        if (lane == 0) flag_wait(flags + FL_X2 * 128 * FSTR, ftgt);
        __syncwarp();
        load_stats(g_x2st + (strm * 4 + w) * 64, g, q, m0, m1, r0, r1);
        load_frags(a, g_x2buf + strm * 36 * 128 + tid);
      }
      TS(1 + L * 20);
      uint32_t kf[18], vf[18], qf[18];
      {
        float acc[72];
        if (wg == 1) bar_sync(4, 256);
        mma_pass<144, 3, 256, true>(acc, a, ring, DESC_KV, leader, m0, m1, wg == 0 ? 4 : -1);
#pragma unroll
        for (int c = 0; c < 9; c++) {
          kf[2 * c] = pack_bf16(acc[4 * c] * r0, acc[4 * c + 1] * r0);
          kf[2 * c + 1] = pack_bf16(acc[4 * c + 2] * r1, acc[4 * c + 3] * r1);
          vf[2 * c] = pack_bf16(acc[36 + 4 * c] * r0, acc[36 + 4 * c + 1] * r0);
          vf[2 * c + 1] = pack_bf16(acc[36 + 4 * c + 2] * r1, acc[36 + 4 * c + 3] * r1);
        }
      }
      TS(2 + L * 20);
      const unsigned tag = epoch * 2 + L + 1;
      const uint32_t hs = base + NSLOT * SLOT + wg * 8192 + lane * 8;
      if (w < 3) {
#pragma unroll
        for (int c = 0; c < 9; c++) asm volatile("st.shared.v2.u32 [%0], {%1,%2};" ::"r"(hs + (w * 9 + c) * 256), "r"(kf[2 * c + 1]), "r"(vf[2 * c + 1]) : "memory");
      } else if (rb < 15) {
        uint4* hp = g_halo + ((L * 32 + strm + 2) * 8 + j) * 9 * 32 + lane;
#pragma unroll
        for (int c = 0; c < 9; c++)
          asm volatile("{\n.reg .b64 x, y;\nmov.b64 x, {%1,%3};\nmov.b64 y, {%2,%3};\nst.relaxed.gpu.global.v2.b64 [%0], {x, y};\n}"
                       ::"l"(hp + c * 32), "r"(kf[2 * c + 1]), "r"(vf[2 * c + 1]), "r"(tag) : "memory");
      }
      {
        float acc[36];
        mma_pass<72, 6, 256, false>(acc, a, ring, DESC_Q, leader, 0, 0, -1);
#pragma unroll
        for (int c = 0; c < 9; c++) {
          qf[2 * c] = pack_bf16(acc[4 * c] * r0, acc[4 * c + 1] * r0);
          qf[2 * c + 1] = pack_bf16(acc[4 * c + 2] * r1, acc[4 * c + 3] * r1);
        }
      }
      TS(3 + L * 20);
      {
        uint32_t kh[9], vh[9];
        bar_sync(5 + wg, 128);
        if (w > 0) {
#pragma unroll
          for (int c = 0; c < 9; c++) asm volatile("ld.shared.v2.u32 {%0,%1}, [%2];" : "=r"(kh[c]), "=r"(vh[c]) : "r"(hs + ((w - 1) * 9 + c) * 256) : "memory");
        } else if (rb > 0) {
          const uint4* hp = g_halo + ((L * 32 + strm) * 8 + j) * 9 * 32 + lane;
          unsigned spins = 0;
          while (true) {
            bool ok = true;
#pragma unroll
            for (int c = 0; c < 9; c++) {
              uint32_t t0, t1;
              asm volatile("{\n.reg .b64 x, y;\nld.relaxed.gpu.global.v2.b64 {x, y}, [%4];\nmov.b64 {%0,%2}, x;\nmov.b64 {%1,%3}, y;\n}"
                           : "=r"(kh[c]), "=r"(vh[c]), "=r"(t0), "=r"(t1) : "l"(hp + c * 32) : "memory");
              ok = ok && t0 == tag && t1 == tag;
            }
            if (__all_sync(0xffffffffu, ok)) break;
            if (++spins > 0x100000u) asm volatile("trap;");
          }
        } else {
#pragma unroll
          for (int c = 0; c < 9; c++) kh[c] = vh[c] = 0;
        }
        const bool nohalo = (rb == 0 && w == 0);
        const bool le0 = 2 * q <= g, le1 = 2 * q + 1 <= g;
        const uint32_t M = (le0 ? 0xffffu : 0u) | (le1 ? 0xffff0000u : 0u);
        uint32_t pA[4], pB[4];
        const float sc = 0.23570226039551584f * 1.4426950408889634f;
#pragma unroll
        for (int h = 0; h < 4; h++) {
          const uint32_t qa0 = q >= h ? qf[4 * h] : 0u, qa1 = q >= h ? qf[4 * h + 1] : 0u;
          const uint32_t qc0 = q <= h ? qf[4 * h + 4] : 0u, qc1 = q <= h ? qf[4 * h + 5] : 0u;
          float sm[4] = {0, 0, 0, 0}, s0[4] = {0, 0, 0, 0}, s1[4] = {0, 0, 0, 0};
          mma16816(sm, qa0, qa1, qf[4 * h + 2], qf[4 * h + 3], kh[2 * h], kh[2 * h + 1]);
          mma16816(s0, qa0, qa1, qf[4 * h + 2], qf[4 * h + 3], kf[4 * h], kf[4 * h + 2]);
          mma16816(s1, qa0, qa1, qf[4 * h + 2], qf[4 * h + 3], kf[4 * h + 1], kf[4 * h + 3]);
          mma1688(sm, qc0, qc1, kh[2 * h + 2]);
          mma1688(s0, qc0, qc1, kf[4 * h + 4]);
          mma1688(s1, qc0, qc1, kf[4 * h + 5]);
          float x0 = (le0 ? s0[0] : sm[0]) * sc, x1 = (le1 ? s0[1] : sm[1]) * sc;
          float y0 = (le0 ? s1[2] : s0[2]) * sc, y1 = (le1 ? s1[3] : s0[3]) * sc;
          if (nohalo) { if (!le0) x0 = -1e9f; if (!le1) x1 = -1e9f; }
          const float mx = quad_max(fmaxf(x0, x1)), my = quad_max(fmaxf(y0, y1));
          x0 = exp2f(x0 - mx); x1 = exp2f(x1 - mx); y0 = exp2f(y0 - my); y1 = exp2f(y1 - my);
          const float ix = 1.f / quad_sum(x0 + x1), iy = 1.f / quad_sum(y0 + y1);
          pA[h] = pack_bf16(x0 * ix, x1 * ix);
          pB[h] = pack_bf16(y0 * iy, y1 * iy);
        }
        uint2* op = (uint2*)(g_obuf + strm * 36 * 128 + tid);
#pragma unroll
        for (int c = 0; c < 9; c++) {
          const uint32_t vm = movm_t(vh[c]), v0 = movm_t(vf[2 * c]), v1 = movm_t(vf[2 * c + 1]);
          const int h = c == 8 ? 3 : c >> 1;
          float o[4] = {0, 0, 0, 0};
          mma16816(o, pA[h] & ~M, 0u, pA[h] & M, pB[h] & ~M, vm, v0);
          mma1688(o, 0u, pB[h] & M, v1);
          uint32_t o0 = pack_bf16(o[0], o[1]), o1 = pack_bf16(o[2], o[3]);
          if (c == 2 || c == 4 || c == 6) {
            float e[4] = {0, 0, 0, 0};
            mma16816(e, pA[h - 1] & ~M, 0u, pA[h - 1] & M, pB[h - 1] & ~M, vm, v0);
            mma1688(e, 0u, pB[h - 1] & M, v1);
            if (q < h) { o0 = pack_bf16(e[0], e[1]); o1 = pack_bf16(e[2], e[3]); }
          }
          const int G = j * 9 + c;
          st_cg2(op + (G >> 1) * 256 + (G & 1), o0, o1);
        }
        __syncwarp();
        if (lane == 0) flag_signal(flags + (FL_O + L) * 128 * FSTR);
      }
      TS(4 + L * 20);
      {
        uint32_t xr[18];
        if (L == 0) {
          const uint32_t* xp = (const uint32_t*)(P.x + (size_t)tok0 * DM + j * 72 + 2 * q);
#pragma unroll
          for (int c = 0; c < 9; c++) { xr[2 * c] = __ldg(xp + c * 4); xr[2 * c + 1] = __ldg(xp + 16 * (DM / 2) + c * 4); }
        } else {
          const uint2* xp = (const uint2*)(g_x2buf + strm * 36 * 128 + tid);
#pragma unroll
          for (int c = 0; c < 9; c++) { const int G = j * 9 + c; uint2 v = ld_cg2(xp + (G >> 1) * 256 + (G & 1)); xr[2 * c] = v.x; xr[2 * c + 1] = v.y; }
        }
        if (lane == 0) flag_wait(flags + (FL_O + L) * 128 * FSTR, ftgt);
        __syncwarp();
        TS(5 + L * 20);
        load_frags(a, g_obuf + strm * 36 * 128 + tid);
        float acc[36];
        mma_pass<72, 6, 256, false>(acc, a, ring, DESC_Q, leader, 0, 0, -1);
        TS(6 + L * 20);
        float s10 = 0.f, s20 = 0.f, s11 = 0.f, s21 = 0.f;
        uint2* xo = (uint2*)(g_x1buf + strm * 36 * 128 + tid);
#pragma unroll
        for (int c = 0; c < 9; c++) {
          const uint32_t y0 = bf2_add(xr[2 * c], pack_bf16(acc[4 * c], acc[4 * c + 1]));
          const uint32_t y1 = bf2_add(xr[2 * c + 1], pack_bf16(acc[4 * c + 2], acc[4 * c + 3]));
          const int G = j * 9 + c;
          st_cg2(xo + (G >> 1) * 256 + (G & 1), y0, y1);
          acc_stats(y0, s10, s20); acc_stats(y1, s11, s21);
        }
        store_stats(g_x1st + (strm * 4 + w) * 64, j, g, q, s10, s20, s11, s21);
        __syncwarp();
        if (lane == 0) { flag_signal(flags + (FL_X1 + L) * 128 * FSTR); flag_wait(flags + (FL_X1 + L) * 128 * FSTR, ftgt); }
        __syncwarp();
      }
      TS(7 + L * 20);
      load_stats(g_x1st + (strm * 4 + w) * 64, g, q, m0, m1, r0, r1);
      load_frags(a, g_x1buf + strm * 36 * 128 + tid);
      uint4* const hb = g_hbuf + (size_t)(cta * 2 + wg) * 36 * 128 + tid;
      {
        const float ka0 = 0.7978845608028654f * r0, kb0 = 0.035677408136300125f * r0 * r0 * r0, kc0 = 0.5f * r0 * r0;
        const float ka1 = 0.7978845608028654f * r1, kb1 = 0.035677408136300125f * r1 * r1 * r1, kc1 = 0.5f * r1 * r1;
        float acc[64];
        uint32_t hf[16];
        auto geglu = [&]() {
          float r[32];
#pragma unroll
          for (int e = 0; e < 32; e++) {
            float x = acc[e];
            if (e >= 2) x = __uint_as_float(__float_as_uint(x) ^ (__float_as_uint(r[e - 2]) & P.zero));
            const bool hi = e & 2;
            float t = x * fmaf(x * x, hi ? kb1 : kb0, hi ? ka1 : ka0);
            asm("tanh.approx.f32 %0, %0;" : "+f"(t));
            const float u = x * acc[32 + e] * (hi ? kc1 : kc0);
            r[e] = fmaf(u, t, u);
            if (e & 1) hf[e >> 1] = pack_bf16(r[e - 1], r[e]);
          }
        };
        if (wg == 1) bar_sync(4, 256);
        mma_pass<128, 4, 2048, true>(acc, a, ring, DESC_SW128, leader, m0, m1, 3 + (wg ^ 1));
        TS(8 + L * 20);
#pragma unroll 1
        for (int t = 0; t < 8; t++) {
          geglu();
          if (t < NSTASH) {
#pragma unroll
            for (int i = 0; i < 4; i++)
              asm volatile("st.shared.v4.u32 [%0], {%1,%2,%3,%4};" ::"r"(base + (NSLOT + t) * SLOT + wg * 8192 + i * 2048 + tid * 16),
                           "r"(hf[4 * i]), "r"(hf[4 * i + 1]), "r"(hf[4 * i + 2]), "r"(hf[4 * i + 3]) : "memory");
          } else {
#pragma unroll
            for (int i = 0; i < 4; i++) st_cg4(hb + (t * 4 + i) * 128, hf[4 * i], hf[4 * i + 1], hf[4 * i + 2], hf[4 * i + 3]);
          }
          bar_sync(3 + wg, 256);
          mma_pass<128, 4, 2048, false>(acc, a, ring, DESC_SW128, leader, 0, 0, 3 + (wg ^ 1));
        }
        TS(9 + L * 20);
#pragma unroll
        for (int i = 0; i < 32; i++) {
          uint4 v;
          if (i < NSTASH * 4) asm volatile("ld.shared.v4.u32 {%0,%1,%2,%3}, [%4];" : "=r"(v.x), "=r"(v.y), "=r"(v.z), "=r"(v.w)
                                           : "r"(base + (NSLOT + (i >> 2)) * SLOT + wg * 8192 + (i & 3) * 2048 + tid * 16) : "memory");
          else v = ld_cg4(hb + i * 128);
          a[4 * i] = v.x; a[4 * i + 1] = v.y; a[4 * i + 2] = v.z; a[4 * i + 3] = v.w;
        }
        geglu();
#pragma unroll
        for (int i = 0; i < 16; i++) a[128 + i] = hf[i];
      }
      TS(10 + L * 20);
#pragma unroll 1
      for (int p = 0; p < 5; p++) {
        bar_sync(3 + wg, 256);
        const int nb = (p == 4 && wg == 1) ? -1 : 3 + (wg ^ 1);
        if (p == 2) {
          float acc[32];
          mma_pass<64, 8, 2048, false>(acc, a, ring, DESC_SW128, leader, 0, 0, nb);
#pragma unroll
          for (int i = 0; i < 4; i++)
            st_cg4(hb + (32 + i) * 128, pack_bf16(acc[8 * i], acc[8 * i + 1]), pack_bf16(acc[8 * i + 2], acc[8 * i + 3]),
                   pack_bf16(acc[8 * i + 4], acc[8 * i + 5]), pack_bf16(acc[8 * i + 6], acc[8 * i + 7]));
        } else {
          float acc[64];
          mma_pass<128, 4, 2048, false>(acc, a, ring, DESC_SW128, leader, 0, 0, nb);
          const int pp = p < 2 ? p : p - 1;
#pragma unroll
          for (int i = 0; i < 8; i++)
            st_cg4(hb + (pp * 8 + i) * 128, pack_bf16(acc[8 * i], acc[8 * i + 1]), pack_bf16(acc[8 * i + 2], acc[8 * i + 3]),
                   pack_bf16(acc[8 * i + 4], acc[8 * i + 5]), pack_bf16(acc[8 * i + 6], acc[8 * i + 7]));
        }
      }
      TS(11 + L * 20);
      {
        __syncwarp();
        if (lane == 0) flag_signal(flags + (FL_P + L) * 128 * FSTR);
        uint32_t xr[18];
        {
          const uint4* xp = g_x1buf + strm * 36 * 128 + tid;
#pragma unroll
          for (int p = 0; p < 4; p++) { uint4 v = ld_cg4(xp + (p * 8 + j) * 128); xr[4 * p] = v.x; xr[4 * p + 1] = v.y; xr[4 * p + 2] = v.z; xr[4 * p + 3] = v.w; }
          uint2 v = ld_cg2((const uint2*)(xp + (32 + (j >> 1)) * 128) + (j & 1)); xr[16] = v.x; xr[17] = v.y;
        }
        if (lane == 0) flag_wait(flags + (FL_P + L) * 128 * FSTR, ftgt);
        __syncwarp();
        TS(12 + L * 20);
        const uint4* pb = g_hbuf + (size_t)((cta & ~14) * 2 + wg) * 36 * 128 + tid;
#pragma unroll
        for (int s = 0; s < 8; s++) {
          const uint4* ps = pb + (size_t)s * 4 * 36 * 128;
#pragma unroll
          for (int p = 0; p < 4; p++) { uint4 v = ld_cg4(ps + (p * 8 + j) * 128); a[s * 18 + 4 * p] = v.x; a[s * 18 + 4 * p + 1] = v.y; a[s * 18 + 4 * p + 2] = v.z; a[s * 18 + 4 * p + 3] = v.w; }
          uint2 v = ld_cg2((const uint2*)(ps + (32 + (j >> 1)) * 128) + (j & 1)); a[s * 18 + 16] = v.x; a[s * 18 + 17] = v.y;
        }
#pragma unroll
        for (int i = 0; i < 18; i++) {
          float lo = 0.f, hi = 0.f;
#pragma unroll
          for (int s = 0; s < 8; s++) { lo += bf_lo(a[s * 18 + i]); hi += bf_hi(a[s * 18 + i]); }
          xr[i] = bf2_add(xr[i], pack_bf16(lo, hi));
        }
        if (L == 0) {
          uint4* xo = g_x2buf + strm * 36 * 128 + tid;
#pragma unroll
          for (int p = 0; p < 4; p++) st_cg4(xo + (p * 8 + j) * 128, xr[4 * p], xr[4 * p + 1], xr[4 * p + 2], xr[4 * p + 3]);
          st_cg2((uint2*)(xo + (32 + (j >> 1)) * 128) + (j & 1), xr[16], xr[17]);
          float s10 = 0.f, s20 = 0.f, s11 = 0.f, s21 = 0.f;
#pragma unroll
          for (int i = 0; i < 18; i += 2) { acc_stats(xr[i], s10, s20); acc_stats(xr[i + 1], s11, s21); }
          store_stats(g_x2st + (strm * 4 + w) * 64, j, g, q, s10, s20, s11, s21);
          __syncwarp();
          if (lane == 0) flag_signal(flags + FL_X2 * 128 * FSTR);
        } else {
          uint32_t* op = (uint32_t*)(P.out + (size_t)tok0 * DM) + q;
#pragma unroll
          for (int p = 0; p < 4; p++) {
            const int c = (p * 128 + j * 16) / 2;
            op[c] = xr[4 * p]; op[16 * (DM / 2) + c] = xr[4 * p + 1]; op[c + 4] = xr[4 * p + 2]; op[16 * (DM / 2) + c + 4] = xr[4 * p + 3];
          }
          op[256 + j * 4] = xr[16]; op[16 * (DM / 2) + 256 + j * 4] = xr[17];
        }
      }
      TS(13 + L * 20);
    }
  }
}

typedef CUresult (*EncodeFn)(CUtensorMap*, CUtensorMapDataType, cuuint32_t, void*, const cuuint64_t*, const cuuint64_t*, const cuuint32_t*,
                             const cuuint32_t*, CUtensorMapInterleave, CUtensorMapSwizzle, CUtensorMapL2promotion, CUtensorMapFloatOOBfill);

void encode(EncodeFn fn, CUtensorMap* m, const void* p, int rank, const cuuint64_t* dims, const cuuint64_t* str, const cuuint32_t* box) {
  const cuuint32_t es[3] = {1, 1, 1};
  fn(m, CU_TENSOR_MAP_DATA_TYPE_BFLOAT16, rank, const_cast<void*>(p), dims, str, box, es, CU_TENSOR_MAP_INTERLEAVE_NONE,
     CU_TENSOR_MAP_SWIZZLE_128B, CU_TENSOR_MAP_L2_PROMOTION_L2_256B, CU_TENSOR_MAP_FLOAT_OOB_FILL_NONE);
}

}

extern "C" void kernel_launch(void* const* d_in, const int* in_sizes, int n_in, void* d_out, int out_size) {
  (void)in_sizes; (void)n_in; (void)out_size;
  Params P;
  P.x = (const __nv_bfloat16*)d_in[0]; P.wqkv = (const __nv_bfloat16*)d_in[1]; P.wo = (const __nv_bfloat16*)d_in[2];
  P.wg = (const __nv_bfloat16*)d_in[4]; P.wu = (const __nv_bfloat16*)d_in[5]; P.wd = (const __nv_bfloat16*)d_in[6];
  P.out = (__nv_bfloat16*)d_out; P.zero = 0;
  void* fnp = nullptr; cudaDriverEntryPointQueryResult qr;
  cudaGetDriverEntryPoint("cuTensorMapEncodeTiled", &fnp, cudaEnableDefault, &qr);
  EncodeFn fn = (EncodeFn)fnp;
  CUtensorMap mx, mg, mu, md;
  { const cuuint64_t dims[3] = {DM, 2, SEQ / 2}, str[2] = {DM * 2, DM * 4}; const cuuint32_t box[3] = {64, 1, 64}; encode(fn, &mx, P.x, 3, dims, str, box); }
  { const cuuint64_t dims[2] = {DFF, DM}, str[1] = {DFF * 2}; const cuuint32_t box[2] = {64, 64}; encode(fn, &mg, P.wg, 2, dims, str, box); encode(fn, &mu, P.wu, 2, dims, str, box); }
  { const cuuint64_t dims[2] = {DM, DFF}, str[1] = {DM * 2}; const cuuint32_t box[2] = {64, 64}; encode(fn, &md, P.wd, 2, dims, str, box); }
  cudaFuncSetAttribute(fused_kernel, cudaFuncAttributeMaxDynamicSharedMemorySize, SMEM_BYTES);
  cudaLaunchConfig_t cfg = {};
  cfg.gridDim = dim3(128); cfg.blockDim = dim3(384); cfg.dynamicSmemBytes = SMEM_BYTES; cfg.stream = cudaStreamPerThread;
  cudaLaunchAttribute at[1];
  at[0].id = cudaLaunchAttributeClusterDimension; at[0].val.clusterDim.x = USE_MC ? 2 : 1; at[0].val.clusterDim.y = 1; at[0].val.clusterDim.z = 1;
  cfg.attrs = at; cfg.numAttrs = 1;
  cudaLaunchKernelEx(&cfg, fused_kernel, mx, mg, mu, md, P);
}
```

```cpp
#include <cuda_runtime.h>
#include <cuda_bf16.h>
#include <cuda.h>
#include <stdint.h>

#define TIMING 0

namespace {

constexpr int SEQ = 2048, DM = 576, DFF = 4608;
constexpr uint32_t SB = 1024;
constexpr uint32_t SLOT = 16384;
constexpr uint32_t PSLOT = 13824;
constexpr uint32_t BARS = SB + 14 * SLOT;
constexpr int SMEM_BYTES = 14 * SLOT + 256;
__host__ __device__ constexpr uint32_t slot_addr(int s) { return SB + s * SLOT; }
__host__ __device__ constexpr uint32_t bar_full(int s) { return BARS + 8 * s; }
__host__ __device__ constexpr uint32_t bar_empty(int s) { return BARS + 128 + 8 * s; }
enum { NB_ORD0 = 1, NB_ORD1 = 2, NB_WG = 3  , NB_INIT = 5, NB_P3 = 6  , NB_STA = 8  , NB_RDY = 10   };

constexpr uint32_t TILE = 36 * 2048;
constexpr uint32_t OFF_O = 0, OFF_X1 = TILE  , OFF_X2 = 3 * TILE, OFF_ST = 4 * TILE  ,
                   OFF_P = 4 * TILE + 3 * 4096, STRM = OFF_P + 8 * TILE;
__device__ __align__(1024) uint8_t g_scr[32 * STRM];
__device__ __align__(1024) uint8_t g_wpack[8 * 24 * PSLOT];
__device__ uint4 g_halo[2 * 32 * 8 * 9 * 32];
constexpr int FSTR = 8;
__device__ unsigned g_flags[(8 + 16 + 64) * FSTR];
__device__ unsigned g_epoch[128];

__device__ __forceinline__ uint32_t smem_u32(const void* p) { return (uint32_t)__cvta_generic_to_shared(p); }
__device__ __forceinline__ void mbar_init(uint32_t bar, uint32_t cnt) { asm volatile("mbarrier.init.shared::cta.b64 [%0], %1;" ::"r"(bar), "r"(cnt)); }
__device__ __forceinline__ void mbar_expect_tx(uint32_t bar, uint32_t bytes) { asm volatile("mbarrier.arrive.expect_tx.shared::cta.b64 _, [%0], %1;" ::"r"(bar), "r"(bytes) : "memory"); }
__device__ __forceinline__ void mbar_arrive(uint32_t bar) { asm volatile("mbarrier.arrive.shared::cta.b64 _, [%0];" ::"r"(bar) : "memory"); }
__device__ __forceinline__ void mbar_wait(uint32_t bar, uint32_t parity) {
  asm volatile("{\n.reg .pred p;\nLAB_WAIT:\nmbarrier.try_wait.parity.shared::cta.b64 p, [%0], %1;\n@!p bra LAB_WAIT;\n}" ::"r"(bar), "r"(parity) : "memory");
}
__device__ __forceinline__ void flag_wait(const unsigned* flag, unsigned target) {
  asm volatile("{\n.reg .pred p;\n.reg .u32 v;\nLAB_WAIT:\nld.acquire.gpu.global.u32 v, [%0];\nsub.u32 v, v, %1;\n"
               "setp.lt.s32 p, v, 0;\n@p bra LAB_WAIT;\n}" ::"l"(flag), "r"(target) : "memory");
}
__device__ __forceinline__ void flag_signal(unsigned* flag) { asm volatile("red.release.gpu.global.add.u32 [%0], 1;" ::"l"(flag) : "memory"); }
__device__ __forceinline__ void tma_2d(uint32_t dst, const CUtensorMap* m, int c0, int c1, uint32_t bar) {
  asm volatile("cp.async.bulk.tensor.2d.shared::cluster.global.mbarrier::complete_tx::bytes [%0], [%1, {%3, %4}], [%2];"
               ::"r"(dst), "l"(m), "r"(bar), "r"(c0), "r"(c1) : "memory");
}
__device__ __forceinline__ void tma_3d(uint32_t dst, const CUtensorMap* m, int c0, int c1, int c2, uint32_t bar) {
  asm volatile("cp.async.bulk.tensor.3d.shared::cluster.global.mbarrier::complete_tx::bytes [%0], [%1, {%3, %4, %5}], [%2];"
               ::"r"(dst), "l"(m), "r"(bar), "r"(c0), "r"(c1), "r"(c2) : "memory");
}
__device__ __forceinline__ void bulk_load(uint32_t dst, const void* src, uint32_t bytes, uint32_t bar) {
  asm volatile("cp.async.bulk.shared::cluster.global.mbarrier::complete_tx::bytes [%0], [%1], %2, [%3];" ::"r"(dst), "l"(src), "r"(bytes), "r"(bar) : "memory");
}
__device__ __forceinline__ void l2_prefetch(const void* src, uint32_t bytes) { asm volatile("cp.async.bulk.prefetch.L2.global [%0], %1;" ::"l"(src), "r"(bytes) : "memory"); }
__device__ __forceinline__ void wg_fence() { asm volatile("wgmma.fence.sync.aligned;" ::: "memory"); }
__device__ __forceinline__ void wg_commit() { asm volatile("wgmma.commit_group.sync.aligned;" ::: "memory"); }
template <int N> __device__ __forceinline__ void wg_wait() { asm volatile("wgmma.wait_group.sync.aligned %0;" ::"n"(N) : "memory"); }
__device__ __forceinline__ void bar_sync(int id, int n) { asm volatile("bar.sync %0, %1;" ::"r"(id), "r"(n) : "memory"); }
__device__ __forceinline__ void bar_arrive(int id, int n) { asm volatile("bar.arrive %0, %1;" ::"r"(id), "r"(n) : "memory"); }
__device__ __forceinline__ uint32_t pack_bf16(float lo, float hi) { uint32_t r; asm("cvt.rn.bf16x2.f32 %0, %1, %2;" : "=r"(r) : "f"(hi), "f"(lo)); return r; }
__device__ __forceinline__ float bf_lo(uint32_t w) { return __uint_as_float(w << 16); }
__device__ __forceinline__ float bf_hi(uint32_t w) { return __uint_as_float(w & 0xffff0000u); }
__device__ __forceinline__ float bf_round(float x) { return bf_lo(pack_bf16(x, 0.f)); }
__device__ __forceinline__ uint32_t bf2_sub(uint32_t a, uint32_t b) { uint32_t r; asm("sub.rn.bf16x2 %0, %1, %2;" : "=r"(r) : "r"(a), "r"(b)); return r; }
__device__ __forceinline__ uint32_t bf2_add(uint32_t a, uint32_t b) { uint32_t r; asm("add.rn.bf16x2 %0, %1, %2;" : "=r"(r) : "r"(a), "r"(b)); return r; }
__device__ __forceinline__ void ld16(uint32_t* v, const uint8_t* p) {
  asm volatile("{\n.reg .b64 x, y;\nld.relaxed.gpu.global.v2.b64 {x, y}, [%4];\nmov.b64 {%0,%1}, x;\nmov.b64 {%2,%3}, y;\n}"
               : "=r"(v[0]), "=r"(v[1]), "=r"(v[2]), "=r"(v[3]) : "l"(p) : "memory");
}
__device__ __forceinline__ void ld8(uint32_t* v, const uint8_t* p) {
  asm volatile("{\n.reg .b64 x;\nld.relaxed.gpu.global.b64 x, [%2];\nmov.b64 {%0,%1}, x;\n}" : "=r"(v[0]), "=r"(v[1]) : "l"(p) : "memory");
}
__device__ __forceinline__ void st16(uint8_t* p, uint32_t a, uint32_t b, uint32_t c, uint32_t d) {
  asm volatile("{\n.reg .b64 x, y;\nmov.b64 x, {%1,%2};\nmov.b64 y, {%3,%4};\nst.relaxed.gpu.global.v2.b64 [%0], {x, y};\n}"
               ::"l"(p), "r"(a), "r"(b), "r"(c), "r"(d) : "memory");
}
__device__ __forceinline__ void st8(uint8_t* p, uint32_t a, uint32_t b) {
  asm volatile("{\n.reg .b64 x;\nmov.b64 x, {%1,%2};\nst.relaxed.gpu.global.b64 [%0], x;\n}" ::"l"(p), "r"(a), "r"(b) : "memory");
}
__device__ __forceinline__ uint32_t nz(uint32_t w) { return max(w, 1u); }
__device__ __forceinline__ void bb_cut(uint32_t zero) { asm volatile("{\n.reg .pred p;\nLAB_BB:\nsetp.ne.u32 p, %0, 0;\n@p bra LAB_BB;\n}" ::"r"(zero) : "memory"); }
__device__ __forceinline__ void mma16816(float (&c)[4], uint32_t a0, uint32_t a1, uint32_t a2, uint32_t a3, uint32_t b0, uint32_t b1) {
  asm volatile("mma.sync.aligned.m16n8k16.row.col.f32.bf16.bf16.f32 {%0,%1,%2,%3}, {%4,%5,%6,%7}, {%8,%9}, {%0,%1,%2,%3};"
               : "+f"(c[0]), "+f"(c[1]), "+f"(c[2]), "+f"(c[3]) : "r"(a0), "r"(a1), "r"(a2), "r"(a3), "r"(b0), "r"(b1));
}
__device__ __forceinline__ void mma1688(float (&c)[4], uint32_t a0, uint32_t a1, uint32_t b0) {
  asm volatile("mma.sync.aligned.m16n8k8.row.col.f32.bf16.bf16.f32 {%0,%1,%2,%3}, {%4,%5}, {%6}, {%0,%1,%2,%3};"
               : "+f"(c[0]), "+f"(c[1]), "+f"(c[2]), "+f"(c[3]) : "r"(a0), "r"(a1), "r"(b0));
}
__device__ __forceinline__ uint32_t movm_t(uint32_t a) { uint32_t d; asm volatile("movmatrix.sync.aligned.m8n8.trans.b16 %0, %1;" : "=r"(d) : "r"(a)); return d; }
__device__ __forceinline__ float ex2(float x) { float r; asm("ex2.approx.ftz.f32 %0, %1;" : "=f"(r) : "f"(x)); return r; }
__device__ __forceinline__ float quad_sum(float v) { v += __shfl_xor_sync(0xffffffffu, v, 1); v += __shfl_xor_sync(0xffffffffu, v, 2); return v; }
__device__ __forceinline__ float quad_max(float v) { v = fmaxf(v, __shfl_xor_sync(0xffffffffu, v, 1)); v = fmaxf(v, __shfl_xor_sync(0xffffffffu, v, 2)); return v; }

__device__ __forceinline__ void wgmma_rs_n64(float (&d)[32], uint32_t a0, uint32_t a1, uint32_t a2, uint32_t a3, uint64_t desc, int scale_d) {
  asm volatile("{\n.reg .pred p;\nsetp.ne.b32 p, %37, 0;\n"
    "wgmma.mma_async.sync.aligned.m64n64k16.f32.bf16.bf16 "
    "{%0, %1, %2, %3, %4, %5, %6, %7, %8, %9, %10, %11, %12, %13, %14, %15, %16, %17, %18, %19, %20, %21, %22, %23, %24, %25, %26, %27, %28, %29, %30, %31}, "
    "{%32, %33, %34, %35}, %36, p, 1, 1, 1;\n}\n"
    : "+f"(d[0]), "+f"(d[1]), "+f"(d[2]), "+f"(d[3]), "+f"(d[4]), "+f"(d[5]), "+f"(d[6]), "+f"(d[7]), "+f"(d[8]), "+f"(d[9]), "+f"(d[10]), "+f"(d[11]), "+f"(d[12]), "+f"(d[13]), "+f"(d[14]), "+f"(d[15]), "+f"(d[16]), "+f"(d[17]), "+f"(d[18]), "+f"(d[19]), "+f"(d[20]), "+f"(d[21]), "+f"(d[22]), "+f"(d[23]), "+f"(d[24]), "+f"(d[25]), "+f"(d[26]), "+f"(d[27]), "+f"(d[28]), "+f"(d[29]), "+f"(d[30]), "+f"(d[31])
    : "r"(a0), "r"(a1), "r"(a2), "r"(a3), "l"(desc), "r"(scale_d));
}

__device__ __forceinline__ void wgmma_rs_n72(float (&d)[36], uint32_t a0, uint32_t a1, uint32_t a2, uint32_t a3, uint64_t desc, int scale_d) {
  asm volatile("{\n.reg .pred p;\nsetp.ne.b32 p, %41, 0;\n"
    "wgmma.mma_async.sync.aligned.m64n72k16.f32.bf16.bf16 "
    "{%0, %1, %2, %3, %4, %5, %6, %7, %8, %9, %10, %11, %12, %13, %14, %15, %16, %17, %18, %19, %20, %21, %22, %23, %24, %25, %26, %27, %28, %29, %30, %31, %32, %33, %34, %35}, "
    "{%36, %37, %38, %39}, %40, p, 1, 1, 1;\n}\n"
    : "+f"(d[0]), "+f"(d[1]), "+f"(d[2]), "+f"(d[3]), "+f"(d[4]), "+f"(d[5]), "+f"(d[6]), "+f"(d[7]), "+f"(d[8]), "+f"(d[9]), "+f"(d[10]), "+f"(d[11]), "+f"(d[12]), "+f"(d[13]), "+f"(d[14]), "+f"(d[15]), "+f"(d[16]), "+f"(d[17]), "+f"(d[18]), "+f"(d[19]), "+f"(d[20]), "+f"(d[21]), "+f"(d[22]), "+f"(d[23]), "+f"(d[24]), "+f"(d[25]), "+f"(d[26]), "+f"(d[27]), "+f"(d[28]), "+f"(d[29]), "+f"(d[30]), "+f"(d[31]), "+f"(d[32]), "+f"(d[33]), "+f"(d[34]), "+f"(d[35])
    : "r"(a0), "r"(a1), "r"(a2), "r"(a3), "l"(desc), "r"(scale_d));
}

__device__ __forceinline__ void wgmma_rs_n128(float (&d)[64], uint32_t a0, uint32_t a1, uint32_t a2, uint32_t a3, uint64_t desc, int scale_d) {
  asm volatile("{\n.reg .pred p;\nsetp.ne.b32 p, %69, 0;\n"
    "wgmma.mma_async.sync.aligned.m64n128k16.f32.bf16.bf16 "
    "{%0, %1, %2, %3, %4, %5, %6, %7, %8, %9, %10, %11, %12, %13, %14, %15, %16, %17, %18, %19, %20, %21, %22, %23, %24, %25, %26, %27, %28, %29, %30, %31, %32, %33, %34, %35, %36, %37, %38, %39, %40, %41, %42, %43, %44, %45, %46, %47, %48, %49, %50, %51, %52, %53, %54, %55, %56, %57, %58, %59, %60, %61, %62, %63}, "
    "{%64, %65, %66, %67}, %68, p, 1, 1, 1;\n}\n"
    : "+f"(d[0]), "+f"(d[1]), "+f"(d[2]), "+f"(d[3]), "+f"(d[4]), "+f"(d[5]), "+f"(d[6]), "+f"(d[7]), "+f"(d[8]), "+f"(d[9]), "+f"(d[10]), "+f"(d[11]), "+f"(d[12]), "+f"(d[13]), "+f"(d[14]), "+f"(d[15]), "+f"(d[16]), "+f"(d[17]), "+f"(d[18]), "+f"(d[19]), "+f"(d[20]), "+f"(d[21]), "+f"(d[22]), "+f"(d[23]), "+f"(d[24]), "+f"(d[25]), "+f"(d[26]), "+f"(d[27]), "+f"(d[28]), "+f"(d[29]), "+f"(d[30]), "+f"(d[31]), "+f"(d[32]), "+f"(d[33]), "+f"(d[34]), "+f"(d[35]), "+f"(d[36]), "+f"(d[37]), "+f"(d[38]), "+f"(d[39]), "+f"(d[40]), "+f"(d[41]), "+f"(d[42]), "+f"(d[43]), "+f"(d[44]), "+f"(d[45]), "+f"(d[46]), "+f"(d[47]), "+f"(d[48]), "+f"(d[49]), "+f"(d[50]), "+f"(d[51]), "+f"(d[52]), "+f"(d[53]), "+f"(d[54]), "+f"(d[55]), "+f"(d[56]), "+f"(d[57]), "+f"(d[58]), "+f"(d[59]), "+f"(d[60]), "+f"(d[61]), "+f"(d[62]), "+f"(d[63])
    : "r"(a0), "r"(a1), "r"(a2), "r"(a3), "l"(desc), "r"(scale_d));
}

__device__ __forceinline__ void wgmma_rs_n144(float (&d)[72], uint32_t a0, uint32_t a1, uint32_t a2, uint32_t a3, uint64_t desc, int scale_d) {
  asm volatile("{\n.reg .pred p;\nsetp.ne.b32 p, %77, 0;\n"
    "wgmma.mma_async.sync.aligned.m64n144k16.f32.bf16.bf16 "
    "{%0, %1, %2, %3, %4, %5, %6, %7, %8, %9, %10, %11, %12, %13, %14, %15, %16, %17, %18, %19, %20, %21, %22, %23, %24, %25, %26, %27, %28, %29, %30, %31, %32, %33, %34, %35, %36, %37, %38, %39, %40, %41, %42, %43, %44, %45, %46, %47, %48, %49, %50, %51, %52, %53, %54, %55, %56, %57, %58, %59, %60, %61, %62, %63, %64, %65, %66, %67, %68, %69, %70, %71}, "
    "{%72, %73, %74, %75}, %76, p, 1, 1, 1;\n}\n"
    : "+f"(d[0]), "+f"(d[1]), "+f"(d[2]), "+f"(d[3]), "+f"(d[4]), "+f"(d[5]), "+f"(d[6]), "+f"(d[7]), "+f"(d[8]), "+f"(d[9]), "+f"(d[10]), "+f"(d[11]), "+f"(d[12]), "+f"(d[13]), "+f"(d[14]), "+f"(d[15]), "+f"(d[16]), "+f"(d[17]), "+f"(d[18]), "+f"(d[19]), "+f"(d[20]), "+f"(d[21]), "+f"(d[22]), "+f"(d[23]), "+f"(d[24]), "+f"(d[25]), "+f"(d[26]), "+f"(d[27]), "+f"(d[28]), "+f"(d[29]), "+f"(d[30]), "+f"(d[31]), "+f"(d[32]), "+f"(d[33]), "+f"(d[34]), "+f"(d[35]), "+f"(d[36]), "+f"(d[37]), "+f"(d[38]), "+f"(d[39]), "+f"(d[40]), "+f"(d[41]), "+f"(d[42]), "+f"(d[43]), "+f"(d[44]), "+f"(d[45]), "+f"(d[46]), "+f"(d[47]), "+f"(d[48]), "+f"(d[49]), "+f"(d[50]), "+f"(d[51]), "+f"(d[52]), "+f"(d[53]), "+f"(d[54]), "+f"(d[55]), "+f"(d[56]), "+f"(d[57]), "+f"(d[58]), "+f"(d[59]), "+f"(d[60]), "+f"(d[61]), "+f"(d[62]), "+f"(d[63]), "+f"(d[64]), "+f"(d[65]), "+f"(d[66]), "+f"(d[67]), "+f"(d[68]), "+f"(d[69]), "+f"(d[70]), "+f"(d[71])
    : "r"(a0), "r"(a1), "r"(a2), "r"(a3), "l"(desc), "r"(scale_d));
}

template <int N> struct WG;
template <> struct WG<64>  { static __device__ __forceinline__ void f(float (&d)[32], const uint32_t* a, uint64_t ds, int s) { wgmma_rs_n64(d, a[0], a[1], a[2], a[3], ds, s); } };
template <> struct WG<72>  { static __device__ __forceinline__ void f(float (&d)[36], const uint32_t* a, uint64_t ds, int s) { wgmma_rs_n72(d, a[0], a[1], a[2], a[3], ds, s); } };
template <> struct WG<128> { static __device__ __forceinline__ void f(float (&d)[64], const uint32_t* a, uint64_t ds, int s) { wgmma_rs_n128(d, a[0], a[1], a[2], a[3], ds, s); } };
template <> struct WG<144> { static __device__ __forceinline__ void f(float (&d)[72], const uint32_t* a, uint64_t ds, int s) { wgmma_rs_n144(d, a[0], a[1], a[2], a[3], ds, s); } };

constexpr uint64_t DESC_SW128 = ((uint64_t)(8192 >> 4) << 16) | ((uint64_t)(1024 >> 4) << 32) | (1ull << 62);
constexpr uint64_t DESC_KV = ((uint64_t)(128 >> 4) << 16) | ((uint64_t)(768 >> 4) << 32);
constexpr uint64_t DESC_Q = ((uint64_t)(128 >> 4) << 16) | ((uint64_t)(1536 >> 4) << 32);

enum { PS_KV, PS_Q, PS_WO, PS_FF };
template <int PS> __host__ __device__ constexpr int pass_slot(int i) {
  return PS == PS_KV ? (i < 3 ? 9 + i : i - 3) : PS == PS_WO ? 6 + i : i;
}

template <int N, int PS, int KPS, int KSTEP, uint64_t DESC, bool CHK, bool SUB>
__device__ __forceinline__ void mma_pass(float (&acc)[N / 2], uint32_t (&a)[144], uint32_t par, bool leader, int bar_id,
                                         const uint8_t* src = nullptr, uint32_t nochk = 0, uint32_t m0 = 0, uint32_t m1 = 0, uint32_t zero = 0) {
  constexpr int NS = 36 / KPS;
#pragma unroll
  for (int s = 0; s < NS; s++) {
    const int sl = pass_slot<PS>(s);
    if (CHK) {
      while (true) {
        uint32_t m = 0xffffffffu;
#pragma unroll
        for (int i = s * KPS; i < (s + 1) * KPS; i++) m = min(m, min(a[4 * i], a[4 * i + 2]));
        if (!__any_sync(0xffffffffu, (m | nochk) == 0)) break;
#pragma unroll
        for (int i = s * KPS; i < (s + 1) * KPS; i++) ld16(&a[4 * i], src + i * 2048);
      }
    }
    if (SUB) {
#pragma unroll
      for (int i = s * KPS * 4; i < (s + 1) * KPS * 4; i += 2) { a[i] = bf2_sub(a[i], m0); a[i + 1] = bf2_sub(a[i + 1], m1); }
    }
    mbar_wait(bar_full(sl), sl < 9 ? par : par ^ 1);
    wg_fence();
#pragma unroll
    for (int kk = 0; kk < KPS; kk++)
      WG<N>::f(acc, &a[(s * KPS + kk) * 4], DESC | (uint64_t)((slot_addr(sl) + kk * KSTEP) >> 4), (s | kk) ? 1 : 0);
    wg_commit();
    if (s == NS - 1 && bar_id >= 0) bar_arrive(bar_id, 256);
    if (s > 0) {
      wg_wait<1>();
      if (!(PS == PS_WO && s > 3) && leader) mbar_arrive(bar_empty(pass_slot<PS>(s - 1)));
    }
    if (PS == PS_KV && s == 1) {
#pragma unroll
      for (int i = 0; i < 4; i++) asm volatile("xor.b32 %0, %1, %2;" : "=r"(a[i]) : "r"(a[i]), "r"(zero));
    }
  }
  wg_wait<0>();
  if (PS != PS_WO && leader) mbar_arrive(bar_empty(pass_slot<PS>(NS - 1)));
}

__device__ __forceinline__ void load_frags(uint32_t (&a)[144], const uint8_t* p) {
#pragma unroll
  for (int i = 0; i < 36; i++) ld16(&a[4 * i], p + i * 2048);
}
__device__ __forceinline__ void ln_scalars(float s1, float s2, uint32_t& m, float& rstd) {
  const float mean = s1 * (1.f / DM);
  const float var = fmaxf(s2 * (1.f / DM) - mean * mean, 0.f);
  m = pack_bf16(mean, mean);
  float sd; asm("sqrt.approx.f32 %0, %1;" : "=f"(sd) : "f"(bf_round(bf_round(var) + 1e-5f)));
  rstd = __fdividef(1.f, bf_round(sd));
}
__device__ __forceinline__ void gather_ln(uint32_t (&a)[144], const uint8_t* frags, const uint8_t* st, uint32_t& m0, uint32_t& m1, float& r0, float& r1) {
  uint32_t u[4], v[4];
  do { ld16(u, st); ld16(v, st + 512); } while (__any_sync(0xffffffffu, min(min(u[0], u[2]), min(v[0], v[2])) == 0));
  load_frags(a, frags);
  const float a2 = quad_sum(__uint_as_float(u[0]) + __uint_as_float(u[2])), a1 = quad_sum(__uint_as_float(u[1]) + __uint_as_float(u[3]));
  const float b2 = quad_sum(__uint_as_float(v[0]) + __uint_as_float(v[2])), b1 = quad_sum(__uint_as_float(v[1]) + __uint_as_float(v[3]));
  ln_scalars(a1, a2, m0, r0); ln_scalars(b1, b2, m1, r1);
}
struct Stats {
  float s[4] = {0, 0, 0, 0}, d0[4] = {0, 0, 0, 0}, d1[4] = {0, 0, 0, 0};
  __device__ __forceinline__ void add16(const uint32_t* f) {
    mma16816(s, f[0], f[1], f[2], f[3], 0x3f803f80u, 0x3f803f80u);
    mma16816(d0, f[0], f[1], f[2], f[3], f[0], f[2]);
    mma16816(d1, f[0], f[1], f[2], f[3], f[1], f[3]);
  }
  __device__ __forceinline__ void add8(const uint32_t* f) {
    mma1688(s, f[0], f[1], 0x3f803f80u); mma1688(d0, f[0], f[1], f[0]); mma1688(d1, f[0], f[1], f[1]);
  }
  __device__ __forceinline__ float sq0(int g) const { return (g & 1) ? d0[1] : d0[0]; }
  __device__ __forceinline__ float sq1(int g) const { return (g & 1) ? d1[3] : d1[2]; }
};
__device__ __forceinline__ void store_stats18(const uint32_t (&y)[18], uint8_t* st  , int g, int q) {
  Stats t;
#pragma unroll
  for (int i = 0; i < 4; i++) t.add16(&y[4 * i]);
  t.add8(&y[16]);
  if (q == (g >> 1)) {
    st8(st, __float_as_uint(t.sq0(g)) | 1u, __float_as_uint(t.s[0]));
    st8(st + 512, __float_as_uint(t.sq1(g)) | 1u, __float_as_uint(t.s[2]));
  }
}

#define TS(i) do {} while (0)

struct Params {
  const __nv_bfloat16 *x, *wqkv, *wo, *wg, *wu, *wd;
  __nv_bfloat16* out;
  unsigned zero, zero2;
};

__device__ __forceinline__ void fill_packed(int sl, uint32_t par, const uint8_t* src) {
  mbar_wait(bar_empty(sl), par);
  mbar_expect_tx(bar_full(sl), PSLOT);
  bulk_load(slot_addr(sl), src, PSLOT, bar_full(sl));
}

__global__ void __launch_bounds__(384, 1)
fused_kernel(const __grid_constant__ CUtensorMap map_x, const __grid_constant__ CUtensorMap map_wg,
             const __grid_constant__ CUtensorMap map_wu, const __grid_constant__ CUtensorMap map_wd, const Params P) {
  extern __shared__ __align__(1024) uint8_t smem_raw[];
  const int wg = __shfl_sync(0xffffffffu, threadIdx.x >> 7, 0);
  const int cta = blockIdx.x, j = cta & 7, rb = cta >> 3;
  uint4 pk[4];
  const int pk_k = rb * 36 + threadIdx.x / 9, pk_u = threadIdx.x % 9;
  if (threadIdx.x < 324) {
    const uint4* s = (const uint4*)(P.wqkv + pk_k * 1728 + j * 72 + pk_u * 8);
    pk[1] = __ldg(s + 72); pk[2] = __ldg(s + 144); pk[0] = __ldg(s);
    pk[3] = __ldg((const uint4*)(P.wo + pk_k * 576 + j * 72 + pk_u * 8));
  }
  const unsigned epoch = __shfl_sync(0xffffffffu, *(volatile unsigned*)&g_epoch[cta], 0);
  if (threadIdx.x == 352) {
    if (smem_u32(smem_raw) != SB) asm volatile("trap;");
#pragma unroll 1
    for (int i = 0; i < 13; i++) { mbar_init(bar_full(i), 1); mbar_init(bar_empty(i), 2); }
    asm volatile("fence.proxy.async.shared::cta;" ::: "memory");
#pragma unroll 1
    for (int c = 0; c < 9; c++) {
      mbar_expect_tx(bar_full(c), SLOT);
      tma_3d(slot_addr(c), &map_x, c * 64, 0, rb * 64, bar_full(c));
      tma_3d(slot_addr(c) + 8192, &map_x, c * 64, 1, rb * 64, bar_full(c));
    }
  }
  {
    uint8_t* z = g_scr + rb * 2 * STRM + j * 9216;
#pragma unroll
    for (int i = 0; i < 6; i++) {
      const int e = threadIdx.x + i * 384, pc = e / 576;
      st16(z + (pc >> 1) * STRM + (pc & 1) * TILE + (e - pc * 576) * 16, 0, 0, 0, 0);
    }
    if (threadIdx.x < 64) st16(g_scr + (rb * 2 + (threadIdx.x >> 5)) * STRM + OFF_ST + j * 512 + (threadIdx.x & 31) * 16, 0, 0, 0, 0);
  }
  if (threadIdx.x < 324) {
    uint8_t* d = g_wpack + j * 24 * PSLOT;
    uint8_t* dkv = d + (pk_k / 48) * PSLOT + pk_u * 768 + (pk_k % 48) * 16;
    uint8_t* dq = d + (12 + pk_k / 96) * PSLOT + pk_u * 1536 + (pk_k % 96) * 16;
    st16(dkv, pk[1].x, pk[1].y, pk[1].z, pk[1].w);
    st16(dkv + 9 * 768, pk[2].x, pk[2].y, pk[2].z, pk[2].w);
    st16(dq, pk[0].x, pk[0].y, pk[0].z, pk[0].w);
    st16(dq + 6 * PSLOT, pk[3].x, pk[3].y, pk[3].z, pk[3].w);
    asm volatile("fence.proxy.async.global;" ::: "memory");
  }
  __syncthreads();

  if (wg == 2) {
    asm volatile("setmaxnreg.dec.sync.aligned.u32 24;");
    const int pw = (threadIdx.x >> 5) & 3, lane = threadIdx.x & 31;
    if (pw == 0) {
      if (lane == 0) {
        asm volatile("fence.acq_rel.gpu;" ::: "memory");
        asm volatile("red.relaxed.gpu.global.add.u32 [%0], 1;" ::"l"(&g_flags[j * FSTR]) : "memory");
        asm volatile("red.relaxed.gpu.global.add.u32 [%0], 1;" ::"l"(&g_flags[(8 + rb) * FSTR]) : "memory");
        flag_wait(&g_flags[j * FSTR], (epoch + 1) * 16);
        asm volatile("fence.proxy.async.global;" ::: "memory");
        const uint8_t* wp = g_wpack + j * 24 * PSLOT;
#pragma unroll 1
        for (int s = 0; s < 3; s++) fill_packed(9 + s, 1, wp + s * PSLOT);
        flag_wait(&g_flags[(8 + rb) * FSTR], (epoch + 1) * 8);
#pragma unroll 1
        for (int L = 0; L < 2; L++) {
#pragma unroll 1
          for (int s = 0; s < 21; s++) {
            const int sl = s < 12 ? s : s - 12;
            fill_packed(sl, s >= 12, wp + (s < 9 ? s + 3 : s < 12 ? s + 12 : s) * PSLOT);
          }
#pragma unroll 1
          for (int t = 0; t < 14; t++) {
            const int p = t - 9;
            const CUtensorMap* ma = p < 0 ? &map_wg : &map_wd;
            const CUtensorMap* mb = p < 0 ? &map_wu : &map_wd;
            const int ca = p < 0 ? j * 576 + t * 64 : p == 2 ? 512 : (p < 2 ? p : p - 1) * 128;
            const int cb = p < 0 ? ca : ca + 64, r0 = p < 0 ? 0 : j * 576;
#pragma unroll 1
            for (int k = 0; k < 9; k++) {
              mbar_wait(bar_empty(k), t & 1);
              mbar_expect_tx(bar_full(k), p == 2 ? 8192 : SLOT);
              tma_2d(slot_addr(k), ma, ca, r0 + k * 64, bar_full(k));
              if (p != 2) tma_2d(slot_addr(k) + 8192, mb, cb, r0 + k * 64, bar_full(k));
            }
            if (p == 1 && L == 0) {
#pragma unroll 1
              for (int s = 0; s < 3; s++) fill_packed(9 + s, 1, wp + s * PSLOT);
            }
          }
        }
        g_epoch[cta] = epoch + 1;
      }
    } else if (pw < 3) {
      const int hw = pw - 1, strm = rb * 2 + hw;
      uint8_t* sp = g_scr + strm * STRM + lane * 16;
#pragma unroll 1
      for (int L = 0; L < 2; L++) {
        bar_sync(NB_P3 + hw, 160);
#pragma unroll 1
        for (int i = 0; i < 32; i++) st16(sp + OFF_P + j * TILE + 24 * 2048 + i * 512, 0, 0, 0, 0);
        if (L == 0) {
#pragma unroll 1
          for (int i = 0; i < 18; i++) {
            st16(sp + OFF_O + j * 9216 + i * 512, 0, 0, 0, 0);
            st16(sp + OFF_X1 + TILE + j * 9216 + i * 512, 0, 0, 0, 0);
            st16(sp + OFF_X2 + j * 9216 + i * 512, 0, 0, 0, 0);
          }
          st16(sp + OFF_ST + 4096 + j * 1024, 0, 0, 0, 0);
          st16(sp + OFF_ST + 4096 + j * 1024 + 512, 0, 0, 0, 0);
        }
        bar_sync(NB_STA + hw, 160);
        if (lane == 0) {
          unsigned* f = &g_flags[(24 + L * 32 + strm) * FSTR];
          flag_signal(f);
          flag_wait(f, (epoch + 1) * 8);
        }
        __syncwarp();
        bar_arrive(NB_RDY + hw, 160);
      }
    } else {
#pragma unroll 1
      for (int i = lane; i < 108; i += 32) {
        const __nv_bfloat16* w = i < 72 ? ((i & 1) ? P.wu : P.wg) + (rb * 36 + (i >> 1)) * DFF + j * 576 : P.wd + (j * 576 + rb * 36 + i - 72) * DM;
        l2_prefetch(w, 1152);
      }
      if (lane == 0)
        asm volatile("{\n.reg .pred p;\n.reg .u64 t0, t1;\nmov.u64 t0, %%globaltimer;\nLAB_WD:\n"
                     "mbarrier.try_wait.parity.shared::cta.b64 p, [%0], 0, 100000;\n@p bra LAB_OK;\n"
                     "mov.u64 t1, %%globaltimer;\nsub.u64 t1, t1, t0;\nsetp.lt.u64 p, t1, 2000000000;\n@p bra LAB_WD;\ntrap;\nLAB_OK:\n}"
                     ::"r"(bar_empty(12)) : "memory");
    }
  } else {
    asm volatile("setmaxnreg.inc.sync.aligned.u32 240;");
    const int tid = threadIdx.x & 127, w = tid >> 5, lane = tid & 31, g = lane >> 2, q = lane & 3;
    const bool leader = tid == 0;
    const int strm = rb * 2 + wg;
    uint8_t* const sp = g_scr + strm * STRM + tid * 16;
    const int st_rd = OFF_ST + w * 1024 + g * 64 + q * 16 - tid * 16;
    const int st_wr = OFF_ST + w * 1024 + g * 64 + j * 8 - tid * 16;
    const int tok0 = rb * 128 + 2 * (w * 16 + g) + wg;
    uint32_t a[144];
    TS(0);
#pragma unroll 1
    for (int L = 0; L < 2; L++) {
      uint32_t m0, m1; float r0, r1;
      if (L == 0) {
        Stats t;
        const int row = w * 16 + (lane & 15);
        const uint32_t ra = SB + wg * 8192 + row * 128;
#pragma unroll
        for (int c = 0; c < 9; c++) {
          mbar_wait(bar_full(c), 0);
#pragma unroll
          for (int kk = 0; kk < 4; kk++) {
            const int i = c * 16 + kk * 4;
            asm volatile("ldmatrix.sync.aligned.m8n8.x4.shared.b16 {%0,%1,%2,%3}, [%4];"
                         : "=r"(a[i]), "=r"(a[i + 1]), "=r"(a[i + 2]), "=r"(a[i + 3])
                         : "r"(ra + (((kk * 2 + (lane >> 4)) ^ (row & 7)) << 4) + c * SLOT) : "memory");
          }
#pragma unroll
          for (int kk = 0; kk < 4; kk++) t.add16(&a[c * 16 + kk * 4]);
          if (c % 3 == 2) {
            bar_sync(NB_WG + wg, 128);
            if (leader) { mbar_arrive(bar_empty(c - 2)); mbar_arrive(bar_empty(c - 1)); mbar_arrive(bar_empty(c)); }
          }
        }
        const int dl = (lane & ~3) | (g >> 1);
        ln_scalars(t.s[0], __shfl_sync(0xffffffffu, t.sq0(g), dl), m0, r0);
        ln_scalars(t.s[2], __shfl_sync(0xffffffffu, t.sq1(g), dl), m1, r1);
      } else {
        gather_ln(a, sp + OFF_X2, sp + st_rd + 8192, m0, m1, r0, r1);
      }
      TS(1 + L * 20);
      uint32_t kf[18], vf[18], qf[18];
      {
        float acc[72];
        if (wg == 1) bar_sync(NB_ORD1, 256);
        mma_pass<144, PS_KV, 3, 256, DESC_KV, true, true>(acc, a, 1, leader, wg == 0 ? NB_ORD1 : -1, sp + OFF_X2, L ^ 1, m0, m1, P.zero);
#pragma unroll
        for (int c = 0; c < 9; c++) {
          kf[2 * c] = pack_bf16(acc[4 * c] * r0, acc[4 * c + 1] * r0);
          kf[2 * c + 1] = pack_bf16(acc[4 * c + 2] * r1, acc[4 * c + 3] * r1);
          vf[2 * c] = pack_bf16(acc[36 + 4 * c] * r0, acc[36 + 4 * c + 1] * r0);
          vf[2 * c + 1] = pack_bf16(acc[36 + 4 * c + 2] * r1, acc[36 + 4 * c + 3] * r1);
        }
      }
      TS(2 + L * 20);
      const unsigned tag = epoch * 2 + L + 1;
      const uint32_t hs = slot_addr(13) + wg * 8192 + w * 2304 + lane * 8;
      uint8_t* const hp = (uint8_t*)(g_halo + ((L * 32 + strm) * 8 + j) * 9 * 32 + lane);
      if (w < 3) {
#pragma unroll
        for (int c = 0; c < 9; c++) asm volatile("st.shared.v2.u32 [%0], {%1,%2};" ::"r"(hs + c * 256), "r"(kf[2 * c + 1]), "r"(vf[2 * c + 1]) : "memory");
      } else if (rb < 15) {
#pragma unroll
        for (int c = 0; c < 9; c++) st16(hp + 2 * 8 * 9 * 512 + c * 512, kf[2 * c + 1], tag, vf[2 * c + 1], tag);
      }
      {
        float acc[36];
#pragma unroll
        for (int i = 0; i < 4; i++) asm volatile("xor.b32 %0, %1, %2;" : "=r"(a[i]) : "r"(a[i]), "r"(P.zero2));
        mma_pass<72, PS_Q, 6, 256, DESC_Q, false, false>(acc, a, 0, leader, -1);
#pragma unroll
        for (int c = 0; c < 9; c++) {
          qf[2 * c] = pack_bf16(acc[4 * c] * r0, acc[4 * c + 1] * r0);
          qf[2 * c + 1] = pack_bf16(acc[4 * c + 2] * r1, acc[4 * c + 3] * r1);
        }
      }
      TS(3 + L * 20);
      uint8_t* const own_e = sp + ((j * 9) >> 1) * 2048 + (j & 1) * 8;
      uint8_t* const own_o = sp + ((j * 9 + 1) >> 1) * 2048 + ((j & 1) ^ 1) * 8;
      uint32_t xr[18];
      {
        uint32_t kh[9], vh[9];
        bar_sync(NB_WG + wg, 128);
        if (w > 0) {
#pragma unroll
          for (int c = 0; c < 9; c++) asm volatile("ld.shared.v2.u32 {%0,%1}, [%2];" : "=r"(kh[c]), "=r"(vh[c]) : "r"(hs - 2304 + c * 256) : "memory");
        } else if (rb > 0) {
          bool bad;
          do {
            bad = false;
#pragma unroll
            for (int c = 0; c < 9; c++) {
              uint32_t v[4];
              ld16(v, hp + c * 512);
              kh[c] = v[0]; vh[c] = v[2];
              bad = bad || v[1] != tag || v[3] != tag;
            }
          } while (__any_sync(0xffffffffu, bad));
        } else {
#pragma unroll
          for (int c = 0; c < 9; c++) kh[c] = vh[c] = 0;
        }
        if (L == 0) {
          const uint32_t* xp = (const uint32_t*)(P.x + tok0 * DM + j * 72 + 2 * q);
#pragma unroll
          for (int c = 0; c < 9; c++) { xr[2 * c] = __ldg(xp + c * 4); xr[2 * c + 1] = __ldg(xp + 16 * (DM / 2) + c * 4); }
        } else {
#pragma unroll
          for (int c = 0; c < 9; c++) ld8(&xr[2 * c], ((c & 1) ? own_o : own_e) + OFF_X2 + (c >> 1) * 2048);
        }
        TS(14 + L * 20);
        const bool nohalo = (rb == 0 && w == 0);
        const bool le0 = 2 * q <= g, le1 = 2 * q + 1 <= g;
        const uint32_t M = (le0 ? 0xffffu : 0u) | (le1 ? 0xffff0000u : 0u);
        uint32_t pA[4], pB[4];
        const float sc = 0.23570226039551584f * 1.4426950408889634f;
#pragma unroll
        for (int h = 0; h < 4; h++) {
          const uint32_t qa0 = q >= h ? qf[4 * h] : 0u, qa1 = q >= h ? qf[4 * h + 1] : 0u;
          const uint32_t qc0 = q <= h ? qf[4 * h + 4] : 0u, qc1 = q <= h ? qf[4 * h + 5] : 0u;
          float sm[4] = {0, 0, 0, 0}, s0[4] = {0, 0, 0, 0}, s1[4] = {0, 0, 0, 0};
          mma16816(sm, qa0, qa1, qf[4 * h + 2], qf[4 * h + 3], kh[2 * h], kh[2 * h + 1]);
          mma16816(s0, qa0, qa1, qf[4 * h + 2], qf[4 * h + 3], kf[4 * h], kf[4 * h + 2]);
          mma16816(s1, qa0, qa1, qf[4 * h + 2], qf[4 * h + 3], kf[4 * h + 1], kf[4 * h + 3]);
          mma1688(sm, qc0, qc1, kh[2 * h + 2]);
          mma1688(s0, qc0, qc1, kf[4 * h + 4]);
          mma1688(s1, qc0, qc1, kf[4 * h + 5]);
          float x0 = (le0 ? s0[0] : sm[0]) * sc, x1 = (le1 ? s0[1] : sm[1]) * sc;
          float y0 = (le0 ? s1[2] : s0[2]) * sc, y1 = (le1 ? s1[3] : s0[3]) * sc;
          if (nohalo) { if (!le0) x0 = -1e9f; if (!le1) x1 = -1e9f; }
          const float mx = quad_max(fmaxf(x0, x1)), my = quad_max(fmaxf(y0, y1));
          x0 = ex2(x0 - mx); x1 = ex2(x1 - mx); y0 = ex2(y0 - my); y1 = ex2(y1 - my);
          const float ix = __fdividef(1.f, quad_sum(x0 + x1)), iy = __fdividef(1.f, quad_sum(y0 + y1));
          pA[h] = pack_bf16(x0 * ix, x1 * ix);
          pB[h] = pack_bf16(y0 * iy, y1 * iy);
        }
#pragma unroll
        for (int c = 0; c < 9; c++) {
          const uint32_t vm = movm_t(vh[c]), v0 = movm_t(vf[2 * c]), v1 = movm_t(vf[2 * c + 1]);
          const int h = c == 8 ? 3 : c >> 1;
          float o[4] = {0, 0, 0, 0};
          mma16816(o, pA[h] & ~M, 0u, pA[h] & M, pB[h] & ~M, vm, v0);
          mma1688(o, 0u, pB[h] & M, v1);
          uint32_t o0 = pack_bf16(o[0], o[1]), o1 = pack_bf16(o[2], o[3]);
          if (c == 2 || c == 4 || c == 6) {
            float e[4] = {0, 0, 0, 0};
            mma16816(e, pA[h - 1] & ~M, 0u, pA[h - 1] & M, pB[h - 1] & ~M, vm, v0);
            mma1688(e, 0u, pB[h - 1] & M, v1);
            if (q < h) { o0 = pack_bf16(e[0], e[1]); o1 = pack_bf16(e[2], e[3]); }
          }
          st8(((c & 1) ? own_o : own_e) + OFF_O + (c >> 1) * 2048, nz(o0), o1);
        }
      }
      TS(4 + L * 20);
      {
        {
          const int G = (lane & 7) * 9 + 8;
          const uint8_t* pr = sp + OFF_O + (G >> 1) * 2048 + (G & 1) * 8;
          uint32_t v[2];
          do { ld8(v, pr); } while (__any_sync(0xffffffffu, v[0] == 0));
        }
        TS(5 + L * 20);
        load_frags(a, sp + OFF_O);
        float acc[36];
        mma_pass<72, PS_WO, 6, 256, DESC_Q, true, false>(acc, a, 0, leader, -1, sp + OFF_O);
        TS(6 + L * 20);
#pragma unroll
        for (int c = 0; c < 9; c++) {
          xr[2 * c] = nz(bf2_add(xr[2 * c], pack_bf16(acc[4 * c], acc[4 * c + 1])));
          xr[2 * c + 1] = bf2_add(xr[2 * c + 1], pack_bf16(acc[4 * c + 2], acc[4 * c + 3]));
          st8(((c & 1) ? own_o : own_e) + OFF_X1 + L * TILE + (c >> 1) * 2048, xr[2 * c], xr[2 * c + 1]);
        }
        store_stats18(xr, sp + st_wr + L * 4096, g, q);
      }
      TS(16 + L * 20);
      gather_ln(a, sp + OFF_X1 + L * TILE, sp + st_rd + L * 4096, m0, m1, r0, r1);
      TS(7 + L * 20);
      uint8_t* const hb = sp + OFF_P + j * TILE;
      {
        const float ka0 = 0.7978845608028654f * r0, kb0 = 0.035677408136300125f * r0 * r0 * r0, kc0 = 0.5f * r0 * r0;
        const float ka1 = 0.7978845608028654f * r1, kb1 = 0.035677408136300125f * r1 * r1 * r1, kc1 = 0.5f * r1 * r1;
        float acc[64];
        uint32_t hf[16];
        auto geglu = [&]() {
          float r[32];
#pragma unroll
          for (int e = 0; e < 32; e++) {
            float x = acc[e];
            if (e >= 2) x = __uint_as_float(__float_as_uint(x) ^ (__float_as_uint(r[e - 2]) & P.zero));
            const bool hi = e & 2;
            float t = x * fmaf(x * x, hi ? kb1 : kb0, hi ? ka1 : ka0);
            asm("tanh.approx.f32 %0, %0;" : "+f"(t));
            const float u = x * acc[32 + e] * (hi ? kc1 : kc0);
            r[e] = fmaf(u, t, u);
            if (e & 1) hf[e >> 1] = pack_bf16(r[e - 1], r[e]);
          }
        };
        const uint32_t hsm = wg * 8192 + tid * 16;
        if (wg == 1) bar_sync(NB_ORD1, 256);
        mma_pass<128, PS_FF, 4, 2048, DESC_SW128, true, true>(acc, a, 1, leader, NB_ORD1 - wg, sp + OFF_X1 + L * TILE, 0, m0, m1);
        bar_arrive(NB_P3 + wg, 160);
        TS(8 + L * 20);
#pragma unroll 1
        for (int t = 0; t < 8; t++) {
          geglu();
          if (t < 5) {
            const uint32_t d = slot_addr(t < 2 ? 12 : 7) + t * SLOT + hsm;
#pragma unroll
            for (int i = 0; i < 4; i++)
              asm volatile("st.shared.v4.u32 [%0], {%1,%2,%3,%4};" ::"r"(d + i * 2048), "r"(hf[4 * i]), "r"(hf[4 * i + 1]), "r"(hf[4 * i + 2]), "r"(hf[4 * i + 3]) : "memory");
          } else {
#pragma unroll
            for (int i = 0; i < 4; i++) st16(hb + ((t - 5) * 4 + i) * 2048, hf[4 * i], hf[4 * i + 1], hf[4 * i + 2], hf[4 * i + 3]);
          }
          bar_sync(NB_ORD0 + wg, 256);
          mma_pass<128, PS_FF, 4, 2048, DESC_SW128, false, false>(acc, a, t & 1, leader, NB_ORD1 - wg);
        }
        TS(9 + L * 20);
#pragma unroll
        for (int i = 20; i < 32; i++) ld16(&a[4 * i], hb + (i - 20) * 2048);
#pragma unroll
        for (int i = 0; i < 20; i++)
          asm volatile("ld.shared.v4.u32 {%0,%1,%2,%3}, [%4];" : "=r"(a[4 * i]), "=r"(a[4 * i + 1]), "=r"(a[4 * i + 2]), "=r"(a[4 * i + 3])
                       : "r"(slot_addr((i < 8 ? 12 : 7) + (i >> 2)) + (i & 3) * 2048 + hsm) : "memory");
        bb_cut(P.zero);
        geglu();
#pragma unroll
        for (int i = 0; i < 16; i++) a[128 + i] = hf[i];
        asm volatile("fence.proxy.async.shared::cta;" ::: "memory");
      }
      TS(10 + L * 20);
#pragma unroll 1
      for (int p = 0; p < 5; p++) {
        bar_sync(NB_ORD0 + wg, 256);
        if (p == 0 && leader) { mbar_arrive(bar_empty(9)); mbar_arrive(bar_empty(10)); mbar_arrive(bar_empty(11)); }
        const int nb = (p == 4 && wg == 1) ? -1 : NB_ORD1 - wg;
        if (p == 2) {
          float acc[32];
          mma_pass<64, PS_FF, 4, 2048, DESC_SW128, false, false>(acc, a, 0, leader, nb);
#pragma unroll
          for (int i = 0; i < 4; i++)
            st16(hb + (32 + i) * 2048, pack_bf16(acc[8 * i], acc[8 * i + 1]), pack_bf16(acc[8 * i + 2], acc[8 * i + 3]),
                 pack_bf16(acc[8 * i + 4], acc[8 * i + 5]), pack_bf16(acc[8 * i + 6], acc[8 * i + 7]));
        } else {
          float acc[64];
          mma_pass<128, PS_FF, 4, 2048, DESC_SW128, false, false>(acc, a, p & 1, leader, nb);
          if (p == 4) bar_sync(NB_RDY + wg, 160);
          uint8_t* d = hb + (p < 2 ? p : p - 1) * 16384;
#pragma unroll
          for (int i = 0; i < 8; i++)
            st16(d + i * 2048, nz(pack_bf16(acc[8 * i], acc[8 * i + 1])), pack_bf16(acc[8 * i + 2], acc[8 * i + 3]),
                 nz(pack_bf16(acc[8 * i + 4], acc[8 * i + 5])), pack_bf16(acc[8 * i + 6], acc[8 * i + 7]));
          if (p == 3) bar_arrive(NB_STA + wg, 160);
        }
      }
      TS(11 + L * 20);
      {
        const uint8_t* pw = sp + j * 2048;
        const uint8_t* pn = sp + (32 + (j >> 1)) * 2048 + (j & 1) * 8;
#pragma unroll
        for (int s = 0; s < 8; s++) {
#pragma unroll
          for (int p = 0; p < 3; p++) ld16(&a[s * 16 + 4 * p], pw + OFF_P + s * TILE + p * 16384);
          ld8(&a[128 + 2 * s], pn + OFF_P + s * TILE);
        }
#pragma unroll
        for (int p = 0; p < 4; p++) ld16(&xr[4 * p], pw + OFF_X1 + L * TILE + p * 16384);
        ld8(&xr[16], pn + OFF_X1 + L * TILE);
        uint32_t m;
        do {
          m = 0xffffffffu;
#pragma unroll
          for (int s = 0; s < 8; s++) {
            ld16(&a[s * 16 + 12], pw + OFF_P + s * TILE + 3 * 16384);
            m = min(m, min(a[s * 16 + 12], a[s * 16 + 14]));
          }
        } while (__any_sync(0xffffffffu, m == 0));
        TS(12 + L * 20);
        const uint32_t ident = (2 * q == g ? 0x3f80u : 0u) | (2 * q + 1 == g ? 0x3f800000u : 0u);
#pragma unroll
        for (int c = 0; c < 9; c++) {
          float o[4] = {0, 0, 0, 0};
#pragma unroll
          for (int s = 0; s < 8; s++) {
            const uint32_t* f = c < 8 ? &a[s * 16 + 2 * c] : &a[128 + 2 * s];
            mma1688(o, f[0], f[1], ident);
          }
          xr[2 * c] = bf2_add(xr[2 * c], pack_bf16(o[0], o[1]));
          xr[2 * c + 1] = bf2_add(xr[2 * c + 1], pack_bf16(o[2], o[3]));
        }
        TS(18 + L * 20);
        if (L == 0) {
#pragma unroll
          for (int p = 0; p < 4; p++) st16((uint8_t*)pw + OFF_X2 + p * 16384, nz(xr[4 * p]), xr[4 * p + 1], nz(xr[4 * p + 2]), xr[4 * p + 3]);
          st8((uint8_t*)pn + OFF_X2, nz(xr[16]), xr[17]);
          store_stats18(xr, sp + st_wr + 8192, g, q);
        } else {
          uint32_t* op = (uint32_t*)(P.out + tok0 * DM) + q;
#pragma unroll
          for (int p = 0; p < 4; p++) {
            const int c = (p * 128 + j * 16) / 2;
            op[c] = xr[4 * p]; op[16 * (DM / 2) + c] = xr[4 * p + 1]; op[c + 4] = xr[4 * p + 2]; op[16 * (DM / 2) + c + 4] = xr[4 * p + 3];
          }
          op[256 + j * 4] = xr[16]; op[16 * (DM / 2) + 256 + j * 4] = xr[17];
        }
      }
      TS(13 + L * 20);
    }
    bar_sync(NB_WG + wg, 128);
    if (leader) mbar_arrive(bar_empty(12));
  }
}

typedef CUresult (*EncodeFn)(CUtensorMap*, CUtensorMapDataType, cuuint32_t, void*, const cuuint64_t*, const cuuint64_t*, const cuuint32_t*,
                             const cuuint32_t*, CUtensorMapInterleave, CUtensorMapSwizzle, CUtensorMapL2promotion, CUtensorMapFloatOOBfill);

void encode(EncodeFn fn, CUtensorMap* m, const void* p, int rank, const cuuint64_t* dims, const cuuint64_t* str, const cuuint32_t* box) {
  const cuuint32_t es[3] = {1, 1, 1};
  fn(m, CU_TENSOR_MAP_DATA_TYPE_BFLOAT16, rank, const_cast<void*>(p), dims, str, box, es, CU_TENSOR_MAP_INTERLEAVE_NONE,
     CU_TENSOR_MAP_SWIZZLE_128B, CU_TENSOR_MAP_L2_PROMOTION_L2_256B, CU_TENSOR_MAP_FLOAT_OOB_FILL_NONE);
}

}

extern "C" void kernel_launch(void* const* d_in, const int* in_sizes, int n_in, void* d_out, int out_size) {
  (void)in_sizes; (void)n_in; (void)out_size;
  Params P;
  P.x = (const __nv_bfloat16*)d_in[0]; P.wqkv = (const __nv_bfloat16*)d_in[1]; P.wo = (const __nv_bfloat16*)d_in[2];
  P.wg = (const __nv_bfloat16*)d_in[4]; P.wu = (const __nv_bfloat16*)d_in[5]; P.wd = (const __nv_bfloat16*)d_in[6];
  P.out = (__nv_bfloat16*)d_out; P.zero = 0; P.zero2 = 0;
  void* fnp = nullptr; cudaDriverEntryPointQueryResult qr;
  cudaGetDriverEntryPoint("cuTensorMapEncodeTiled", &fnp, cudaEnableDefault, &qr);
  EncodeFn fn = (EncodeFn)fnp;
  CUtensorMap mx, mg, mu, md;
  { const cuuint64_t dims[3] = {DM, 2, SEQ / 2}, str[2] = {DM * 2, DM * 4}; const cuuint32_t box[3] = {64, 1, 64}; encode(fn, &mx, P.x, 3, dims, str, box); }
  { const cuuint64_t dims[2] = {DFF, DM}, str[1] = {DFF * 2}; const cuuint32_t box[2] = {64, 64}; encode(fn, &mg, P.wg, 2, dims, str, box); encode(fn, &mu, P.wu, 2, dims, str, box); }
  { const cuuint64_t dims[2] = {DM, DFF}, str[1] = {DM * 2}; const cuuint32_t box[2] = {64, 64}; encode(fn, &md, P.wd, 2, dims, str, box); }
  cudaFuncSetAttribute(fused_kernel, cudaFuncAttributeMaxDynamicSharedMemorySize, SMEM_BYTES);
  fused_kernel<<<128, 384, SMEM_BYTES, cudaStreamPerThread>>>(mx, mg, mu, md, P);
}
```

```cpp
#include <cuda_runtime.h>
#include <cuda_bf16.h>
#include <cuda.h>
#include <stdint.h>

#define KV_LEAD 5
#define D_KV 8
#define D_WO 5
#define D_T0 6
#define PF_AHEAD 3
#define CH_LAST 4
#define TH 2
#define SPLIT_N 0
#define MC 1
#define TIMING 0

namespace {

constexpr int SEQ = 2048, DM = 576, DFF = 4608;
constexpr uint32_t SB = 1024;
constexpr uint32_t SLOT = 16384;
constexpr uint32_t PSLOT = 13824;
constexpr uint32_t BARS = SB + 14 * SLOT;
constexpr int SMEM_BYTES = 14 * SLOT + 256 + 2560;
__host__ __device__ constexpr uint32_t slot_addr(int s) { return SB + s * SLOT; }
__host__ __device__ constexpr uint32_t bar_full(int s) { return BARS + 8 * s; }
__host__ __device__ constexpr uint32_t bar_empty(int s) { return BARS + 128 + 8 * s; }
enum { NB_ORD0 = 1, NB_ORD1 = 2, NB_WG = 3  , NB_HALO = 5  , NB_FREE = 7   };
constexpr uint32_t SM_EPOCH = BARS + 120;

constexpr uint32_t TILE = 36 * 2048;
constexpr uint32_t OFF_X1 = 0  , OFF_O = TILE, OFF_X2 = 2 * TILE, OFF_ST = 4 * TILE  ;
constexpr uint32_t PBUF = 7 * 2048, PSRC = 2 * PBUF + PBUF / 2;
constexpr uint32_t OFF_P = OFF_ST + 3 * 4096, OFF_HALO = OFF_P + 8 * PSRC  , OFF_HINT = OFF_HALO + 2 * 8 * 3072  ,
                   STRM = OFF_HINT + 12 * 128;
constexpr uint32_t OFF_WPACK = 32 * STRM, OFF_FLAGS = OFF_WPACK + 8 * 24 * PSLOT;
__device__ __align__(1024) uint8_t g_scr[OFF_FLAGS + (8 + 64 + 128) * 32];

__device__ __forceinline__ uint32_t smem_u32(const void* p) { return (uint32_t)__cvta_generic_to_shared(p); }
extern __shared__ __align__(1024) uint8_t smem_raw[];
__device__ __forceinline__ uint32_t win() { return MC ? (blockIdx.x & 1) << 24 : 0; }
#define SA(A, W) ".reg .u32 sa;\nadd.u32 sa, " A ", " W ";\n"
__device__ __forceinline__ void mbar_init(uint32_t bar, uint32_t cnt) { asm volatile("{\n" SA("%0", "%2") "mbarrier.init.shared::cta.b64 [sa], %1;\n}" ::"r"(bar), "r"(cnt), "r"(win())); }
__device__ __forceinline__ void mbar_expect_tx(uint32_t bar, uint32_t bytes) { asm volatile("{\n" SA("%0", "%2") "mbarrier.arrive.expect_tx.shared::cta.b64 _, [sa], %1;\n}" ::"r"(bar), "r"(bytes), "r"(win()) : "memory"); }
__device__ __forceinline__ void mbar_arrive(uint32_t bar) { asm volatile("{\n" SA("%0", "%1") "mbarrier.arrive.shared::cta.b64 _, [sa];\n}" ::"r"(bar), "r"(win()) : "memory"); }
__device__ __forceinline__ uint32_t lds32(uint32_t a) { uint32_t v; asm volatile("{\n" SA("%1", "%2") "ld.shared.u32 %0, [sa];\n}" : "=r"(v) : "r"(a), "r"(win()) : "memory"); return v; }
__device__ __forceinline__ void lds64(uint32_t& x, uint32_t& y, uint32_t a) { asm volatile("{\n" SA("%2", "%3") "ld.shared.v2.u32 {%0,%1}, [sa];\n}" : "=r"(x), "=r"(y) : "r"(a), "r"(win()) : "memory"); }
__device__ __forceinline__ void lds128(uint32_t* v, uint32_t a) {
  asm volatile("{\n" SA("%4", "%5") "ld.shared.v4.u32 {%0,%1,%2,%3}, [sa];\n}" : "=r"(v[0]), "=r"(v[1]), "=r"(v[2]), "=r"(v[3]) : "r"(a), "r"(win()) : "memory");
}
__device__ __forceinline__ void sts32(uint32_t a, uint32_t x) { asm volatile("{\n" SA("%0", "%2") "st.shared.u32 [sa], %1;\n}" ::"r"(a), "r"(x), "r"(win()) : "memory"); }
__device__ __forceinline__ void sts64(uint32_t a, uint32_t x, uint32_t y) { asm volatile("{\n" SA("%0", "%3") "st.shared.v2.u32 [sa], {%1,%2};\n}" ::"r"(a), "r"(x), "r"(y), "r"(win()) : "memory"); }
__device__ __forceinline__ void sts128(uint32_t a, uint32_t x, uint32_t y, uint32_t z, uint32_t w) {
  asm volatile("{\n" SA("%0", "%5") "st.shared.v4.u32 [sa], {%1,%2,%3,%4};\n}" ::"r"(a), "r"(x), "r"(y), "r"(z), "r"(w), "r"(win()) : "memory");
}
__device__ __forceinline__ void mbar_wait(uint32_t bar, uint32_t parity) {
  asm volatile("{\n.reg .pred p;\n" SA("%0", "%2") "LAB_WAIT:\nmbarrier.try_wait.parity.shared::cta.b64 p, [sa], %1;\n@!p bra LAB_WAIT;\n}" ::"r"(bar), "r"(parity), "r"(win()) : "memory");
}
__device__ __forceinline__ void timed_wait(uint32_t bar) {
  asm volatile("{\n.reg .pred p;\n.reg .u64 t0, t1;\nmov.u64 t0, %%globaltimer;\nLAB_WD:\n"
               "mbarrier.try_wait.parity.shared::cta.b64 p, [%0], 0, 100000;\n@p bra LAB_OK;\n"
               "mov.u64 t1, %%globaltimer;\nsub.u64 t1, t1, t0;\nsetp.lt.u64 p, t1, 2000000000;\n@p bra LAB_WD;\ntrap;\nLAB_OK:\n}" ::"r"(bar + win()) : "memory");
}
__device__ __forceinline__ void flag_wait(const unsigned* flag, unsigned target) {
  asm volatile("{\n.reg .pred p;\n.reg .u32 v;\nLAB_WAIT:\nld.acquire.gpu.global.u32 v, [%0];\nsub.u32 v, v, %1;\n"
               "setp.lt.s32 p, v, 0;\n@p nanosleep.u32 100;\n@p bra LAB_WAIT;\n}" ::"l"(flag), "r"(target) : "memory");
}
__device__ __forceinline__ void hint_post(uint8_t* p) {
  __syncwarp();
  asm volatile("{\n.reg .pred p;\nelect.sync _|p, 0xffffffff;\n@p red.relaxed.gpu.global.add.u32 [%0], 1;\n}" ::"l"(p) : "memory");
}
__device__ __forceinline__ void hint_wait(const uint8_t* p, uint32_t target) {
  asm volatile("{\n.reg .pred p;\n.reg .u32 v;\nLAB_WAIT:\nld.relaxed.gpu.global.u32 v, [%0];\nsub.u32 v, v, %1;\n"
               "setp.lt.s32 p, v, 0;\nvote.sync.any.pred p, p, 0xffffffff;\n@p bra LAB_WAIT;\n}" ::"l"(p), "r"(target) : "memory");
}
__device__ __forceinline__ void flag_signal(unsigned* flag) { asm volatile("red.release.gpu.global.add.u32 [%0], 1;" ::"l"(flag) : "memory"); }
struct Rel {
  bool on; uint32_t base;
  __device__ __forceinline__ void operator()(int s) const {
    if (on) {
      if (MC) asm volatile("{\n" SA("%0", "%1") "mbarrier.arrive.shared::cluster.b64 _, [sa];\n}" ::"r"(bar_empty(s)), "r"(base) : "memory");
      else mbar_arrive(bar_empty(s));
    }
  }
};
__device__ __forceinline__ uint32_t cta_window(uint32_t rank) { uint32_t a; asm("mapa.shared::cluster.u32 %0, %1, %2;" : "=r"(a) : "r"(0), "r"(rank)); return a; }
__device__ __forceinline__ void tma_2d_mc(uint32_t dst, const CUtensorMap* m, int c0, int c1, uint32_t bar) {
  asm volatile("cp.async.bulk.tensor.2d.shared::cluster.global.mbarrier::complete_tx::bytes.multicast::cluster [%0], [%1, {%3, %4}], [%2], %5;"
               ::"r"(dst), "l"(m), "r"(bar), "r"(c0), "r"(c1), "h"((uint16_t)3) : "memory");
}
__device__ __forceinline__ void bulk_load_mc(uint32_t dst, const void* src, uint32_t bytes, uint32_t bar) {
  asm volatile("cp.async.bulk.shared::cluster.global.mbarrier::complete_tx::bytes.multicast::cluster [%0], [%1], %2, [%3], %4;"
               ::"r"(dst), "l"(src), "r"(bytes), "r"(bar), "h"((uint16_t)3) : "memory");
}
__device__ __forceinline__ void tma_2d(uint32_t dst, const CUtensorMap* m, int c0, int c1, uint32_t bar) {
  asm volatile("cp.async.bulk.tensor.2d.shared::cluster.global.mbarrier::complete_tx::bytes [%0], [%1, {%3, %4}], [%2];"
               ::"r"(dst), "l"(m), "r"(bar), "r"(c0), "r"(c1) : "memory");
}
__device__ __forceinline__ void tma_3d(uint32_t dst, const CUtensorMap* m, int c0, int c1, int c2, uint32_t bar) {
  asm volatile("cp.async.bulk.tensor.3d.shared::cluster.global.mbarrier::complete_tx::bytes [%0], [%1, {%3, %4, %5}], [%2];"
               ::"r"(dst), "l"(m), "r"(bar), "r"(c0), "r"(c1), "r"(c2) : "memory");
}
__device__ __forceinline__ void bulk_load(uint32_t dst, const void* src, uint32_t bytes, uint32_t bar) {
  asm volatile("cp.async.bulk.shared::cluster.global.mbarrier::complete_tx::bytes [%0], [%1], %2, [%3];" ::"r"(dst), "l"(src), "r"(bytes), "r"(bar) : "memory");
}
__device__ __forceinline__ void l2_prefetch(const void* src, uint32_t bytes) { asm volatile("cp.async.bulk.prefetch.L2.global [%0], %1;" ::"l"(src), "r"(bytes) : "memory"); }
__device__ __forceinline__ void wg_fence() { asm volatile("wgmma.fence.sync.aligned;" ::: "memory"); }
__device__ __forceinline__ void wg_commit() { asm volatile("wgmma.commit_group.sync.aligned;" ::: "memory"); }
template <int N> __device__ __forceinline__ void wg_wait() { asm volatile("wgmma.wait_group.sync.aligned %0;" ::"n"(N) : "memory"); }
__device__ __forceinline__ void bar_sync(int id, int n) { asm volatile("bar.sync %0, %1;" ::"r"(id), "r"(n) : "memory"); }
__device__ __forceinline__ void bar_arrive(int id, int n) { asm volatile("bar.arrive %0, %1;" ::"r"(id), "r"(n) : "memory"); }
__device__ __forceinline__ uint32_t pack_bf16(float lo, float hi) { uint32_t r; asm("cvt.rn.bf16x2.f32 %0, %1, %2;" : "=r"(r) : "f"(hi), "f"(lo)); return r; }
__device__ __forceinline__ float bf_lo(uint32_t w) { return __uint_as_float(w << 16); }
__device__ __forceinline__ float bf_hi(uint32_t w) { return __uint_as_float(w & 0xffff0000u); }
__device__ __forceinline__ float bf_round(float x) { return bf_lo(pack_bf16(x, 0.f)); }
__device__ __forceinline__ uint32_t bf2_sub(uint32_t a, uint32_t b) { uint32_t r; asm("sub.rn.bf16x2 %0, %1, %2;" : "=r"(r) : "r"(a), "r"(b)); return r; }
__device__ __forceinline__ uint32_t bf2_add(uint32_t a, uint32_t b) { uint32_t r; asm("add.rn.bf16x2 %0, %1, %2;" : "=r"(r) : "r"(a), "r"(b)); return r; }
#define GADDR(B, O, I) "cvt.u64.u32 ad, " O ";\nadd.u64 ad, ad, " B ";\nadd.u64 ad, ad, " I ";\n"
__device__ __forceinline__ void ld16(uint32_t* v, const uint8_t* ub, uint32_t off, uint32_t imm) {
  asm volatile("{\n.reg .b128 z;\n.reg .b64 x, y, ad;\n" GADDR("%4", "%5", "%6") "ld.relaxed.gpu.global.b128 z, [ad];\n"
               "mov.b128 {x, y}, z;\nmov.b64 {%0,%1}, x;\nmov.b64 {%2,%3}, y;\n}"
               : "=r"(v[0]), "=r"(v[1]), "=r"(v[2]), "=r"(v[3]) : "l"(ub), "r"(off), "l"((uint64_t)imm) : "memory");
}
__device__ __forceinline__ void ld8(uint32_t* v, const uint8_t* ub, uint32_t off, uint32_t imm) {
  asm volatile("{\n.reg .b64 x, ad;\n" GADDR("%2", "%3", "%4") "ld.relaxed.gpu.global.b64 x, [ad];\nmov.b64 {%0,%1}, x;\n}"
               : "=r"(v[0]), "=r"(v[1]) : "l"(ub), "r"(off), "l"((uint64_t)imm) : "memory");
}
__device__ __forceinline__ void st16(uint8_t* ub, uint32_t off, uint32_t imm, uint32_t a, uint32_t b, uint32_t c, uint32_t d) {
  asm volatile("{\n.reg .b128 z;\n.reg .b64 x, y, ad;\n" GADDR("%0", "%1", "%2") "mov.b64 x, {%3,%4};\nmov.b64 y, {%5,%6};\nmov.b128 z, {x, y};\n"
               "st.relaxed.gpu.global.b128 [ad], z;\n}" ::"l"(ub), "r"(off), "l"((uint64_t)imm), "r"(a), "r"(b), "r"(c), "r"(d) : "memory");
}
__device__ __forceinline__ void st8(uint8_t* ub, uint32_t off, uint32_t imm, uint32_t a, uint32_t b) {
  asm volatile("{\n.reg .b64 x, ad;\n" GADDR("%0", "%1", "%2") "mov.b64 x, {%3,%4};\nst.relaxed.gpu.global.b64 [ad], x;\n}"
               ::"l"(ub), "r"(off), "l"((uint64_t)imm), "r"(a), "r"(b) : "memory");
}
__device__ __forceinline__ uint32_t ldg4(const void* ub, uint32_t off, uint32_t imm) {
  uint32_t v; asm volatile("{\n.reg .b64 ad;\n" GADDR("%1", "%2", "%3") "ld.global.nc.u32 %0, [ad];\n}" : "=r"(v) : "l"(ub), "r"(off), "l"((uint64_t)imm)); return v;
}
__device__ __forceinline__ void stg4(void* ub, uint32_t off, uint32_t imm, uint32_t v) {
  asm volatile("{\n.reg .b64 ad;\n" GADDR("%0", "%1", "%2") "st.global.u32 [ad], %3;\n}" ::"l"(ub), "r"(off), "l"((uint64_t)imm), "r"(v) : "memory");
}
__device__ __forceinline__ uint32_t tid_() { uint32_t t; asm volatile("mov.u32 %0, %%tid.x;" : "=r"(t)); return t & 127; }
__device__ __forceinline__ uint32_t nz(uint32_t w) { return max(w, 1u); }
__device__ __forceinline__ void mma16816(float (&c)[4], uint32_t a0, uint32_t a1, uint32_t a2, uint32_t a3, uint32_t b0, uint32_t b1) {
  asm("mma.sync.aligned.m16n8k16.row.col.f32.bf16.bf16.f32 {%0,%1,%2,%3}, {%4,%5,%6,%7}, {%8,%9}, {%0,%1,%2,%3};"
               : "+f"(c[0]), "+f"(c[1]), "+f"(c[2]), "+f"(c[3]) : "r"(a0), "r"(a1), "r"(a2), "r"(a3), "r"(b0), "r"(b1));
}
__device__ __forceinline__ void mma1688(float (&c)[4], uint32_t a0, uint32_t a1, uint32_t b0) {
  asm("mma.sync.aligned.m16n8k8.row.col.f32.bf16.bf16.f32 {%0,%1,%2,%3}, {%4,%5}, {%6}, {%0,%1,%2,%3};"
               : "+f"(c[0]), "+f"(c[1]), "+f"(c[2]), "+f"(c[3]) : "r"(a0), "r"(a1), "r"(b0));
}
__device__ __forceinline__ uint32_t movm_t(uint32_t a) { uint32_t d; asm("movmatrix.sync.aligned.m8n8.trans.b16 %0, %1;" : "=r"(d) : "r"(a)); return d; }
__device__ __forceinline__ float ex2(float x) { float r; asm("ex2.approx.ftz.f32 %0, %1;" : "=f"(r) : "f"(x)); return r; }
__device__ __forceinline__ float quad_sum(float v) { v += __shfl_xor_sync(0xffffffffu, v, 1); v += __shfl_xor_sync(0xffffffffu, v, 2); return v; }
__device__ __forceinline__ float quad_max(float v) { v = fmaxf(v, __shfl_xor_sync(0xffffffffu, v, 1)); v = fmaxf(v, __shfl_xor_sync(0xffffffffu, v, 2)); return v; }

__device__ __forceinline__ void wgmma_rs_n64(float (&d)[32], uint32_t a0, uint32_t a1, uint32_t a2, uint32_t a3, uint64_t desc, int scale_d) {
  asm volatile("{\n.reg .pred p;\nsetp.ne.b32 p, %37, 0;\n"
    "wgmma.mma_async.sync.aligned.m64n64k16.f32.bf16.bf16 "
    "{%0, %1, %2, %3, %4, %5, %6, %7, %8, %9, %10, %11, %12, %13, %14, %15, %16, %17, %18, %19, %20, %21, %22, %23, %24, %25, %26, %27, %28, %29, %30, %31}, "
    "{%32, %33, %34, %35}, %36, p, 1, 1, 1;\n}\n"
    : "+f"(d[0]), "+f"(d[1]), "+f"(d[2]), "+f"(d[3]), "+f"(d[4]), "+f"(d[5]), "+f"(d[6]), "+f"(d[7]), "+f"(d[8]), "+f"(d[9]), "+f"(d[10]), "+f"(d[11]), "+f"(d[12]), "+f"(d[13]), "+f"(d[14]), "+f"(d[15]), "+f"(d[16]), "+f"(d[17]), "+f"(d[18]), "+f"(d[19]), "+f"(d[20]), "+f"(d[21]), "+f"(d[22]), "+f"(d[23]), "+f"(d[24]), "+f"(d[25]), "+f"(d[26]), "+f"(d[27]), "+f"(d[28]), "+f"(d[29]), "+f"(d[30]), "+f"(d[31])
    : "r"(a0), "r"(a1), "r"(a2), "r"(a3), "l"(desc), "r"(scale_d));
}

__device__ __forceinline__ void wgmma_rs_n72(float (&d)[36], uint32_t a0, uint32_t a1, uint32_t a2, uint32_t a3, uint64_t desc, int scale_d) {
  asm volatile("{\n.reg .pred p;\nsetp.ne.b32 p, %41, 0;\n"
    "wgmma.mma_async.sync.aligned.m64n72k16.f32.bf16.bf16 "
    "{%0, %1, %2, %3, %4, %5, %6, %7, %8, %9, %10, %11, %12, %13, %14, %15, %16, %17, %18, %19, %20, %21, %22, %23, %24, %25, %26, %27, %28, %29, %30, %31, %32, %33, %34, %35}, "
    "{%36, %37, %38, %39}, %40, p, 1, 1, 1;\n}\n"
    : "+f"(d[0]), "+f"(d[1]), "+f"(d[2]), "+f"(d[3]), "+f"(d[4]), "+f"(d[5]), "+f"(d[6]), "+f"(d[7]), "+f"(d[8]), "+f"(d[9]), "+f"(d[10]), "+f"(d[11]), "+f"(d[12]), "+f"(d[13]), "+f"(d[14]), "+f"(d[15]), "+f"(d[16]), "+f"(d[17]), "+f"(d[18]), "+f"(d[19]), "+f"(d[20]), "+f"(d[21]), "+f"(d[22]), "+f"(d[23]), "+f"(d[24]), "+f"(d[25]), "+f"(d[26]), "+f"(d[27]), "+f"(d[28]), "+f"(d[29]), "+f"(d[30]), "+f"(d[31]), "+f"(d[32]), "+f"(d[33]), "+f"(d[34]), "+f"(d[35])
    : "r"(a0), "r"(a1), "r"(a2), "r"(a3), "l"(desc), "r"(scale_d));
}

__device__ __forceinline__ void wgmma_rs_n128(float (&d)[64], uint32_t a0, uint32_t a1, uint32_t a2, uint32_t a3, uint64_t desc, int scale_d) {
  asm volatile("{\n.reg .pred p;\nsetp.ne.b32 p, %69, 0;\n"
    "wgmma.mma_async.sync.aligned.m64n128k16.f32.bf16.bf16 "
    "{%0, %1, %2, %3, %4, %5, %6, %7, %8, %9, %10, %11, %12, %13, %14, %15, %16, %17, %18, %19, %20, %21, %22, %23, %24, %25, %26, %27, %28, %29, %30, %31, %32, %33, %34, %35, %36, %37, %38, %39, %40, %41, %42, %43, %44, %45, %46, %47, %48, %49, %50, %51, %52, %53, %54, %55, %56, %57, %58, %59, %60, %61, %62, %63}, "
    "{%64, %65, %66, %67}, %68, p, 1, 1, 1;\n}\n"
    : "+f"(d[0]), "+f"(d[1]), "+f"(d[2]), "+f"(d[3]), "+f"(d[4]), "+f"(d[5]), "+f"(d[6]), "+f"(d[7]), "+f"(d[8]), "+f"(d[9]), "+f"(d[10]), "+f"(d[11]), "+f"(d[12]), "+f"(d[13]), "+f"(d[14]), "+f"(d[15]), "+f"(d[16]), "+f"(d[17]), "+f"(d[18]), "+f"(d[19]), "+f"(d[20]), "+f"(d[21]), "+f"(d[22]), "+f"(d[23]), "+f"(d[24]), "+f"(d[25]), "+f"(d[26]), "+f"(d[27]), "+f"(d[28]), "+f"(d[29]), "+f"(d[30]), "+f"(d[31]), "+f"(d[32]), "+f"(d[33]), "+f"(d[34]), "+f"(d[35]), "+f"(d[36]), "+f"(d[37]), "+f"(d[38]), "+f"(d[39]), "+f"(d[40]), "+f"(d[41]), "+f"(d[42]), "+f"(d[43]), "+f"(d[44]), "+f"(d[45]), "+f"(d[46]), "+f"(d[47]), "+f"(d[48]), "+f"(d[49]), "+f"(d[50]), "+f"(d[51]), "+f"(d[52]), "+f"(d[53]), "+f"(d[54]), "+f"(d[55]), "+f"(d[56]), "+f"(d[57]), "+f"(d[58]), "+f"(d[59]), "+f"(d[60]), "+f"(d[61]), "+f"(d[62]), "+f"(d[63])
    : "r"(a0), "r"(a1), "r"(a2), "r"(a3), "l"(desc), "r"(scale_d));
}

__device__ __forceinline__ void wgmma_rs_n144(float (&d)[72], uint32_t a0, uint32_t a1, uint32_t a2, uint32_t a3, uint64_t desc, int scale_d) {
  asm volatile("{\n.reg .pred p;\nsetp.ne.b32 p, %77, 0;\n"
    "wgmma.mma_async.sync.aligned.m64n144k16.f32.bf16.bf16 "
    "{%0, %1, %2, %3, %4, %5, %6, %7, %8, %9, %10, %11, %12, %13, %14, %15, %16, %17, %18, %19, %20, %21, %22, %23, %24, %25, %26, %27, %28, %29, %30, %31, %32, %33, %34, %35, %36, %37, %38, %39, %40, %41, %42, %43, %44, %45, %46, %47, %48, %49, %50, %51, %52, %53, %54, %55, %56, %57, %58, %59, %60, %61, %62, %63, %64, %65, %66, %67, %68, %69, %70, %71}, "
    "{%72, %73, %74, %75}, %76, p, 1, 1, 1;\n}\n"
    : "+f"(d[0]), "+f"(d[1]), "+f"(d[2]), "+f"(d[3]), "+f"(d[4]), "+f"(d[5]), "+f"(d[6]), "+f"(d[7]), "+f"(d[8]), "+f"(d[9]), "+f"(d[10]), "+f"(d[11]), "+f"(d[12]), "+f"(d[13]), "+f"(d[14]), "+f"(d[15]), "+f"(d[16]), "+f"(d[17]), "+f"(d[18]), "+f"(d[19]), "+f"(d[20]), "+f"(d[21]), "+f"(d[22]), "+f"(d[23]), "+f"(d[24]), "+f"(d[25]), "+f"(d[26]), "+f"(d[27]), "+f"(d[28]), "+f"(d[29]), "+f"(d[30]), "+f"(d[31]), "+f"(d[32]), "+f"(d[33]), "+f"(d[34]), "+f"(d[35]), "+f"(d[36]), "+f"(d[37]), "+f"(d[38]), "+f"(d[39]), "+f"(d[40]), "+f"(d[41]), "+f"(d[42]), "+f"(d[43]), "+f"(d[44]), "+f"(d[45]), "+f"(d[46]), "+f"(d[47]), "+f"(d[48]), "+f"(d[49]), "+f"(d[50]), "+f"(d[51]), "+f"(d[52]), "+f"(d[53]), "+f"(d[54]), "+f"(d[55]), "+f"(d[56]), "+f"(d[57]), "+f"(d[58]), "+f"(d[59]), "+f"(d[60]), "+f"(d[61]), "+f"(d[62]), "+f"(d[63]), "+f"(d[64]), "+f"(d[65]), "+f"(d[66]), "+f"(d[67]), "+f"(d[68]), "+f"(d[69]), "+f"(d[70]), "+f"(d[71])
    : "r"(a0), "r"(a1), "r"(a2), "r"(a3), "l"(desc), "r"(scale_d));
}

template <int N> struct WG;
template <> struct WG<64>  { static __device__ __forceinline__ void f(float (&d)[32], const uint32_t* a, uint64_t ds, int s) { wgmma_rs_n64(d, a[0], a[1], a[2], a[3], ds, s); } };
template <> struct WG<72>  { static __device__ __forceinline__ void f(float (&d)[36], const uint32_t* a, uint64_t ds, int s) { wgmma_rs_n72(d, a[0], a[1], a[2], a[3], ds, s); } };
template <> struct WG<128> { static __device__ __forceinline__ void f(float (&d)[64], const uint32_t* a, uint64_t ds, int s) { wgmma_rs_n128(d, a[0], a[1], a[2], a[3], ds, s); } };
template <> struct WG<144> { static __device__ __forceinline__ void f(float (&d)[72], const uint32_t* a, uint64_t ds, int s) { wgmma_rs_n144(d, a[0], a[1], a[2], a[3], ds, s); } };

constexpr uint64_t DESC_SW128 = ((uint64_t)(8192 >> 4) << 16) | ((uint64_t)(1024 >> 4) << 32) | (1ull << 62);
constexpr uint64_t DESC_KV = ((uint64_t)(128 >> 4) << 16) | ((uint64_t)(768 >> 4) << 32);
constexpr uint64_t DESC_Q = ((uint64_t)(128 >> 4) << 16) | ((uint64_t)(1536 >> 4) << 32);

template <int V> struct IntC { static constexpr int value = V; };
enum { PS_KV, PS_Q, PS_WO, PS_FF };
template <int PS> __host__ __device__ constexpr int pass_slot(int i) {
  return PS == PS_KV ? (i < 3 ? 9 + i : i - 3) : PS == PS_WO ? 6 + i : i;
}

__device__ __forceinline__ void load_frag(uint32_t (&a)[144], int i, const uint8_t* sb, uint32_t uo, uint32_t t) {
  if (i < 32) ld16(&a[4 * i], sb, uo + t * 16, i * 2048);
  else { ld8(&a[4 * i], sb, uo + t * 8, i * 2048); ld8(&a[4 * i + 2], sb, uo + t * 8, i * 2048 + 1024); }
}
__device__ __forceinline__ void store_own(const uint32_t (&y)[18], uint8_t* sb, uint32_t uo, int j) {
  const uint32_t t = tid_() + j * 128;
#pragma unroll
  for (int i = 0; i < 4; i++) st16(sb, uo + t * 16, i * 16384, nz(y[4 * i]), y[4 * i + 1], y[4 * i + 2], y[4 * i + 3]);
  st8(sb, uo + t * 8, 65536, nz(y[16]), y[17]);
}
__device__ __forceinline__ void load_own(uint32_t (&y)[18], const uint8_t* sb, uint32_t uo, int j) {
  const uint32_t t = tid_() + j * 128;
#pragma unroll
  for (int i = 0; i < 4; i++) ld16(&y[4 * i], sb, uo + t * 16, i * 16384);
  ld8(&y[16], sb, uo + t * 8, 65536);
}

template <int N, int PS, int KPS, int KSTEP, int CHK, bool SUB, bool HREL = false>
__device__ __forceinline__ void mma_pass(float (&acc)[N / 2], uint32_t (&a)[144], uint64_t desc, uint32_t par, const Rel& rel, int bar_id,
                                         const uint8_t* sb = nullptr, uint32_t uo = 0, uint32_t nochk = 0, uint32_t m0 = 0, uint32_t m1 = 0, uint32_t zero = 0) {
  constexpr int NS = 36 / KPS;
  constexpr int P_REL = (N <= SPLIT_N) ? KPS / 2 - 1 : KPS - 1, P_CHK = KPS - 1;
  auto prepare = [&](int s) {
    const int sl = pass_slot<PS>(s);
    mbar_wait(bar_full(sl), sl < 9 ? par : par ^ 1);
    if (CHK) {
      while (true) {
        uint32_t m = a[4 * s * KPS];
#pragma unroll
        for (int i = s * KPS; i < (s + 1) * KPS; i++) {
          if (i > s * KPS) asm volatile("min.u32 %0, %0, %1;" : "+r"(m) : "r"(a[4 * i]));
          if (i >= 32) asm volatile("min.u32 %0, %0, %1;" : "+r"(m) : "r"(a[4 * i + 2]));
        }
        if (!__any_sync(0xffffffffu, (m | nochk) == 0)) break;
        const uint32_t t = tid_();
#pragma unroll
        for (int i = s * KPS; i < (s + 1) * KPS; i++) load_frag(a, i, sb, uo, t);
      }
      if (s + CHK < NS && !nochk) {
        const uint32_t t = tid_();
#pragma unroll
        for (int i = (s + CHK) * KPS; i < (s + CHK + 1) * KPS; i++) load_frag(a, i, sb, uo, t);
      }
    }
  };
  prepare(0);
#pragma unroll
  for (int s = 0; s < NS; s++) {
    if (SUB) {
#pragma unroll
      for (int i = s * KPS * 4; i < (s + 1) * KPS * 4; i += 2) { a[i] = bf2_sub(a[i], m0); a[i + 1] = bf2_sub(a[i + 1], m1); }
    }
#pragma unroll
    for (int kk = 0; kk < KPS; kk++) {
      if (kk == 0 || kk == P_REL + 1 || kk == P_CHK + 1) wg_fence();
      WG<N>::f(acc, &a[(s * KPS + kk) * 4], desc + ((slot_addr(pass_slot<PS>(s)) + kk * KSTEP) >> 4), (s | kk) ? 1 : 0);
      if (kk == P_REL || kk == P_CHK || kk == KPS - 1) wg_commit();
      if (kk == KPS - 1 && s == (PS == PS_KV ? KV_LEAD : NS - 1) && bar_id >= 0) bar_arrive(bar_id, 256);
      if (kk == P_REL && s > 0) {
        wg_wait<(P_CHK < P_REL ? 2 : 1)>();
        if (!(PS == PS_WO && s > 3)) rel(pass_slot<PS>(s - 1));
        if (HREL && s <= 6 && nochk) {
#pragma unroll
          for (int i = 2 * s - 2; i < 2 * s; i++) ld16(&a[4 * i], sb, uo, (i >> 2) * TILE + (i & 3) * 2048);
        }
        if (PS == PS_KV && s == 1) {
#pragma unroll
          for (int i = 0; i < 4; i++) asm volatile("xor.b32 %0, %1, %2;" : "=r"(a[i]) : "r"(a[i]), "r"(zero));
        }
      }
      if (kk == P_CHK && s + 1 < NS) prepare(s + 1);
    }
  }
  wg_wait<0>();
  if (PS != PS_WO) rel(pass_slot<PS>(NS - 1));
}

template <int NF> __device__ __forceinline__ void load_frags(uint32_t (&a)[144], const uint8_t* sb, uint32_t uo, uint32_t t) {
#pragma unroll
  for (int i = 0; i < NF; i++) load_frag(a, i, sb, uo, t);
}
__device__ __forceinline__ void ln_scalars(float s1, float s2, uint32_t& m, float& rstd) {
  const float mean = s1 * (1.f / DM);
  const float var = fmaxf(s2 * (1.f / DM) - mean * mean, 0.f);
  m = pack_bf16(mean, mean);
  float sd; asm("sqrt.approx.f32 %0, %1;" : "=f"(sd) : "f"(bf_round(bf_round(var) + 1e-5f)));
  rstd = __fdividef(1.f, bf_round(sd));
}
template <int NF> __device__ __forceinline__ void gather_ln(uint32_t (&a)[144], const uint8_t* sb, uint32_t uo, uint32_t sto,
                                          uint32_t& m0, uint32_t& m1, float& r0, float& r1) {
  uint32_t u[4], v[4];
  const uint32_t t = tid_(), so = sto + (t >> 5) * 1024 + (t & 3) * 256 + (t & 28) * 4;
  ld16(u, sb, so, OFF_ST); ld16(v, sb, so, OFF_ST + 128);
  load_frags<NF>(a, sb, uo, t);
  while (__builtin_expect(__any_sync(0xffffffffu, min(u[0], v[0]) == 0), 0)) { ld16(u, sb, so, OFF_ST); ld16(v, sb, so, OFF_ST + 128); }
  const float a2 = quad_sum(__uint_as_float(u[0]) + __uint_as_float(v[0])), a1 = quad_sum(__uint_as_float(u[1]) + __uint_as_float(v[1]));
  const float b2 = quad_sum(__uint_as_float(u[2]) + __uint_as_float(v[2])), b1 = quad_sum(__uint_as_float(u[3]) + __uint_as_float(v[3]));
  ln_scalars(a1, a2, m0, r0); ln_scalars(b1, b2, m1, r1);
}
struct Stats {
  float s[4] = {0, 0, 0, 0}, d0[4] = {0, 0, 0, 0}, d1[4] = {0, 0, 0, 0};
  __device__ __forceinline__ void add16(const uint32_t* f) {
    mma16816(s, f[0], f[1], f[2], f[3], 0x3f803f80u, 0x3f803f80u);
    mma16816(d0, f[0], f[1], f[2], f[3], f[0], f[2]);
    mma16816(d1, f[0], f[1], f[2], f[3], f[1], f[3]);
  }
  __device__ __forceinline__ float sq0(int g) const { return (g & 1) ? d0[1] : d0[0]; }
  __device__ __forceinline__ float sq1(int g) const { return (g & 1) ? d1[3] : d1[2]; }
};
__device__ __forceinline__ void store_stats18(const uint32_t (&y)[18], uint8_t* sb, uint32_t sto) {
  float s[4] = {0, 0, 0, 0}, u[4] = {0, 0, 0, 0};
#pragma unroll
  for (int i = 0; i < 18; i++) {
    const float lo = bf_lo(y[i]), hi = bf_hi(y[i]);
    const int r = (i & 1) * 2;
    s[r] = fmaf(lo, lo, s[r]); u[r] = fmaf(hi, hi, u[r]); s[r + 1] += lo; u[r + 1] += hi;
  }
#pragma unroll
  for (int i = 0; i < 4; i++) s[i] += u[i];
#pragma unroll
  for (int i = 0; i < 4; i++) s[i] += __shfl_xor_sync(0xffffffffu, s[i], 1);
#pragma unroll
  for (int i = 0; i < 4; i++) s[i] += __shfl_xor_sync(0xffffffffu, s[i], 2);
  const uint32_t t = tid_();
  if ((t & 3) == 0) st16(sb, sto + (t >> 5) * 1024 + (t & 28) * 4, OFF_ST, __float_as_uint(s[0]) | 1u, __float_as_uint(s[1]), __float_as_uint(s[2]), __float_as_uint(s[3]));
}
__device__ __forceinline__ void reduce4(const uint32_t* f, uint32_t* y) {
#pragma unroll
  for (int i = 0; i < 4; i++) {
    float lo = bf_lo(f[i]), hi = bf_hi(f[i]);
#pragma unroll
    for (int s = 1; s < 8; s++) { lo += bf_lo(f[4 * s + i]); hi += bf_hi(f[4 * s + i]); }
    y[i] = pack_bf16(lo, hi);
  }
}

#define TS(i) do {} while (0)
#define TSP(i) do {} while (0)
#define TSH(i) do {} while (0)

struct Params {
  const __nv_bfloat16 *x, *wqkv, *wo, *wg, *wu, *wd;
  __nv_bfloat16* out;
  uint8_t* scr;
  uint8_t* times;
  unsigned zero, zero2;
};

__device__ __forceinline__ void tma_prefetch(const CUtensorMap* m, int c0, int c1) {
  asm volatile("cp.async.bulk.prefetch.tensor.2d.L2.global [%0, {%1, %2}];" ::"l"(m), "r"(c0), "r"(c1) : "memory");
}
__device__ __forceinline__ void fill_packed(int sl, uint32_t par, const uint8_t* src, uint32_t rank, uint32_t own) {
  mbar_wait(bar_empty(sl), par);
  mbar_expect_tx(bar_full(sl), PSLOT);
  if (MC) bulk_load_mc(own + slot_addr(sl) + rank * (PSLOT / 2), src + rank * (PSLOT / 2), PSLOT / 2, own + bar_full(sl));
  else bulk_load(slot_addr(sl), src, PSLOT, bar_full(sl));
}

__global__ void __launch_bounds__(384, 1)
fused_kernel(const __grid_constant__ CUtensorMap map_x, const __grid_constant__ CUtensorMap map_wg,
             const __grid_constant__ CUtensorMap map_wu, const __grid_constant__ CUtensorMap map_wd, const Params P) {
  const int wg = __shfl_sync(0xffffffffu, threadIdx.x >> 7, 0);
  const int cta = blockIdx.x, rank = MC ? cta & 1 : 0, j = MC ? (cta >> 1) & 7 : cta & 7, rb = MC ? (cta >> 4) * 2 + rank : cta >> 3;
  const uint32_t own = win();
  unsigned* const flags = (unsigned*)(P.scr + OFF_FLAGS);
  if (__shfl_sync(0xffffffffu, threadIdx.x >> 5, 0) == 11) {
    if (threadIdx.x == 352) {
#pragma unroll
      for (int i = 0; i < 14; i++) { mbar_init(bar_full(i), 1); mbar_init(bar_empty(i), MC && i < 12 ? 4 : 2); }
      asm volatile("fence.mbarrier_init.release.cluster;" ::: "memory");
      if (smem_u32(smem_raw) != own + SB) asm volatile("trap;");
    }
    __syncwarp();
    bar_arrive(0, 384);
    if (MC) asm volatile("barrier.cluster.arrive.relaxed.aligned;" ::: "memory");
    if (threadIdx.x == 352) {
#pragma unroll 1
      for (int c = 0; c < 9; c++) {
        mbar_expect_tx(bar_full(c), SLOT);
        tma_3d(own + slot_addr(c), &map_x, c * 64, rb * 64, 0, own + bar_full(c));
      }
    }
  } else {
    if (MC) asm volatile("barrier.cluster.arrive.relaxed.aligned;" ::: "memory");
    if (threadIdx.x == 351) sts32(SM_EPOCH, *(volatile unsigned*)&flags[(72 + cta) * 8]);
    if (threadIdx.x < 324) {
      const int k = rb * 36 + (threadIdx.x / 36) * 4 + (threadIdx.x & 3), u = (threadIdx.x % 36) >> 2;
      const uint4* s = (const uint4*)(P.wqkv + k * 1728 + j * 72 + u * 8);
      const uint4 vk = __ldg(s + 72), vv = __ldg(s + 144), vq = __ldg(s);
      const int ko = k < 512 ? ((k >> 4) & 7) * 72 + (k >> 7) * 16 + (k & 15) : ((k >> 3) & 7) * 72 + 64 + (k & 7);
      const uint4 vo = __ldg((const uint4*)(P.wo + ko * 576 + (u < 8 ? (u >> 1) * 128 + j * 16 + (u & 1) * 8 : 512 + j * 8)));
      uint8_t* d = P.scr + OFF_WPACK + j * 24 * PSLOT;
      const uint32_t dkv = (k / 48) * PSLOT + u * 768 + (k % 48) * 16, dq = (k / 96) * PSLOT + u * 1536 + (k % 96) * 16;
      st16(d, dkv, 0, vk.x, vk.y, vk.z, vk.w);
      st16(d, dkv, 9 * 768, vv.x, vv.y, vv.z, vv.w);
      st16(d, dq, 12 * PSLOT, vq.x, vq.y, vq.z, vq.w);
      st16(d, dq, 18 * PSLOT, vo.x, vo.y, vo.z, vo.w);
      if (threadIdx.x == 0) TSP(3);
      asm volatile("fence.proxy.async.global;" ::: "memory");
    }
    bar_sync(0, 384);
  }
  if (MC) { __syncwarp(); asm volatile("barrier.cluster.wait.acquire.aligned;" ::: "memory"); }

  if (wg == 2) {
    asm volatile("setmaxnreg.dec.sync.aligned.u32 24;");
    const int pw = __shfl_sync(0xffffffffu, (threadIdx.x >> 5) & 3, 0), lane = threadIdx.x & 31;
    auto tile_col = [](int t, int j) { return t < 9 ? j * 576 + t * 64 : t == 9 ? 512 : (t - 10) * 128; };
    auto prefetch_tile = [&](int t) {
#pragma unroll 1
      for (int b = rb; b < 18; b += 16) {
        const int h = b & 1, k = b >> 1;
        if (t < 9) tma_prefetch(h ? &map_wu : &map_wg, tile_col(t, j), k * 64);
        else if (t != 9 || !h) tma_prefetch(&map_wd, tile_col(t, j) + h * 64, j * 576 + k * 64);
      }
    };
    if (pw == 0) {
      if (lane == 0) {
        TSP(5);
        flag_signal(&flags[j * 8]);
        TSP(6);
        flag_wait(&flags[j * 8], (lds32(SM_EPOCH) + 1) * 16);
        TSP(7);
        asm volatile("fence.proxy.async.global;" ::: "memory");
        const uint8_t* wp = P.scr + OFF_WPACK + j * 24 * PSLOT;
#pragma unroll 1
        for (int s = 0; s < 3; s++) fill_packed(9 + s, 1, wp + s * PSLOT, rank, own);
#pragma unroll 1
        for (int L = 0; L < 2; L++) {
#pragma unroll 1
          for (int s = 0; s < 21; s++) {
            if (TH && s >= TH) { const int o = s - TH; mbar_wait(bar_full(o < 9 ? o : o - 9), o < 9 || o >= 18); }
            fill_packed(s < 9 ? s : s - 9, s >= 9 && s < 18, wp + (s + 3) * PSLOT, rank, own);
          }
#pragma unroll 1
          for (int t = 0; t < 14; t++) {
            const int p = t - 9;
            const CUtensorMap* ma = p < 0 ? &map_wg : &map_wd;
            const CUtensorMap* mb = p < 0 ? &map_wu : &map_wd;
            const int ca = tile_col(t, j), cb = p < 0 ? ca : ca + 64, r0 = p < 0 ? 0 : j * 576;
            if (L * 14 + t + PF_AHEAD < 28) prefetch_tile((t + PF_AHEAD) % 14);
#pragma unroll 1
            for (int k = 0; k < 9; k++) {
              if (TH && t == 0) mbar_wait(bar_full(k >= TH ? k - TH : k + 12 - TH), 1);
              mbar_wait(bar_empty(k), t & 1);
              mbar_expect_tx(bar_full(k), p == 0 ? 8192 : SLOT);
              const int r = r0 + (p < 0 || k == 8 ? k : k < 3 ? k + 5 : k - 3) * 64;
              if (MC) {
                if (p != 0) tma_2d_mc(own + slot_addr(k) + rank * 8192, rank ? mb : ma, rank ? cb : ca, r, own + bar_full(k));
                else if ((k & 1) == rank) tma_2d_mc(own + slot_addr(k), ma, ca, r, own + bar_full(k));
              } else {
                tma_2d(slot_addr(k), ma, ca, r, bar_full(k));
                if (p != 0) tma_2d(slot_addr(k) + 8192, mb, cb, r, bar_full(k));
              }
            }
            if (p == 1 && L == 0) {
              l2_prefetch(wp + rb * (24 * PSLOT / 16), 24 * PSLOT / 16);
#pragma unroll 1
              for (int s = 0; s < 3; s++) fill_packed(9 + s, 1, wp + s * PSLOT, rank, own);
            }
          }
        }
        flags[(72 + cta) * 8] = lds32(SM_EPOCH) + 1;
      }
    } else if (pw < 3) {
      const int hw = pw - 1;
      const uint32_t ep = __shfl_sync(0xffffffffu, lds32(SM_EPOCH), 0);
      uint8_t* const sb = P.scr + (rb * 2 + hw) * STRM;
      const uint32_t xs = slot_addr(12) + hw * SLOT, fb = bar_full(12) + hw * 8;
#pragma unroll 1
      for (int L = 0; L < 2; L++) {
        const uint32_t tag = ep * 2 + L + 1;
        if (L == 0) flag_wait(flags + (8 + rb) * 8, (ep + 1) * 8);
        bar_sync(NB_FREE + hw, 160);
        if (rb > 0) hint_wait(sb + OFF_HINT + 512 + j * 128, tag);
#pragma unroll 1
        for (int c = 0; c < 3; c++) {
          uint32_t u[4] = {0, 0, 0, 0}, v[4] = {0, 0, 0, 0};
          if (rb > 0) {
            const uint32_t ho = lane * 16 + (L * 8 + j) * 3072 + c * 1024;
            do { ld16(u, sb, ho, OFF_HALO); ld16(v, sb, ho, OFF_HALO + 512); } while (__any_sync(0xffffffffu, u[0] != tag || v[0] != tag));
          }
#pragma unroll
          for (int i = 0; i < 3; i++) sts64(xs + lane * 8 + (c * 3 + i) * 256, u[i + 1], v[i + 1]);
        }
        bar_arrive(NB_HALO + hw, 160);
#pragma unroll 1
        for (int p = 0; p < 4; p++) {
          if (L == 0 && p == 3) flag_wait(flags + (40 + rb) * 8, (ep + 1) * 8);
          bar_sync(NB_FREE + hw, 160);
          TSH(L * 12 + p * 3);
          hint_wait(sb + OFF_HINT + (lane & 3) * 128, (ep * 15 + L * 8 + p + 3) * 8);
          TSH(L * 12 + p * 3 + 1);
          if (lane == 0) {
            mbar_expect_tx(fb, p ? PBUF : PBUF / 2);
            bulk_load(own + xs, sb + OFF_P + j * PSRC + (p ? (p == 2) * PBUF : 2 * PBUF), p ? PBUF : PBUF / 2, own + fb);
          }
          TSH(L * 12 + p * 3 + 2);
        }
      }
    } else {
      timed_wait(bar_full(9));
      if (lane == 0) {
#pragma unroll 1
        for (int t = 0; t < PF_AHEAD; t++) prefetch_tile(t);
      }
#pragma unroll 1
      for (int r = 0; r < 2; r++) {
#pragma unroll 1
        for (int t = r; t < 2 + 2 * r; t++) {
          const uint32_t so = rb * 2 * STRM + lane * 16;
#pragma unroll 1
          for (int i = 0; i < 18; i++) {
            st16(P.scr, so + t * TILE + j * 9216 + i * 512, 0, 0, 0, 0, 0);
            st16(P.scr, so + t * TILE + j * 9216 + i * 512, STRM, 0, 0, 0, 0);
            if (r || (i & 1)) __nanosleep(0);
          }
          if (t != 1) {
            st16(P.scr, so + (t ? t - 1 : 0) * 4096 + j * 512, OFF_ST, 0, 0, 0, 0);
            st16(P.scr, so + (t ? t - 1 : 0) * 4096 + j * 512, OFF_ST + STRM, 0, 0, 0, 0);
          }
        }
        __syncwarp();
        if (lane == 0) flag_signal(flags + (8 + r * 32 + rb) * 8);
        timed_wait(bar_empty(13) - r * 8);
      }
      if (MC) asm volatile("barrier.cluster.arrive.relaxed.aligned;\nbarrier.cluster.wait.aligned;" ::: "memory");
    }
  } else {
    asm volatile("setmaxnreg.inc.sync.aligned.u32 240;");
    const int w = __shfl_sync(0xffffffffu, (threadIdx.x >> 5) & 3, 0);
    const bool leader = (threadIdx.x & 127) == 0;
    const Rel rel{MC ? (threadIdx.x & 95) == 0 : leader, MC ? cta_window(w & 1) : 0};
    uint8_t* const sb = P.scr + (rb * 2 + wg) * STRM;
    uint8_t* const hint = sb + OFF_HINT + w * 128;
    auto hint_target = [](int e) { return (lds32(SM_EPOCH) * 15 + e + 1) * 8; };
    uint32_t a[144];
    TS(0);
#pragma unroll 1
    for (int L = 0; L < 2; L++) {
      uint32_t m0, m1; float r0, r1;
      if (L == 0) {
        Stats t;
        const int lane = tid_() & 31, g = lane >> 2;
        const int row = w * 16 + (lane & 15);
        const uint32_t ra = win() + SB + wg * 8192 + row * 128;
#pragma unroll
        for (int c = 0; c < 9; c++) {
          mbar_wait(bar_full(c), 0);
          if (c == 0) TS(60); if (c == 4) TS(61); if (c == 8) TS(62);
#pragma unroll
          for (int kk = 0; kk < 4; kk++) {
            const int i = c * 16 + kk * 4;
            asm volatile("ldmatrix.sync.aligned.m8n8.x4.shared.b16 {%0,%1,%2,%3}, [%4];"
                         : "=r"(a[i]), "=r"(a[i + 1]), "=r"(a[i + 2]), "=r"(a[i + 3])
                         : "r"(ra + (((kk * 2 + (lane >> 4)) ^ (row & 7)) << 4) + c * SLOT) : "memory");
          }
#pragma unroll
          for (int kk = 0; kk < 4; kk++) t.add16(&a[c * 16 + kk * 4]);
          if (c % 3 == 2) {
            bar_sync(NB_WG + wg, 128);
            rel(c - 2); rel(c - 1); rel(c);
          }
        }
        const int dl = (lane & ~3) | (g >> 1);
        ln_scalars(t.s[0], __shfl_sync(0xffffffffu, t.sq0(g), dl), m0, r0);
        ln_scalars(t.s[2], __shfl_sync(0xffffffffu, t.sq1(g), dl), m1, r1);
      } else {
#pragma unroll
        for (int i = 12 * D_KV; i < 144; i++) a[i] = 0;
        hint_wait(hint, hint_target(7));
        gather_ln<3 * D_KV>(a, sb, OFF_X2, 8192, m0, m1, r0, r1);
      }
      TS(1 + L * 20);
      uint32_t kf[18], vf[18], qf[18];
      {
        float acc[72];
        if (wg == 1) bar_sync(NB_ORD1, 256);
        mma_pass<144, PS_KV, 3, 256, D_KV, true>(acc, a, DESC_KV, 1, rel, wg == 0 ? NB_ORD1 : -1, sb, OFF_X2, L ^ 1, m0, m1, P.zero);
#pragma unroll
        for (int c = 0; c < 9; c++) {
          kf[2 * c] = pack_bf16(acc[4 * c] * r0, acc[4 * c + 1] * r0);
          kf[2 * c + 1] = pack_bf16(acc[4 * c + 2] * r1, acc[4 * c + 3] * r1);
          vf[2 * c] = pack_bf16(acc[36 + 4 * c] * r0, acc[36 + 4 * c + 1] * r0);
          vf[2 * c + 1] = pack_bf16(acc[36 + 4 * c + 2] * r1, acc[36 + 4 * c + 3] * r1);
        }
      }
      TS(2 + L * 20);
      if (w < 3) {
        const uint32_t hs = slot_addr(12) + wg * SLOT + 2304 + w * 2048 + tid_() * 8;
#pragma unroll
        for (int c = 0; c < 9; c++) sts64(hs + c * 256, kf[2 * c + 1], vf[2 * c + 1]);
      } else if (rb < 15) {
        const uint32_t tag = lds32(SM_EPOCH) * 2 + L + 1;
        const uint32_t ho = tid_() * 16 + (L * 8 + j) * 3072;
#pragma unroll
        for (int c = 0; c < 3; c++) {
          st16(sb, ho, 2 * STRM + OFF_HALO - 96 * 16 + c * 1024, tag, kf[6 * c + 1], kf[6 * c + 3], kf[6 * c + 5]);
          st16(sb, ho, 2 * STRM + OFF_HALO - 96 * 16 + c * 1024 + 512, tag, vf[6 * c + 1], vf[6 * c + 3], vf[6 * c + 5]);
        }
        hint_post(sb + 2 * STRM + OFF_HINT + 512 + j * 128);
      }
      bar_arrive(NB_FREE + wg, 160);
      {
        float acc[36];
#pragma unroll
        for (int i = 0; i < 4; i++) asm volatile("xor.b32 %0, %1, %2;" : "=r"(a[i]) : "r"(a[i]), "r"(P.zero2));
        if (wg == 1) bar_sync(NB_ORD1, 256);
        mma_pass<72, PS_Q, 6, 256, 0, false>(acc, a, DESC_Q, 0, rel, -1);
#pragma unroll
        for (int c = 0; c < 9; c++) {
          qf[2 * c] = pack_bf16(acc[4 * c] * r0, acc[4 * c + 1] * r0);
          qf[2 * c + 1] = pack_bf16(acc[4 * c + 2] * r1, acc[4 * c + 3] * r1);
        }
      }
      TS(3 + L * 20);
      uint32_t xr[18];
      {
        uint32_t kh[9], vh[9];
        const int tid = tid_(), g = (tid >> 2) & 7, q = tid & 3;
        bar_sync(NB_HALO + wg, 160);
        {
          const uint32_t hs = slot_addr(12) + wg * SLOT + w * 2048 + tid * 8;
#pragma unroll
          for (int c = 0; c < 9; c++) lds64(kh[c], vh[c], hs + c * 256);
        }
        TS(14 + L * 20);
        const bool nohalo = (rb == 0 && w == 0);
        const bool le0 = 2 * q <= g, le1 = 2 * q + 1 <= g;
        const uint32_t M = (le0 ? 0xffffu : 0u) | (le1 ? 0xffff0000u : 0u);
        const float sc = 0.23570226039551584f * 1.4426950408889634f;
        float l[16], t[8];
#pragma unroll
        for (int h = 0; h < 4; h++) {
          const uint32_t qa0 = q >= h ? qf[4 * h] : 0u, qa1 = q >= h ? qf[4 * h + 1] : 0u;
          const uint32_t qc0 = q <= h ? qf[4 * h + 4] : 0u, qc1 = q <= h ? qf[4 * h + 5] : 0u;
          float sm[4] = {0, 0, 0, 0}, s0[4] = {0, 0, 0, 0}, s1[4] = {0, 0, 0, 0};
          mma16816(s0, qa0, qa1, qf[4 * h + 2], qf[4 * h + 3], kf[4 * h], kf[4 * h + 2]);
          mma16816(s1, qa0, qa1, qf[4 * h + 2], qf[4 * h + 3], kf[4 * h + 1], kf[4 * h + 3]);
          mma16816(sm, qa0, qa1, qf[4 * h + 2], qf[4 * h + 3], kh[2 * h], kh[2 * h + 1]);
          mma1688(s0, qc0, qc1, kf[4 * h + 4]);
          mma1688(s1, qc0, qc1, kf[4 * h + 5]);
          mma1688(sm, qc0, qc1, kh[2 * h + 2]);
          if (nohalo) sm[0] = sm[1] = -1e9f / 0.23570226039551584f;
          l[4 * h] = le0 ? s0[0] : sm[0]; l[4 * h + 1] = le1 ? s0[1] : sm[1];
          l[4 * h + 2] = le0 ? s1[2] : s0[2]; l[4 * h + 3] = le1 ? s1[3] : s0[3];
        }
        uint32_t vt[27];
#pragma unroll
        for (int c = 0; c < 9; c++) { vt[3 * c] = movm_t(vh[c]); vt[3 * c + 1] = movm_t(vf[2 * c]); vt[3 * c + 2] = movm_t(vf[2 * c + 1]); }
#pragma unroll
        for (int i = 0; i < 8; i++) t[i] = fmaxf(l[2 * i], l[2 * i + 1]);
#pragma unroll
        for (int i = 0; i < 8; i++) t[i] = fmaxf(t[i], __shfl_xor_sync(0xffffffffu, t[i], 1));
#pragma unroll
        for (int i = 0; i < 8; i++) t[i] = fmaxf(t[i], __shfl_xor_sync(0xffffffffu, t[i], 2)) * sc;
#pragma unroll
        for (int i = 0; i < 8; i++) { l[2 * i] = ex2(fmaf(l[2 * i], sc, -t[i])); l[2 * i + 1] = ex2(fmaf(l[2 * i + 1], sc, -t[i])); t[i] = l[2 * i] + l[2 * i + 1]; }
#pragma unroll
        for (int i = 0; i < 8; i++) t[i] += __shfl_xor_sync(0xffffffffu, t[i], 1);
#pragma unroll
        for (int i = 0; i < 8; i++) t[i] += __shfl_xor_sync(0xffffffffu, t[i], 2);
        uint32_t pf[16];
#pragma unroll
        for (int i = 0; i < 8; i++) {
          float r; asm("rcp.approx.ftz.f32 %0, %1;" : "=f"(r) : "f"(t[i]));
          const uint32_t p = pack_bf16(l[2 * i] * r, l[2 * i + 1] * r);
          pf[2 * i] = p & ~M; pf[2 * i + 1] = p & M;
        }
#pragma unroll
        for (int c = 0; c < 9; c++) {
          const int h = c == 8 ? 3 : c >> 1;
          float o[4] = {0, 0, 0, 0};
          mma16816(o, pf[4 * h], 0u, pf[4 * h + 1], pf[4 * h + 2], vt[3 * c], vt[3 * c + 1]);
          mma1688(o, 0u, pf[4 * h + 3], vt[3 * c + 2]);
          if (c == 2 || c == 4 || c == 6) {
            float e[4] = {0, 0, 0, 0};
            mma16816(e, pf[4 * h - 4], 0u, pf[4 * h - 3], pf[4 * h - 2], vt[3 * c], vt[3 * c + 1]);
            mma1688(e, 0u, pf[4 * h - 1], vt[3 * c + 2]);
            if (q < h) { o[0] = e[0]; o[1] = e[1]; o[2] = e[2]; o[3] = e[3]; }
          }
          qf[2 * c] = pack_bf16(o[0], o[1]); qf[2 * c + 1] = pack_bf16(o[2], o[3]);
        }
        store_own(qf, sb, OFF_O, j);
        hint_post(hint);
        bar_arrive(NB_ORD1 - wg, 256);
        if (L == 0) {
          const uint32_t xo = (rb * 128 + wg + (w * 16 + g) * 2) * (2 * DM) + q * 4 + j * 16;
#pragma unroll
          for (int c = 0; c < 9; c++) {
            const int o = c < 8 ? (c >> 1) * 256 + (c & 1) * 16 : 1024;
            xr[2 * c] = ldg4(P.x, c < 8 ? xo + j * 16 : xo, o); xr[2 * c + 1] = ldg4(P.x, c < 8 ? xo + j * 16 : xo, o + 32 * DM);
          }
        } else {
          load_own(xr, sb, OFF_X2, j);
        }
      }
      TS(4 + L * 20);
      {
        hint_wait(hint, hint_target(L * 8));
        TS(5 + L * 20);
        load_frags<6 * D_WO>(a, sb, OFF_O, tid_());
        float acc[36];
        if (wg == 0) bar_sync(NB_ORD0, 256);
        mma_pass<72, PS_WO, 6, 256, D_WO, false>(acc, a, DESC_Q, 0, rel, -1, sb, OFF_O);
        TS(6 + L * 20);
#pragma unroll
        for (int c = 0; c < 9; c++) {
          xr[2 * c] = bf2_add(xr[2 * c], pack_bf16(acc[4 * c], acc[4 * c + 1]));
          xr[2 * c + 1] = bf2_add(xr[2 * c + 1], pack_bf16(acc[4 * c + 2], acc[4 * c + 3]));
        }
        store_own(xr, sb, L * 3 * TILE, j);
        store_stats18(xr, sb, L * 4096 + j * 128);
        hint_post(hint);
      }
      TS(16 + L * 20);
      hint_wait(hint, hint_target(L * 8 + 1));
      TS(15 + L * 20);
      gather_ln<4 * D_T0>(a, sb, L * 3 * TILE, L * 4096, m0, m1, r0, r1);
      TS(7 + L * 20);
      const uint32_t hb = (L ^ 1) * TILE + j * 9216;
      {
        const float ka0 = 0.7978845608028654f * r0, kb0 = 0.035677408136300125f * r0 * r0 * r0, kc0 = 0.5f * r0 * r0;
        const float ka1 = 0.7978845608028654f * r1, kb1 = 0.035677408136300125f * r1 * r1 * r1, kc1 = 0.5f * r1 * r1;
        float acc[64];
        uint32_t hf[16];
        auto geglu = [&](auto chains, uint32_t hsm) {
          constexpr int CH = decltype(chains)::value;
          float r[32];
#pragma unroll
          for (int e = 0; e < 32; e++) {
            float x = acc[e];
            if (e >= CH) x = __uint_as_float(__float_as_uint(x) ^ (__float_as_uint(r[e - CH]) & P.zero));
            if (CH != 2 && e < 20) {
              const uint32_t ad = (e < 8 ? slot_addr(12) + e * 2048 + wg * 8192 : slot_addr(7 + (e >> 2)) + (e & 3) * 2048) + hsm;
              lds128(&a[48 + 4 * e], e >= CH ? ad ^ (__float_as_uint(r[e - CH]) & P.zero) : ad);
            }
            const bool hi = e & 2;
            float t = x * fmaf(x * x, hi ? kb1 : kb0, hi ? ka1 : ka0);
            asm("tanh.approx.f32 %0, %0;" : "+f"(t));
            const float u = x * acc[32 + e] * (hi ? kc1 : kc0);
            r[e] = fmaf(u, t, u);
            if (e & 1) hf[e >> 1] = pack_bf16(r[e - 1], r[e]);
          }
        };
        if (wg == 1) bar_sync(NB_ORD1, 256);
        mma_pass<128, PS_FF, 4, 2048, D_T0, true>(acc, a, DESC_SW128, 1, rel, NB_ORD1 - wg, sb, L * 3 * TILE, 0, m0, m1);
        TS(8 + L * 20);
#pragma unroll 1
        for (int t = 0; t < 8; t++) {
          geglu(IntC<2>(), 0);
          const uint32_t t16 = tid_() * 16;
          if (t < 5) {
            const uint32_t d = (t < 2 ? slot_addr(12) + wg * SLOT + t * 8192 : slot_addr(7) + t * SLOT + wg * 8192) + t16;
#pragma unroll
            for (int i = 0; i < 4; i++)
              sts128(d + i * 2048, hf[4 * i], hf[4 * i + 1], hf[4 * i + 2], hf[4 * i + 3]);
            if (t == 4) asm volatile("fence.proxy.async.shared::cta;" ::: "memory");
          } else {
#pragma unroll
            for (int i = 0; i < 4; i++) st16(sb, hb + (t - 5) * TILE + t16, i * 2048, hf[4 * i], hf[4 * i + 1], hf[4 * i + 2], hf[4 * i + 3]);
          }
          bar_sync(NB_ORD0 + wg, 256);
          mma_pass<128, PS_FF, 4, 2048, 0, false, true>(acc, a, DESC_SW128, t & 1, rel, NB_ORD1 - wg, sb, hb + t16, t == 7);
        }
        TS(9 + L * 20);
        const uint32_t hsm = wg * 8192 + tid_() * 16;
        geglu(IntC<CH_LAST>(), hsm);
#pragma unroll
        for (int i = 0; i < 16; i++) a[128 + i] = hf[i];
      }
      TS(10 + L * 20);
      {
        auto ytail = [](uint32_t k) { return k < 3 ? slot_addr(9) + PSLOT + k * SLOT : BARS + 256; };
        const uint32_t xs = slot_addr(12) + wg * SLOT;
        {
          bar_sync(NB_ORD0 + wg + ((a[142] | a[143]) & P.zero), 256);
          TS(64 + L * 32);
          rel(9); rel(10); rel(11);
          float acc[32];
          mma_pass<64, PS_FF, 4, 2048, 0, false>(acc, a, DESC_SW128, 0, rel, NB_ORD1 - wg);
          TS(65 + L * 32);
          const uint32_t t8 = tid_() * 8;
#pragma unroll
          for (int i = 0; i < 8; i++) {
            const uint32_t u = pack_bf16(acc[4 * i], acc[4 * i + 1]), v = pack_bf16(acc[4 * i + 2], acc[4 * i + 3]);
            if (i == j) sts64(xs + PBUF + t8 * 2, u, v);
            else st8(sb, ((j - i - 1) & 7) * 1024 + t8, OFF_P + 2 * PBUF + i * PSRC, (u & ~1u) | (L ^ 1), v);
          }
          hint_post(hint);
          if (L == 0 && tid_() == 0) mbar_arrive(bar_empty(13));
          bar_arrive(NB_FREE + wg, 160);
          TS(68 + L * 32);
        }
        uint32_t y[18];
#pragma unroll 1
        for (int p = 1; p < 5; p++) {
          bar_sync(NB_ORD0 + wg, 256);
          TS(64 + L * 32 + p * 5);
          uint32_t in[32];
          const uint32_t t16 = tid_() * 16;
          {
            float acc[64];
            mma_pass<128, PS_FF, 4, 2048, 0, false>(acc, a, DESC_SW128, p & 1, rel, (p == 4 && wg == 1) ? -1 : NB_ORD1 - wg);
            TS(65 + L * 32 + p * 5);
            lds128(&in[28], xs + PBUF + t16);
            mbar_wait(bar_full(12) + wg * 8, (p & 1) ^ 1);
            TS(66 + L * 32 + p * 5);
            {
              const uint32_t flip = p == 1 ? L - 1 : p < 4 ? ~0u : 0u;
              const uint32_t sh = p == 1;
              uint32_t m = 0;
#pragma unroll
              for (int s = 0; s < 7; s++) m |= lds32(xs + ((s * 2048 + t16) >> sh)) ^ flip;
              if (__builtin_expect(__any_sync(0xffffffffu, m & 1), 0)) {
#pragma unroll 1
                for (int s = 0; s < 7; s++) {
                  const uint32_t o = (s * 2048 + t16) >> sh;
                  uint32_t v[4] = {0, 0, 0, 0};
                  do {
                    if (sh) ld8(v, sb, j * PSRC + o, OFF_P + 2 * PBUF);
                    else ld16(v, sb, j * PSRC + (p & 1) * PBUF + o, OFF_P);
                  } while ((v[0] ^ flip) & 1);
                  sts64(xs + o, v[0], v[1]);
                  if (!sh) sts64(xs + o + 8, v[2], v[3]);
                }
                asm volatile("fence.proxy.async.shared::cta;" ::: "memory");
              }
            }
#pragma unroll
            for (int i = 0; i < 8; i++) {
              const uint32_t u0 = pack_bf16(acc[8 * i], acc[8 * i + 1]), u1 = pack_bf16(acc[8 * i + 2], acc[8 * i + 3]);
              const uint32_t u2 = pack_bf16(acc[8 * i + 4], acc[8 * i + 5]), u3 = pack_bf16(acc[8 * i + 6], acc[8 * i + 7]);
              if (i == j) sts128(xs + PBUF + t16, u0, u1, u2, u3);
              else st16(sb, ((j - i - 1) & 7) * 2048 + ((p & 1) ^ 1) * PBUF + t16, OFF_P + i * PSRC, (u0 & ~1u) | (p < 3), u1, u2, u3);
            }
          }
          hint_post(hint);
          TS(68 + L * 32 + p * 5);
          if (p == 1) {
#pragma unroll
            for (int s = 0; s < 7; s++) {
              lds64(in[4 * s], in[4 * s + 1], xs + s * 1024 + t16 / 2);
              in[4 * s + 2] = in[4 * s + 3] = 0;
            }
          } else {
#pragma unroll
            for (int s = 0; s < 7; s++) lds128(&in[4 * s], xs + s * 2048 + t16);
          }
          if (p < 4) bar_arrive(NB_FREE + wg, 160);
          reduce4(in, y + 8);
          if (p == 1) sts64(ytail(wg * 2 + (t16 >> 10)) + 2048 + (t16 & 1023) / 2, y[8], y[9]);
          else if (p < 4) sts128(ytail(wg * 2 + p - 2) + t16, y[8], y[9], y[10], y[11]);
          TS(67 + L * 32 + p * 5);
        }
        TS(11 + L * 20);
        const uint32_t t = tid_();
#pragma unroll
        for (int i = 0; i < 2; i++) lds128(&y[4 * i], ytail(wg * 2 + i) + t * 16);
        lds128(&a[28], xs + PBUF + t * 16);
        lds64(y[16], y[17], ytail(wg * 2 + (t >> 6)) + 2048 + (t & 63) * 8);
        load_own(xr, sb, L * 3 * TILE, j);
        hint_wait(hint, hint_target(L * 8 + 6));
        TS(17 + L * 20);
        {
          uint32_t m;
          do {
            m = 0;
#pragma unroll
            for (int s = 0; s < 7; s++) { ld16(&a[4 * s], sb, j * PSRC + t * 16, OFF_P + PBUF + s * 2048); m |= a[4 * s]; }
          } while (__any_sync(0xffffffffu, m & 1));
          TS(12 + L * 20);
          reduce4(a, y + 12);
        }
#pragma unroll
        for (int i = 0; i < 18; i++) xr[i] = bf2_add(xr[i], y[i]);
        TS(18 + L * 20);
        if (L == 0) {
          store_own(xr, sb, OFF_X2, j);
          store_stats18(xr, sb, 8192 + j * 128);
          hint_post(hint);
        } else {
          const uint32_t xo = (rb * 128 + wg + (w * 16 + ((t >> 2) & 7)) * 2) * (2 * DM) + (t & 3) * 4 + j * 16;
#pragma unroll
          for (int c = 0; c < 9; c++) {
            const int o = c < 8 ? (c >> 1) * 256 + (c & 1) * 16 : 1024;
            stg4(P.out, c < 8 ? xo + j * 16 : xo, o, xr[2 * c]); stg4(P.out, c < 8 ? xo + j * 16 : xo, o + 32 * DM, xr[2 * c + 1]);
          }
        }
      }
      TS(13 + L * 20);
    }
    bar_sync(NB_WG + wg, 128);
    if (tid_() == 0) mbar_arrive(bar_empty(12));
  }
}

typedef CUresult (*EncodeFn)(CUtensorMap*, CUtensorMapDataType, cuuint32_t, void*, const cuuint64_t*, const cuuint64_t*, const cuuint32_t*,
                             const cuuint32_t*, CUtensorMapInterleave, CUtensorMapSwizzle, CUtensorMapL2promotion, CUtensorMapFloatOOBfill);

void encode(EncodeFn fn, CUtensorMap* m, const void* p, int rank, const cuuint64_t* dims, const cuuint64_t* str, const cuuint32_t* box) {
  const cuuint32_t es[3] = {1, 1, 1};
  fn(m, CU_TENSOR_MAP_DATA_TYPE_BFLOAT16, rank, const_cast<void*>(p), dims, str, box, es, CU_TENSOR_MAP_INTERLEAVE_NONE,
     CU_TENSOR_MAP_SWIZZLE_128B, CU_TENSOR_MAP_L2_PROMOTION_L2_256B, CU_TENSOR_MAP_FLOAT_OOB_FILL_NONE);
}

}

extern "C" void kernel_launch(void* const* d_in, const int* in_sizes, int n_in, void* d_out, int out_size) {
  (void)in_sizes; (void)n_in; (void)out_size;
  Params P;
  P.x = (const __nv_bfloat16*)d_in[0]; P.wqkv = (const __nv_bfloat16*)d_in[1]; P.wo = (const __nv_bfloat16*)d_in[2];
  P.wg = (const __nv_bfloat16*)d_in[4]; P.wu = (const __nv_bfloat16*)d_in[5]; P.wd = (const __nv_bfloat16*)d_in[6];
  P.out = (__nv_bfloat16*)d_out; P.zero = 0; P.zero2 = 0;
  cudaGetSymbolAddress((void**)&P.scr, g_scr);
  void* fnp = nullptr; cudaDriverEntryPointQueryResult qr;
  cudaGetDriverEntryPoint("cuTensorMapEncodeTiled", &fnp, cudaEnableDefault, &qr);
  EncodeFn fn = (EncodeFn)fnp;
  CUtensorMap mx, mg, mu, md;
  { const cuuint64_t dims[3] = {DM, SEQ / 2, 2}, str[2] = {DM * 4, DM * 2}; const cuuint32_t box[3] = {64, 64, 2}; encode(fn, &mx, P.x, 3, dims, str, box); }
  { const cuuint64_t dims[2] = {DFF, DM}, str[1] = {DFF * 2}; const cuuint32_t box[2] = {64, 64}; encode(fn, &mg, P.wg, 2, dims, str, box); encode(fn, &mu, P.wu, 2, dims, str, box); }
  { const cuuint64_t dims[2] = {DM, DFF}, str[1] = {DM * 2}; const cuuint32_t box[2] = {64, 64}; encode(fn, &md, P.wd, 2, dims, str, box); }
  cudaFuncSetAttribute(fused_kernel, cudaFuncAttributeMaxDynamicSharedMemorySize, SMEM_BYTES);
  cudaLaunchConfig_t cfg = {};
  cfg.gridDim = dim3(128); cfg.blockDim = dim3(384); cfg.dynamicSmemBytes = SMEM_BYTES; cfg.stream = cudaStreamPerThread;
  cudaLaunchAttribute at[1];
  at[0].id = cudaLaunchAttributeClusterDimension; at[0].val.clusterDim.x = MC ? 2 : 1; at[0].val.clusterDim.y = 1; at[0].val.clusterDim.z = 1;
  cfg.attrs = at; cfg.numAttrs = 1;
  cudaLaunchKernelEx(&cfg, fused_kernel, mx, mg, mu, md, P);
}
```

```cpp
#include <cuda_runtime.h>
#include <cuda_bf16.h>
#include <cuda.h>
#include <stdint.h>

#define KV_LEAD 5
#define D_KV 8
#define D_WO 5
#define D_T0 6
#define PF_AHEAD 3
#define CH_LAST 4
#define TH 2
#define MC 1
#define MAP 1
#define XMODE 0
#define XDL 20
#define TIMING 0

namespace {

constexpr int SEQ = 2048, DM = 576, DFF = 4608;
constexpr uint32_t SB = 1024;
constexpr uint32_t SLOT = 16384;
constexpr uint32_t PSLOT = 13824;
constexpr uint32_t BARS = SB + 14 * SLOT;
constexpr int SMEM_BYTES = 14 * SLOT + 256 + 2560;
__host__ __device__ constexpr uint32_t slot_addr(int s) { return SB + s * SLOT; }
__host__ __device__ constexpr uint32_t bar_full(int s) { return BARS + 8 * s; }
__host__ __device__ constexpr uint32_t bar_empty(int s) { return BARS + 128 + 8 * s; }
enum { NB_ORD0 = 1, NB_ORD1 = 2, NB_WG = 3  , NB_HALO = 5  , NB_FREE = 7   };
constexpr uint32_t SM_EPOCH = BARS + 120;
__host__ __device__ constexpr uint32_t ytail(uint32_t k) { return k < 3 ? slot_addr(9) + PSLOT + k * SLOT : BARS + 256; }
constexpr uint32_t KSTG = 9 * 1152;

constexpr uint32_t TILE = 36 * 2048;
constexpr uint32_t OFF_X1 = 0  , OFF_O = TILE, OFF_X2 = 2 * TILE, OFF_ST = 4 * TILE  ;
constexpr uint32_t PBUF = 7 * 2048, PSRC = 2 * PBUF + PBUF / 2;
constexpr uint32_t OFF_P = OFF_ST + 3 * 4096, OFF_HALO = OFF_P + 8 * PSRC  , OFF_HINT = OFF_HALO + 2 * 8 * 3072  ,
                   STRM = OFF_HINT + 12 * 128;
constexpr uint32_t OFF_WPACK = 32 * STRM, OFF_FLAGS = OFF_WPACK + 8 * 24 * PSLOT;
__device__ __align__(1024) uint8_t g_scr[OFF_FLAGS + (8 + 64 + 128) * 32];

__device__ __forceinline__ uint32_t smem_u32(const void* p) { return (uint32_t)__cvta_generic_to_shared(p); }
extern __shared__ __align__(1024) uint8_t smem_raw[];
__device__ __forceinline__ uint32_t win() { return MC ? (blockIdx.x & 1) << 24 : 0; }
#define SA(A, W) ".reg .u32 sa;\nadd.u32 sa, " A ", " W ";\n"
__device__ __forceinline__ void mbar_init(uint32_t bar, uint32_t cnt) { asm volatile("{\n" SA("%0", "%2") "mbarrier.init.shared::cta.b64 [sa], %1;\n}" ::"r"(bar), "r"(cnt), "r"(win())); }
__device__ __forceinline__ void mbar_expect_tx(uint32_t bar, uint32_t bytes) { asm volatile("{\n" SA("%0", "%2") "mbarrier.arrive.expect_tx.shared::cta.b64 _, [sa], %1;\n}" ::"r"(bar), "r"(bytes), "r"(win()) : "memory"); }
__device__ __forceinline__ void mbar_arrive(uint32_t bar) { asm volatile("{\n" SA("%0", "%1") "mbarrier.arrive.shared::cta.b64 _, [sa];\n}" ::"r"(bar), "r"(win()) : "memory"); }
__device__ __forceinline__ uint32_t lds32(uint32_t a) { uint32_t v; asm volatile("{\n" SA("%1", "%2") "ld.shared.u32 %0, [sa];\n}" : "=r"(v) : "r"(a), "r"(win()) : "memory"); return v; }
__device__ __forceinline__ void lds64(uint32_t& x, uint32_t& y, uint32_t a) { asm volatile("{\n" SA("%2", "%3") "ld.shared.v2.u32 {%0,%1}, [sa];\n}" : "=r"(x), "=r"(y) : "r"(a), "r"(win()) : "memory"); }
__device__ __forceinline__ void lds128(uint32_t* v, uint32_t a) {
  asm volatile("{\n" SA("%4", "%5") "ld.shared.v4.u32 {%0,%1,%2,%3}, [sa];\n}" : "=r"(v[0]), "=r"(v[1]), "=r"(v[2]), "=r"(v[3]) : "r"(a), "r"(win()) : "memory");
}
__device__ __forceinline__ void stsm4(uint32_t a, uint32_t x, uint32_t y, uint32_t z, uint32_t w) {
  asm volatile("{\n" SA("%0", "%5") "stmatrix.sync.aligned.m8n8.x4.shared.b16 [sa], {%1,%2,%3,%4};\n}" ::"r"(a), "r"(x), "r"(y), "r"(z), "r"(w), "r"(win()) : "memory");
}
__device__ __forceinline__ void ldsm4(uint32_t* v, uint32_t a) {
  asm volatile("{\n" SA("%4", "%5") "ldmatrix.sync.aligned.m8n8.x4.shared.b16 {%0,%1,%2,%3}, [sa];\n}" : "=r"(v[0]), "=r"(v[1]), "=r"(v[2]), "=r"(v[3]) : "r"(a), "r"(win()) : "memory");
}
__device__ __forceinline__ void ldsm4t(uint32_t* v, uint32_t a) {
  asm volatile("{\n" SA("%4", "%5") "ldmatrix.sync.aligned.m8n8.x4.trans.shared.b16 {%0,%1,%2,%3}, [sa];\n}" : "=r"(v[0]), "=r"(v[1]), "=r"(v[2]), "=r"(v[3]) : "r"(a), "r"(win()) : "memory");
}
__device__ __forceinline__ void sts32(uint32_t a, uint32_t x) { asm volatile("{\n" SA("%0", "%2") "st.shared.u32 [sa], %1;\n}" ::"r"(a), "r"(x), "r"(win()) : "memory"); }
__device__ __forceinline__ void sts64(uint32_t a, uint32_t x, uint32_t y) { asm volatile("{\n" SA("%0", "%3") "st.shared.v2.u32 [sa], {%1,%2};\n}" ::"r"(a), "r"(x), "r"(y), "r"(win()) : "memory"); }
__device__ __forceinline__ void sts128(uint32_t a, uint32_t x, uint32_t y, uint32_t z, uint32_t w) {
  asm volatile("{\n" SA("%0", "%5") "st.shared.v4.u32 [sa], {%1,%2,%3,%4};\n}" ::"r"(a), "r"(x), "r"(y), "r"(z), "r"(w), "r"(win()) : "memory");
}
__device__ __forceinline__ void mbar_wait(uint32_t bar, uint32_t parity) {
  asm volatile("{\n.reg .pred p;\n" SA("%0", "%2") "LAB_WAIT:\nmbarrier.try_wait.parity.shared::cta.b64 p, [sa], %1;\n@!p bra LAB_WAIT;\n}" ::"r"(bar), "r"(parity), "r"(win()) : "memory");
}
__device__ __forceinline__ void timed_wait(uint32_t bar) {
  asm volatile("{\n.reg .pred p;\n.reg .u64 t0, t1;\nmov.u64 t0, %%globaltimer;\nLAB_WD:\n"
               "mbarrier.try_wait.parity.shared::cta.b64 p, [%0], 0, 100000;\n@p bra LAB_OK;\n"
               "mov.u64 t1, %%globaltimer;\nsub.u64 t1, t1, t0;\nsetp.lt.u64 p, t1, 2000000000;\n@p bra LAB_WD;\ntrap;\nLAB_OK:\n}" ::"r"(bar + win()) : "memory");
}
__device__ __forceinline__ void flag_wait(const unsigned* flag, unsigned target) {
  asm volatile("{\n.reg .pred p;\n.reg .u32 v;\nLAB_WAIT:\nld.acquire.gpu.global.u32 v, [%0];\nsub.u32 v, v, %1;\n"
               "setp.lt.s32 p, v, 0;\n@p nanosleep.u32 100;\n@p bra LAB_WAIT;\n}" ::"l"(flag), "r"(target) : "memory");
}
__device__ __forceinline__ void hint_post(uint8_t* p) {
  __syncwarp();
  asm volatile("{\n.reg .pred p;\nelect.sync _|p, 0xffffffff;\n@p red.relaxed.gpu.global.add.u32 [%0], 1;\n}" ::"l"(p) : "memory");
}
__device__ __forceinline__ void hint_wait(const uint8_t* p, uint32_t target) {
  asm volatile("{\n.reg .pred p;\n.reg .u32 v;\nLAB_WAIT:\nld.relaxed.gpu.global.u32 v, [%0];\nsub.u32 v, v, %1;\n"
               "setp.lt.s32 p, v, 0;\nvote.sync.any.pred p, p, 0xffffffff;\n@p bra LAB_WAIT;\n}" ::"l"(p), "r"(target) : "memory");
}
__device__ __forceinline__ void flag_signal(unsigned* flag) { asm volatile("red.release.gpu.global.add.u32 [%0], 1;" ::"l"(flag) : "memory"); }
struct Rel {
  bool on; uint32_t base;
  __device__ __forceinline__ void operator()(int s) const {
    if (on) {
      if (MC) asm volatile("{\n" SA("%0", "%1") "mbarrier.arrive.shared::cluster.b64 _, [sa];\n}" ::"r"(bar_empty(s)), "r"(base) : "memory");
      else mbar_arrive(bar_empty(s));
    }
  }
};
__device__ __forceinline__ uint32_t cta_window(uint32_t rank) { uint32_t a; asm("mapa.shared::cluster.u32 %0, %1, %2;" : "=r"(a) : "r"(0), "r"(rank)); return a; }
__device__ __forceinline__ void tma_2d_mc(uint32_t dst, const CUtensorMap* m, int c0, int c1, uint32_t bar) {
  asm volatile("cp.async.bulk.tensor.2d.shared::cluster.global.mbarrier::complete_tx::bytes.multicast::cluster [%0], [%1, {%3, %4}], [%2], %5;"
               ::"r"(dst), "l"(m), "r"(bar), "r"(c0), "r"(c1), "h"((uint16_t)3) : "memory");
}
__device__ __forceinline__ void bulk_load_mc(uint32_t dst, const void* src, uint32_t bytes, uint32_t bar) {
  asm volatile("cp.async.bulk.shared::cluster.global.mbarrier::complete_tx::bytes.multicast::cluster [%0], [%1], %2, [%3], %4;"
               ::"r"(dst), "l"(src), "r"(bytes), "r"(bar), "h"((uint16_t)3) : "memory");
}
__device__ __forceinline__ void tma_2d(uint32_t dst, const CUtensorMap* m, int c0, int c1, uint32_t bar) {
  asm volatile("cp.async.bulk.tensor.2d.shared::cluster.global.mbarrier::complete_tx::bytes [%0], [%1, {%3, %4}], [%2];"
               ::"r"(dst), "l"(m), "r"(bar), "r"(c0), "r"(c1) : "memory");
}
__device__ __forceinline__ void tma_3d(uint32_t dst, const CUtensorMap* m, int c0, int c1, int c2, uint32_t bar) {
  asm volatile("cp.async.bulk.tensor.3d.shared::cluster.global.mbarrier::complete_tx::bytes [%0], [%1, {%3, %4, %5}], [%2];"
               ::"r"(dst), "l"(m), "r"(bar), "r"(c0), "r"(c1), "r"(c2) : "memory");
}
__device__ __forceinline__ void bulk_load(uint32_t dst, const void* src, uint32_t bytes, uint32_t bar) {
  asm volatile("cp.async.bulk.shared::cluster.global.mbarrier::complete_tx::bytes [%0], [%1], %2, [%3];" ::"r"(dst), "l"(src), "r"(bytes), "r"(bar) : "memory");
}
__device__ __forceinline__ void l2_prefetch(const void* src, uint32_t bytes) { asm volatile("cp.async.bulk.prefetch.L2.global [%0], %1;" ::"l"(src), "r"(bytes) : "memory"); }
__device__ __forceinline__ void wg_fence() { asm volatile("wgmma.fence.sync.aligned;" ::: "memory"); }
__device__ __forceinline__ void wg_commit() { asm volatile("wgmma.commit_group.sync.aligned;" ::: "memory"); }
template <int N> __device__ __forceinline__ void wg_wait() { asm volatile("wgmma.wait_group.sync.aligned %0;" ::"n"(N) : "memory"); }
__device__ __forceinline__ void bar_sync(int id, int n) { asm volatile("bar.sync %0, %1;" ::"r"(id), "r"(n) : "memory"); }
__device__ __forceinline__ void bar_arrive(int id, int n) { asm volatile("bar.arrive %0, %1;" ::"r"(id), "r"(n) : "memory"); }
__device__ __forceinline__ uint32_t pack_bf16(float lo, float hi) { uint32_t r; asm("cvt.rn.bf16x2.f32 %0, %1, %2;" : "=r"(r) : "f"(hi), "f"(lo)); return r; }
__device__ __forceinline__ float bf_lo(uint32_t w) { return __uint_as_float(w << 16); }
__device__ __forceinline__ float bf_hi(uint32_t w) { return __uint_as_float(w & 0xffff0000u); }
__device__ __forceinline__ float bf_round(float x) { return bf_lo(pack_bf16(x, 0.f)); }
__device__ __forceinline__ uint32_t bf2_sub(uint32_t a, uint32_t b) { uint32_t r; asm("sub.rn.bf16x2 %0, %1, %2;" : "=r"(r) : "r"(a), "r"(b)); return r; }
__device__ __forceinline__ uint32_t bf2_add(uint32_t a, uint32_t b) { uint32_t r; asm("add.rn.bf16x2 %0, %1, %2;" : "=r"(r) : "r"(a), "r"(b)); return r; }
#define GADDR(B, O, I) "cvt.u64.u32 ad, " O ";\nadd.u64 ad, ad, " B ";\nadd.u64 ad, ad, " I ";\n"
__device__ __forceinline__ void ld16(uint32_t* v, const uint8_t* ub, uint32_t off, uint32_t imm) {
  asm volatile("{\n.reg .b128 z;\n.reg .b64 x, y, ad;\n" GADDR("%4", "%5", "%6") "ld.relaxed.gpu.global.b128 z, [ad];\n"
               "mov.b128 {x, y}, z;\nmov.b64 {%0,%1}, x;\nmov.b64 {%2,%3}, y;\n}"
               : "=r"(v[0]), "=r"(v[1]), "=r"(v[2]), "=r"(v[3]) : "l"(ub), "r"(off), "l"((uint64_t)imm) : "memory");
}
__device__ __forceinline__ void ld8(uint32_t* v, const uint8_t* ub, uint32_t off, uint32_t imm) {
  asm volatile("{\n.reg .b64 x, ad;\n" GADDR("%2", "%3", "%4") "ld.relaxed.gpu.global.b64 x, [ad];\nmov.b64 {%0,%1}, x;\n}"
               : "=r"(v[0]), "=r"(v[1]) : "l"(ub), "r"(off), "l"((uint64_t)imm) : "memory");
}
__device__ __forceinline__ void st16(uint8_t* ub, uint32_t off, uint32_t imm, uint32_t a, uint32_t b, uint32_t c, uint32_t d) {
  asm volatile("{\n.reg .b128 z;\n.reg .b64 x, y, ad;\n" GADDR("%0", "%1", "%2") "mov.b64 x, {%3,%4};\nmov.b64 y, {%5,%6};\nmov.b128 z, {x, y};\n"
               "st.relaxed.gpu.global.b128 [ad], z;\n}" ::"l"(ub), "r"(off), "l"((uint64_t)imm), "r"(a), "r"(b), "r"(c), "r"(d) : "memory");
}
__device__ __forceinline__ void st8(uint8_t* ub, uint32_t off, uint32_t imm, uint32_t a, uint32_t b) {
  asm volatile("{\n.reg .b64 x, ad;\n" GADDR("%0", "%1", "%2") "mov.b64 x, {%3,%4};\nst.relaxed.gpu.global.b64 [ad], x;\n}"
               ::"l"(ub), "r"(off), "l"((uint64_t)imm), "r"(a), "r"(b) : "memory");
}
__device__ __forceinline__ uint32_t ldg4(const void* ub, uint32_t off, uint32_t imm) {
  uint32_t v; asm volatile("{\n.reg .b64 ad;\n" GADDR("%1", "%2", "%3") "ld.global.nc.u32 %0, [ad];\n}" : "=r"(v) : "l"(ub), "r"(off), "l"((uint64_t)imm)); return v;
}
__device__ __forceinline__ void stg4(void* ub, uint32_t off, uint32_t imm, uint32_t v) {
  asm volatile("{\n.reg .b64 ad;\n" GADDR("%0", "%1", "%2") "st.global.u32 [ad], %3;\n}" ::"l"(ub), "r"(off), "l"((uint64_t)imm), "r"(v) : "memory");
}
__device__ __forceinline__ uint32_t tid_() { uint32_t t; asm volatile("mov.u32 %0, %%tid.x;" : "=r"(t)); return t & 127; }
__device__ __forceinline__ uint32_t nz(uint32_t w) { return max(w, 1u); }
__device__ __forceinline__ void mma16816(float (&c)[4], uint32_t a0, uint32_t a1, uint32_t a2, uint32_t a3, uint32_t b0, uint32_t b1) {
  asm("mma.sync.aligned.m16n8k16.row.col.f32.bf16.bf16.f32 {%0,%1,%2,%3}, {%4,%5,%6,%7}, {%8,%9}, {%0,%1,%2,%3};"
               : "+f"(c[0]), "+f"(c[1]), "+f"(c[2]), "+f"(c[3]) : "r"(a0), "r"(a1), "r"(a2), "r"(a3), "r"(b0), "r"(b1));
}
__device__ __forceinline__ void mma1688(float (&c)[4], uint32_t a0, uint32_t a1, uint32_t b0) {
  asm("mma.sync.aligned.m16n8k8.row.col.f32.bf16.bf16.f32 {%0,%1,%2,%3}, {%4,%5}, {%6}, {%0,%1,%2,%3};"
               : "+f"(c[0]), "+f"(c[1]), "+f"(c[2]), "+f"(c[3]) : "r"(a0), "r"(a1), "r"(b0));
}
__device__ __forceinline__ float ex2(float x) { float r; asm("ex2.approx.ftz.f32 %0, %1;" : "=f"(r) : "f"(x)); return r; }
__device__ __forceinline__ float quad_sum(float v) { v += __shfl_xor_sync(0xffffffffu, v, 1); v += __shfl_xor_sync(0xffffffffu, v, 2); return v; }
__device__ __forceinline__ float quad_max(float v) { v = fmaxf(v, __shfl_xor_sync(0xffffffffu, v, 1)); v = fmaxf(v, __shfl_xor_sync(0xffffffffu, v, 2)); return v; }

__device__ __forceinline__ void wgmma_rs_n64(float (&d)[32], uint32_t a0, uint32_t a1, uint32_t a2, uint32_t a3, uint64_t desc, int scale_d) {
  asm volatile("{\n.reg .pred p;\nsetp.ne.b32 p, %37, 0;\n"
    "wgmma.mma_async.sync.aligned.m64n64k16.f32.bf16.bf16 "
    "{%0, %1, %2, %3, %4, %5, %6, %7, %8, %9, %10, %11, %12, %13, %14, %15, %16, %17, %18, %19, %20, %21, %22, %23, %24, %25, %26, %27, %28, %29, %30, %31}, "
    "{%32, %33, %34, %35}, %36, p, 1, 1, 1;\n}\n"
    : "+f"(d[0]), "+f"(d[1]), "+f"(d[2]), "+f"(d[3]), "+f"(d[4]), "+f"(d[5]), "+f"(d[6]), "+f"(d[7]), "+f"(d[8]), "+f"(d[9]), "+f"(d[10]), "+f"(d[11]), "+f"(d[12]), "+f"(d[13]), "+f"(d[14]), "+f"(d[15]), "+f"(d[16]), "+f"(d[17]), "+f"(d[18]), "+f"(d[19]), "+f"(d[20]), "+f"(d[21]), "+f"(d[22]), "+f"(d[23]), "+f"(d[24]), "+f"(d[25]), "+f"(d[26]), "+f"(d[27]), "+f"(d[28]), "+f"(d[29]), "+f"(d[30]), "+f"(d[31])
    : "r"(a0), "r"(a1), "r"(a2), "r"(a3), "l"(desc), "r"(scale_d));
}

__device__ __forceinline__ void wgmma_rs_n72(float (&d)[36], uint32_t a0, uint32_t a1, uint32_t a2, uint32_t a3, uint64_t desc, int scale_d) {
  asm volatile("{\n.reg .pred p;\nsetp.ne.b32 p, %41, 0;\n"
    "wgmma.mma_async.sync.aligned.m64n72k16.f32.bf16.bf16 "
    "{%0, %1, %2, %3, %4, %5, %6, %7, %8, %9, %10, %11, %12, %13, %14, %15, %16, %17, %18, %19, %20, %21, %22, %23, %24, %25, %26, %27, %28, %29, %30, %31, %32, %33, %34, %35}, "
    "{%36, %37, %38, %39}, %40, p, 1, 1, 1;\n}\n"
    : "+f"(d[0]), "+f"(d[1]), "+f"(d[2]), "+f"(d[3]), "+f"(d[4]), "+f"(d[5]), "+f"(d[6]), "+f"(d[7]), "+f"(d[8]), "+f"(d[9]), "+f"(d[10]), "+f"(d[11]), "+f"(d[12]), "+f"(d[13]), "+f"(d[14]), "+f"(d[15]), "+f"(d[16]), "+f"(d[17]), "+f"(d[18]), "+f"(d[19]), "+f"(d[20]), "+f"(d[21]), "+f"(d[22]), "+f"(d[23]), "+f"(d[24]), "+f"(d[25]), "+f"(d[26]), "+f"(d[27]), "+f"(d[28]), "+f"(d[29]), "+f"(d[30]), "+f"(d[31]), "+f"(d[32]), "+f"(d[33]), "+f"(d[34]), "+f"(d[35])
    : "r"(a0), "r"(a1), "r"(a2), "r"(a3), "l"(desc), "r"(scale_d));
}

__device__ __forceinline__ void wgmma_rs_n128(float (&d)[64], uint32_t a0, uint32_t a1, uint32_t a2, uint32_t a3, uint64_t desc, int scale_d) {
  asm volatile("{\n.reg .pred p;\nsetp.ne.b32 p, %69, 0;\n"
    "wgmma.mma_async.sync.aligned.m64n128k16.f32.bf16.bf16 "
    "{%0, %1, %2, %3, %4, %5, %6, %7, %8, %9, %10, %11, %12, %13, %14, %15, %16, %17, %18, %19, %20, %21, %22, %23, %24, %25, %26, %27, %28, %29, %30, %31, %32, %33, %34, %35, %36, %37, %38, %39, %40, %41, %42, %43, %44, %45, %46, %47, %48, %49, %50, %51, %52, %53, %54, %55, %56, %57, %58, %59, %60, %61, %62, %63}, "
    "{%64, %65, %66, %67}, %68, p, 1, 1, 1;\n}\n"
    : "+f"(d[0]), "+f"(d[1]), "+f"(d[2]), "+f"(d[3]), "+f"(d[4]), "+f"(d[5]), "+f"(d[6]), "+f"(d[7]), "+f"(d[8]), "+f"(d[9]), "+f"(d[10]), "+f"(d[11]), "+f"(d[12]), "+f"(d[13]), "+f"(d[14]), "+f"(d[15]), "+f"(d[16]), "+f"(d[17]), "+f"(d[18]), "+f"(d[19]), "+f"(d[20]), "+f"(d[21]), "+f"(d[22]), "+f"(d[23]), "+f"(d[24]), "+f"(d[25]), "+f"(d[26]), "+f"(d[27]), "+f"(d[28]), "+f"(d[29]), "+f"(d[30]), "+f"(d[31]), "+f"(d[32]), "+f"(d[33]), "+f"(d[34]), "+f"(d[35]), "+f"(d[36]), "+f"(d[37]), "+f"(d[38]), "+f"(d[39]), "+f"(d[40]), "+f"(d[41]), "+f"(d[42]), "+f"(d[43]), "+f"(d[44]), "+f"(d[45]), "+f"(d[46]), "+f"(d[47]), "+f"(d[48]), "+f"(d[49]), "+f"(d[50]), "+f"(d[51]), "+f"(d[52]), "+f"(d[53]), "+f"(d[54]), "+f"(d[55]), "+f"(d[56]), "+f"(d[57]), "+f"(d[58]), "+f"(d[59]), "+f"(d[60]), "+f"(d[61]), "+f"(d[62]), "+f"(d[63])
    : "r"(a0), "r"(a1), "r"(a2), "r"(a3), "l"(desc), "r"(scale_d));
}

__device__ __forceinline__ void wgmma_rs_n144(float (&d)[72], uint32_t a0, uint32_t a1, uint32_t a2, uint32_t a3, uint64_t desc, int scale_d) {
  asm volatile("{\n.reg .pred p;\nsetp.ne.b32 p, %77, 0;\n"
    "wgmma.mma_async.sync.aligned.m64n144k16.f32.bf16.bf16 "
    "{%0, %1, %2, %3, %4, %5, %6, %7, %8, %9, %10, %11, %12, %13, %14, %15, %16, %17, %18, %19, %20, %21, %22, %23, %24, %25, %26, %27, %28, %29, %30, %31, %32, %33, %34, %35, %36, %37, %38, %39, %40, %41, %42, %43, %44, %45, %46, %47, %48, %49, %50, %51, %52, %53, %54, %55, %56, %57, %58, %59, %60, %61, %62, %63, %64, %65, %66, %67, %68, %69, %70, %71}, "
    "{%72, %73, %74, %75}, %76, p, 1, 1, 1;\n}\n"
    : "+f"(d[0]), "+f"(d[1]), "+f"(d[2]), "+f"(d[3]), "+f"(d[4]), "+f"(d[5]), "+f"(d[6]), "+f"(d[7]), "+f"(d[8]), "+f"(d[9]), "+f"(d[10]), "+f"(d[11]), "+f"(d[12]), "+f"(d[13]), "+f"(d[14]), "+f"(d[15]), "+f"(d[16]), "+f"(d[17]), "+f"(d[18]), "+f"(d[19]), "+f"(d[20]), "+f"(d[21]), "+f"(d[22]), "+f"(d[23]), "+f"(d[24]), "+f"(d[25]), "+f"(d[26]), "+f"(d[27]), "+f"(d[28]), "+f"(d[29]), "+f"(d[30]), "+f"(d[31]), "+f"(d[32]), "+f"(d[33]), "+f"(d[34]), "+f"(d[35]), "+f"(d[36]), "+f"(d[37]), "+f"(d[38]), "+f"(d[39]), "+f"(d[40]), "+f"(d[41]), "+f"(d[42]), "+f"(d[43]), "+f"(d[44]), "+f"(d[45]), "+f"(d[46]), "+f"(d[47]), "+f"(d[48]), "+f"(d[49]), "+f"(d[50]), "+f"(d[51]), "+f"(d[52]), "+f"(d[53]), "+f"(d[54]), "+f"(d[55]), "+f"(d[56]), "+f"(d[57]), "+f"(d[58]), "+f"(d[59]), "+f"(d[60]), "+f"(d[61]), "+f"(d[62]), "+f"(d[63]), "+f"(d[64]), "+f"(d[65]), "+f"(d[66]), "+f"(d[67]), "+f"(d[68]), "+f"(d[69]), "+f"(d[70]), "+f"(d[71])
    : "r"(a0), "r"(a1), "r"(a2), "r"(a3), "l"(desc), "r"(scale_d));
}

template <int N> struct WG;
template <> struct WG<64>  { static __device__ __forceinline__ void f(float (&d)[32], const uint32_t* a, uint64_t ds, int s) { wgmma_rs_n64(d, a[0], a[1], a[2], a[3], ds, s); } };
template <> struct WG<72>  { static __device__ __forceinline__ void f(float (&d)[36], const uint32_t* a, uint64_t ds, int s) { wgmma_rs_n72(d, a[0], a[1], a[2], a[3], ds, s); } };
template <> struct WG<128> { static __device__ __forceinline__ void f(float (&d)[64], const uint32_t* a, uint64_t ds, int s) { wgmma_rs_n128(d, a[0], a[1], a[2], a[3], ds, s); } };
template <> struct WG<144> { static __device__ __forceinline__ void f(float (&d)[72], const uint32_t* a, uint64_t ds, int s) { wgmma_rs_n144(d, a[0], a[1], a[2], a[3], ds, s); } };

constexpr uint64_t DESC_SW128 = ((uint64_t)(8192 >> 4) << 16) | ((uint64_t)(1024 >> 4) << 32) | (1ull << 62);
constexpr uint64_t DESC_KV = ((uint64_t)(128 >> 4) << 16) | ((uint64_t)(768 >> 4) << 32);
constexpr uint64_t DESC_Q = ((uint64_t)(128 >> 4) << 16) | ((uint64_t)(1536 >> 4) << 32);

template <int V> struct IntC { static constexpr int value = V; };
enum { PS_KV, PS_Q, PS_WO, PS_FF };
template <int PS> __host__ __device__ constexpr int pass_slot(int i) {
  return PS == PS_KV ? (i < 3 ? 9 + i : i - 3) : PS == PS_WO ? 6 + i : i;
}

__device__ __forceinline__ void load_frag(uint32_t (&a)[144], int i, const uint8_t* sb, uint32_t uo, uint32_t t) {
  if (i < 32) ld16(&a[4 * i], sb, uo + t * 16, i * 2048);
  else { ld8(&a[4 * i], sb, uo + t * 8, i * 2048); ld8(&a[4 * i + 2], sb, uo + t * 8, i * 2048 + 1024); }
}
__device__ __forceinline__ void store_own(const uint32_t (&y)[18], uint8_t* sb, uint32_t uo, int j) {
  const uint32_t t = tid_() + j * 128;
#pragma unroll
  for (int i = 0; i < 4; i++) st16(sb, uo + t * 16, i * 16384, nz(y[4 * i]), y[4 * i + 1], y[4 * i + 2], y[4 * i + 3]);
  st8(sb, uo + t * 8, 65536, nz(y[16]), y[17]);
}
__device__ __forceinline__ void load_own(uint32_t (&y)[18], const uint8_t* sb, uint32_t uo, int j) {
  const uint32_t t = tid_() + j * 128;
#pragma unroll
  for (int i = 0; i < 4; i++) ld16(&y[4 * i], sb, uo + t * 16, i * 16384);
  ld8(&y[16], sb, uo + t * 8, 65536);
}

template <int N, int PS, int KPS, int KSTEP, int CHK, bool SUB, bool HREL = false>
__device__ __forceinline__ void mma_pass(float (&acc)[N / 2], uint32_t (&a)[144], uint64_t desc, uint32_t par, const Rel& rel, int bar_id,
                                         const uint8_t* sb = nullptr, uint32_t uo = 0, uint32_t nochk = 0, bool noload = false, uint32_t m0 = 0, uint32_t m1 = 0, uint32_t zero = 0) {
  constexpr int NS = 36 / KPS;
  auto check = [&](int s) {
    while (true) {
      uint32_t m = a[4 * s * KPS];
#pragma unroll
      for (int i = s * KPS; i < (s + 1) * KPS; i++) m = min(m, i < 32 ? a[4 * i] : min(a[4 * i], a[4 * i + 2]));
      if (!__any_sync(0xffffffffu, (m | nochk) == 0)) break;
      const uint32_t t = tid_();
#pragma unroll
      for (int i = s * KPS; i < (s + 1) * KPS; i++) load_frag(a, i, sb, uo, t);
    }
  };
#pragma unroll
  for (int s = 0; s < NS; s++) {
    const int sl = pass_slot<PS>(s);
    if (CHK) {
      check(s);
      if (s + CHK < NS && !noload) {
        const uint32_t t = tid_();
#pragma unroll
        for (int i = (s + CHK) * KPS; i < (s + CHK + 1) * KPS; i++) load_frag(a, i, sb, uo, t);
      }
    }
    if (SUB) {
#pragma unroll
      for (int i = s * KPS * 4; i < (s + 1) * KPS * 4; i += 2) { a[i] = bf2_sub(a[i], m0); a[i + 1] = bf2_sub(a[i + 1], m1); }
    }
    mbar_wait(bar_full(sl), sl < 9 ? par : par ^ 1);
    wg_fence();
#pragma unroll
    for (int kk = 0; kk < KPS; kk++)
      WG<N>::f(acc, &a[(s * KPS + kk) * 4], desc + ((slot_addr(sl) + kk * KSTEP) >> 4), (s | kk) ? 1 : 0);
    wg_commit();
    if (s == (PS == PS_KV ? KV_LEAD : NS - 1) && bar_id >= 0) bar_arrive(bar_id, 256);
    if (s > 0) {
      wg_wait<1>();
      if (!(PS == PS_WO && s > 3)) rel(pass_slot<PS>(s - 1));
    }
    if (HREL && s == 3 && nochk) {
#pragma unroll
      for (int i = 0; i < 12; i++) ld16(&a[4 * i], sb, uo, (i >> 2) * TILE + (i & 3) * 2048);
    }
    if (PS == PS_KV && s == 1) {
#pragma unroll
      for (int i = 0; i < 4; i++) asm volatile("xor.b32 %0, %1, %2;" : "=r"(a[i]) : "r"(a[i]), "r"(zero));
    }
  }
  wg_wait<0>();
  if (PS != PS_WO) rel(pass_slot<PS>(NS - 1));
}

template <int NF> __device__ __forceinline__ void load_frags(uint32_t (&a)[144], const uint8_t* sb, uint32_t uo, uint32_t t) {
#pragma unroll
  for (int i = 0; i < NF; i++) load_frag(a, i, sb, uo, t);
}
__device__ __forceinline__ void ln_scalars(float s1, float s2, uint32_t& m, float& rstd) {
  const float mean = s1 * (1.f / DM);
  const float var = fmaxf(s2 * (1.f / DM) - mean * mean, 0.f);
  m = pack_bf16(mean, mean);
  float sd; asm("sqrt.approx.f32 %0, %1;" : "=f"(sd) : "f"(bf_round(bf_round(var) + 1e-5f)));
  rstd = __fdividef(1.f, bf_round(sd));
}
template <int NF> __device__ __forceinline__ void gather_ln(uint32_t (&a)[144], const uint8_t* sb, uint32_t uo, uint32_t sto,
                                          uint32_t& m0, uint32_t& m1, float& r0, float& r1) {
  uint32_t u[32];
  const uint32_t t = tid_(), so = sto + (t >> 5) * 1024 + (t & 28) * 4;
#pragma unroll
  for (int i = 0; i < 8; i++) ld16(&u[4 * i], sb, so, OFF_ST + i * 128);
  load_frags<NF>(a, sb, uo, t);
  while (true) {
    uint32_t m = u[0];
#pragma unroll
    for (int i = 1; i < 8; i++) m = min(m, u[4 * i]);
    if (!__any_sync(0xffffffffu, m == 0)) break;
#pragma unroll
    for (int i = 0; i < 8; i++) ld16(&u[4 * i], sb, so, OFF_ST + i * 128);
  }
  float v[4];
#pragma unroll
  for (int k = 0; k < 4; k++)
    v[k] = ((__uint_as_float(u[k]) + __uint_as_float(u[4 + k])) + (__uint_as_float(u[8 + k]) + __uint_as_float(u[12 + k]))) +
           ((__uint_as_float(u[16 + k]) + __uint_as_float(u[20 + k])) + (__uint_as_float(u[24 + k]) + __uint_as_float(u[28 + k])));
  ln_scalars(v[1], v[0], m0, r0); ln_scalars(v[3], v[2], m1, r1);
}
struct Stats {
  float s[4] = {0, 0, 0, 0}, d0[4] = {0, 0, 0, 0}, d1[4] = {0, 0, 0, 0};
  __device__ __forceinline__ void add16(const uint32_t* f) {
    mma16816(s, f[0], f[1], f[2], f[3], 0x3f803f80u, 0x3f803f80u);
    mma16816(d0, f[0], f[1], f[2], f[3], f[0], f[2]);
    mma16816(d1, f[0], f[1], f[2], f[3], f[1], f[3]);
  }
  __device__ __forceinline__ float sq0(int g) const { return (g & 1) ? d0[1] : d0[0]; }
  __device__ __forceinline__ float sq1(int g) const { return (g & 1) ? d1[3] : d1[2]; }
};
__device__ __forceinline__ void store_stats18(const uint32_t (&y)[18], uint8_t* sb, uint32_t sto) {
  float s[4] = {0, 0, 0, 0}, u[4] = {0, 0, 0, 0};
#pragma unroll
  for (int i = 0; i < 18; i++) {
    const float lo = bf_lo(y[i]), hi = bf_hi(y[i]);
    const int r = (i & 1) * 2;
    s[r] = fmaf(lo, lo, s[r]); u[r] = fmaf(hi, hi, u[r]); s[r + 1] += lo; u[r + 1] += hi;
  }
#pragma unroll
  for (int i = 0; i < 4; i++) s[i] += u[i];
#pragma unroll
  for (int i = 0; i < 4; i++) s[i] += __shfl_xor_sync(0xffffffffu, s[i], 1);
#pragma unroll
  for (int i = 0; i < 4; i++) s[i] += __shfl_xor_sync(0xffffffffu, s[i], 2);
  const uint32_t t = tid_();
  if ((t & 3) == 0) st16(sb, sto + (t >> 5) * 1024 + (t & 28) * 4, OFF_ST, __float_as_uint(s[0]) | 1u, __float_as_uint(s[1]), __float_as_uint(s[2]), __float_as_uint(s[3]));
}
__device__ __forceinline__ void reduce4(const uint32_t* f, uint32_t* y) {
#pragma unroll
  for (int i = 0; i < 4; i++) {
    float lo = bf_lo(f[i]), hi = bf_hi(f[i]);
#pragma unroll
    for (int s = 1; s < 8; s++) { lo += bf_lo(f[4 * s + i]); hi += bf_hi(f[4 * s + i]); }
    y[i] = pack_bf16(lo, hi);
  }
}

#define TS(i) do {} while (0)
#define TSP(i) do {} while (0)
#define TSH(i) do {} while (0)

__host__ __device__ constexpr int role_j(int c) {
  return MAP == 0 ? (MC ? (c >> 1) & 7 : c & 7) : MAP == 1 ? c >> 4 : MAP == 2 ? ((c >> 6) << 2) | ((c >> 1) & 3)
       : MAP == 3 ? ((c >> 5) << 1) | ((c >> 2) & 1) : ((c >> 3) & 3) * 2 + ((c >> 2) & 1);
}
__host__ __device__ constexpr int role_rb(int c) {
  return MAP == 0 ? (MC ? (c >> 4) * 2 + (c & 1) : c >> 3) : MAP == 1 ? c & 15 : MAP == 2 ? ((c >> 3) & 7) * 2 + (c & 1)
       : MAP == 3 ? ((c >> 3) & 3) * 4 + (c & 3) : (c >> 5) * 4 + (c & 3);
}

struct Params {
  const __nv_bfloat16 *x, *wqkv, *wo, *wg, *wu, *wd;
  __nv_bfloat16* out;
  uint8_t* scr;
  uint8_t* times;
  unsigned zero, zero2;
};

__device__ __forceinline__ void tma_prefetch(const CUtensorMap* m, int c0, int c1) {
  asm volatile("cp.async.bulk.prefetch.tensor.2d.L2.global [%0, {%1, %2}];" ::"l"(m), "r"(c0), "r"(c1) : "memory");
}
__device__ __forceinline__ void fill_packed(int sl, uint32_t par, const uint8_t* src, uint32_t rank, uint32_t own) {
  mbar_wait(bar_empty(sl), par);
  mbar_expect_tx(bar_full(sl), PSLOT);
  if (MC) bulk_load_mc(own + slot_addr(sl) + rank * (PSLOT / 2), src + rank * (PSLOT / 2), PSLOT / 2, own + bar_full(sl));
  else bulk_load(slot_addr(sl), src, PSLOT, bar_full(sl));
}

__cluster_dims__(2, 1, 1)
__global__ void __launch_bounds__(384, 1)
fused_kernel(const __grid_constant__ CUtensorMap map_x, const __grid_constant__ CUtensorMap map_wg,
             const __grid_constant__ CUtensorMap map_wu, const __grid_constant__ CUtensorMap map_wd, const Params P) {
  const int wg = __shfl_sync(0xffffffffu, threadIdx.x >> 7, 0);
  const int cta = blockIdx.x, rank = MC ? cta & 1 : 0, j = role_j(cta), rb = role_rb(cta);
  const uint32_t own = win();
  unsigned* const flags = (unsigned*)(P.scr + OFF_FLAGS);
  if (__shfl_sync(0xffffffffu, threadIdx.x >> 5, 0) == 11) {
    if (threadIdx.x == 352) {
#pragma unroll
      for (int i = 0; i < 14; i++) { mbar_init(bar_full(i), 1); mbar_init(bar_empty(i), MC && i < 12 ? 4 : 2); }
      mbar_init(bar_full(14), 1); mbar_init(bar_empty(14), 1);
      asm volatile("fence.mbarrier_init.release.cluster;" ::: "memory");
      if (smem_u32(smem_raw) != own + SB) asm volatile("trap;");
    }
    __syncwarp();
    bar_arrive(0, 384);
    if (MC) asm volatile("barrier.cluster.arrive.relaxed.aligned;" ::: "memory");
    if (threadIdx.x == 352) {
#pragma unroll 1
      for (int c = 0; c < 9; c++) {
        mbar_expect_tx(bar_full(c), SLOT);
        tma_3d(own + slot_addr(c), &map_x, c * 64, rb * 64, 0, own + bar_full(c));
      }
    }

  } else {
    const unsigned ep0 = *(volatile unsigned*)&flags[(72 + cta) * 8];
    {
      const bool on = threadIdx.x < 324;
      const int k = rb * 36 + (on ? threadIdx.x / 36 : 0) * 4 + (threadIdx.x & 3), u = (threadIdx.x % 36) >> 2;
      const uint4* s = (const uint4*)(P.wqkv + k * 1728 + j * 72 + u * 8);
      const uint4 vk = __ldg(s + 72), vv = __ldg(s + 144), vq = __ldg(s);
      const int ko = k < 512 ? ((k >> 4) & 7) * 72 + (k >> 7) * 16 + (k & 15) : ((k >> 3) & 7) * 72 + 64 + (k & 7);
      const uint4 vo = __ldg((const uint4*)(P.wo + ko * 576 + (u < 8 ? (u >> 1) * 128 + j * 16 + (u & 1) * 8 : 512 + j * 8)));
      uint8_t* d = P.scr + OFF_WPACK + j * 24 * PSLOT;
      const uint32_t dkv = (k / 48) * PSLOT + u * 768 + (k % 48) * 16, dq = (k / 96) * PSLOT + u * 1536 + (k % 96) * 16;
      if (MC) asm volatile("barrier.cluster.arrive.relaxed.aligned;" ::: "memory");
      if (on) {
        st16(d, dkv, 0, vk.x, vk.y, vk.z, vk.w);
        st16(d, dkv, 9 * 768, vv.x, vv.y, vv.z, vv.w);
        st16(d, dq, 12 * PSLOT, vq.x, vq.y, vq.z, vq.w);
        st16(d, dq, 18 * PSLOT, vo.x, vo.y, vo.z, vo.w);
      }
      if (threadIdx.x == 351) sts32(SM_EPOCH, ep0);
      if (threadIdx.x == 0) TSP(3);
      asm volatile("fence.proxy.async.global;" ::: "memory");
    }
    bar_sync(0, 384);
  }
  __syncwarp();
  if (MC) asm volatile("barrier.cluster.wait.acquire.aligned;" ::: "memory");

  if (wg == 2) {
    asm volatile("setmaxnreg.dec.sync.aligned.u32 24;");
    const int pw = __shfl_sync(0xffffffffu, (threadIdx.x >> 5) & 3, 0), lane = threadIdx.x & 31;
    auto tile_col = [](int t, int j) { return t < 9 ? j * 576 + t * 64 : t == 9 ? 512 : (t - 10) * 128; };
    auto prefetch_tile = [&](int t) {
#pragma unroll 1
      for (int b = rb; b < 18; b += 16) {
        const int h = b & 1, k = b >> 1;
        if (t < 9) tma_prefetch(h ? &map_wu : &map_wg, tile_col(t, j), k * 64);
        else if (t != 9 || !h) tma_prefetch(&map_wd, tile_col(t, j) + h * 64, j * 576 + k * 64);
      }
    };
    if (pw == 0) {
      if (lane == 0) {
        TSP(5);
        flag_signal(&flags[j * 8]);
        TSP(6);
        flag_wait(&flags[j * 8], (lds32(SM_EPOCH) + 1) * 16);
        TSP(7);
        asm volatile("fence.proxy.async.global;" ::: "memory");
        const uint8_t* wp = P.scr + OFF_WPACK + j * 24 * PSLOT;
#pragma unroll 1
        for (int s = 0; s < 3; s++) fill_packed(9 + s, 1, wp + s * PSLOT, rank, own);
#pragma unroll 1
        for (int L = 0; L < 2; L++) {
#pragma unroll 1
          for (int s = 0; s < 21; s++) {
            if (TH && s >= TH) { const int o = s - TH; mbar_wait(bar_full(o < 9 ? o : o - 9), o < 9 || o >= 18); }
            fill_packed(s < 9 ? s : s - 9, s >= 9 && s < 18, wp + (s + 3) * PSLOT, rank, own);
          }
#pragma unroll 1
          for (int t = 0; t < 14; t++) {
            const int p = t - 9;
            const CUtensorMap* ma = p < 0 ? &map_wg : &map_wd;
            const CUtensorMap* mb = p < 0 ? &map_wu : &map_wd;
            const int ca = tile_col(t, j), cb = p < 0 ? ca : ca + 64, r0 = p < 0 ? 0 : j * 576;
            if (L * 14 + t + PF_AHEAD < 28) prefetch_tile((t + PF_AHEAD) % 14);
#pragma unroll 1
            for (int k = 0; k < 9; k++) {
              if (TH && t == 0) mbar_wait(bar_full(k >= TH ? k - TH : k + 12 - TH), 1);
              mbar_wait(bar_empty(k), t & 1);
              mbar_expect_tx(bar_full(k), p == 0 ? 8192 : SLOT);
              const int r = r0 + (p < 0 || k == 8 ? k : k < 3 ? k + 5 : k - 3) * 64;
              if (MC) {
                if (p != 0) tma_2d_mc(own + slot_addr(k) + rank * 8192, rank ? mb : ma, rank ? cb : ca, r, own + bar_full(k));
                else if ((k & 1) == rank) tma_2d_mc(own + slot_addr(k), ma, ca, r, own + bar_full(k));
              } else {
                tma_2d(slot_addr(k), ma, ca, r, bar_full(k));
                if (p != 0) tma_2d(slot_addr(k) + 8192, mb, cb, r, bar_full(k));
              }
            }
            if (p == 1 && L == 0) {
              l2_prefetch(wp + rb * (24 * PSLOT / 16), 24 * PSLOT / 16);
#pragma unroll 1
              for (int s = 0; s < 3; s++) fill_packed(9 + s, 1, wp + s * PSLOT, rank, own);
            }
          }
        }
        flags[(72 + cta) * 8] = lds32(SM_EPOCH) + 1;
      }
    } else if (pw < 3) {
      const int hw = pw - 1;
      const uint32_t ep = __shfl_sync(0xffffffffu, lds32(SM_EPOCH), 0);
      uint8_t* const sb = P.scr + (rb * 2 + hw) * STRM;
      const uint32_t xs = slot_addr(12) + hw * SLOT, fb = bar_full(12) + hw * 8;
      uint32_t hph = 0;
#pragma unroll 1
      for (int L = 0; L < 2; L++) {
        const uint32_t tag = ep * 2 + L + 1;
        if (L == 0) flag_wait(flags + (8 + rb) * 8, (ep + 1) * 8);
        bar_sync(NB_FREE + hw, 160);
        if (rb > 0) hint_wait(sb + OFF_HINT + 512 + j * 128, tag);
        uint32_t bad;
        do {
          if (rb > 0) {
            if (lane == 0) {
              mbar_expect_tx(bar_full(14) + hw * 128, 3072);
              bulk_load(own + ytail(hw * 2), sb + OFF_HALO + (L * 8 + j) * 3072, 1536, own + bar_full(14) + hw * 128);
              bulk_load(own + ytail(hw * 2 + 1), sb + OFF_HALO + (L * 8 + j) * 3072 + 1536, 1536, own + bar_full(14) + hw * 128);
            }
            mbar_wait(bar_full(14) + hw * 128, hph);
            hph ^= 1;
          }
          bad = 0;
#pragma unroll 1
          for (int c = 0; c < 3; c++) {
            uint32_t u[4] = {tag, 0, 0, 0}, v[4] = {tag, 0, 0, 0};
            if (rb > 0) { lds128(u, ytail(hw * 2) + c * 512 + lane * 16); lds128(v, ytail(hw * 2 + 1) + c * 512 + lane * 16); }
            bad |= (u[0] ^ tag) | (v[0] ^ tag);
#pragma unroll
            for (int i = 0; i < 3; i++) { sts32(xs + KSTG + (c * 3 + i) * 128 + lane * 4, u[i + 1]); sts32(xs + (c * 3 + i) * 128 + lane * 4, v[i + 1]); }
          }
        } while (__any_sync(0xffffffffu, bad != 0));
        bar_arrive(NB_HALO + hw, 160);
#pragma unroll 1
        for (int p = 0; p < 4; p++) {
          if (L == 0 && p == 3) flag_wait(flags + (40 + rb) * 8, (ep + 1) * 8);
          bar_sync(NB_FREE + hw, 160);
          TSH(L * 12 + p * 3);
          hint_wait(sb + OFF_HINT + (lane & 3) * 128, (ep * 15 + L * 8 + p + 3) * 8);
          TSH(L * 12 + p * 3 + 1);
          if (lane == 0) {
            mbar_expect_tx(fb, p ? PBUF : PBUF / 2);
            bulk_load(own + xs, sb + OFF_P + j * PSRC + (p ? (p == 2) * PBUF : 2 * PBUF), p ? PBUF : PBUF / 2, own + fb);
          }
          TSH(L * 12 + p * 3 + 2);
        }
      }
    } else {
      timed_wait(bar_full(9));
      if (lane == 0) {
#pragma unroll 1
        for (int t = 0; t < PF_AHEAD; t++) prefetch_tile(t);
      }
#pragma unroll 1
      for (int r = 0; r < 2; r++) {
#pragma unroll 1
        for (int t = r; t < 2 + 2 * r; t++) {
          const uint32_t so = rb * 2 * STRM + lane * 16;
#pragma unroll 1
          for (int i = 0; i < 18; i++) {
            st16(P.scr, so + t * TILE + j * 9216 + i * 512, 0, 0, 0, 0, 0);
            st16(P.scr, so + t * TILE + j * 9216 + i * 512, STRM, 0, 0, 0, 0);
            if (r || (i & 1)) __nanosleep(0);
          }
          if (t != 1) {
            st16(P.scr, so + (t ? t - 1 : 0) * 4096 + j * 512, OFF_ST, 0, 0, 0, 0);
            st16(P.scr, so + (t ? t - 1 : 0) * 4096 + j * 512, OFF_ST + STRM, 0, 0, 0, 0);
          }
        }
        __syncwarp();
        if (lane == 0) flag_signal(flags + (8 + r * 32 + rb) * 8);
        timed_wait(bar_empty(13) - r * 8);
      }
      if (MC) asm volatile("barrier.cluster.arrive.relaxed.aligned;\nbarrier.cluster.wait.aligned;" ::: "memory");
    }
  } else {
    asm volatile("setmaxnreg.inc.sync.aligned.u32 240;");
    const int w = __shfl_sync(0xffffffffu, (threadIdx.x >> 5) & 3, 0);
    const bool leader = (threadIdx.x & 127) == 0;
    const Rel rel{MC ? (threadIdx.x & 95) == 0 : leader, MC ? cta_window(w & 1) : 0};
    uint8_t* const sb = P.scr + (rb * 2 + wg) * STRM;
    uint8_t* const hint = sb + OFF_HINT + w * 128;
    auto hint_target = [](int e) { return (lds32(SM_EPOCH) * 15 + e + 1) * 8; };
    uint32_t a[144];
    TS(0);
#pragma unroll 1
    for (int L = 0; L < 2; L++) {
      uint32_t m0, m1; float r0, r1;
      if (L == 0) {
        Stats t;
        const int lane = tid_() & 31, g = lane >> 2;
        const int row = w * 16 + (lane & 15);
        const uint32_t ra = SB + wg * 8192 + row * 128;
#pragma unroll
        for (int c = 0; c < 9; c++) {
          mbar_wait(bar_full(c), 0);
          if (c == 0) TS(60); if (c == 4) TS(61); if (c == 8) TS(62);
#pragma unroll
          for (int kk = 0; kk < 4; kk++) {
            const int i = c * 16 + kk * 4;
            ldsm4(&a[i], ra + (((kk * 2 + (lane >> 4)) ^ (row & 7)) << 4) + c * SLOT);
          }
#pragma unroll
          for (int kk = 0; kk < 4; kk++) t.add16(&a[c * 16 + kk * 4]);
          if (c % 3 == 2) {
            bar_sync(NB_WG + wg, 128);
            rel(c - 2); rel(c - 1); rel(c);
          }
        }
        const int dl = (lane & ~3) | (g >> 1);
        ln_scalars(t.s[0], __shfl_sync(0xffffffffu, t.sq0(g), dl), m0, r0);
        ln_scalars(t.s[2], __shfl_sync(0xffffffffu, t.sq1(g), dl), m1, r1);
      } else {
#pragma unroll
        for (int i = 12 * D_KV; i < 144; i++) a[i] = 0;
        hint_wait(hint, hint_target(7));
        gather_ln<3 * D_KV>(a, sb, OFF_X2, 8192, m0, m1, r0, r1);
      }
      TS(1 + L * 20);
      uint32_t kf[18], qf[18];
      {
        float acc[72];
        if (wg == 1) bar_sync(NB_ORD1, 256);
        mma_pass<144, PS_KV, 3, 256, D_KV, true>(acc, a, DESC_KV, 1, rel, wg == 0 ? NB_ORD1 : -1, sb, OFF_X2, L ^ 1, L == 0, m0, m1, P.zero);
        uint32_t vf[18];
#pragma unroll
        for (int c = 0; c < 9; c++) {
          kf[2 * c] = pack_bf16(acc[4 * c] * r0, acc[4 * c + 1] * r0);
          kf[2 * c + 1] = pack_bf16(acc[4 * c + 2] * r1, acc[4 * c + 3] * r1);
          vf[c] = pack_bf16(acc[36 + 4 * c] * r0, acc[36 + 4 * c + 1] * r0);
          vf[9 + c] = pack_bf16(acc[36 + 4 * c + 2] * r1, acc[36 + 4 * c + 3] * r1);
        }
        TS(2 + L * 20);
        const uint32_t l16 = (tid_() & 31) * 16, xs = slot_addr(12) + wg * SLOT + w * 1152;
#pragma unroll
        for (int i = 0; i < 4; i++) stsm4(xs + w * 1152 + 1152 + i * 512 + l16, vf[4 * i], vf[4 * i + 1], vf[4 * i + 2], vf[4 * i + 3]);
        sts32(xs + w * 1152 + 1152 + 2048 + l16 / 4, vf[16]); sts32(xs + w * 1152 + 1152 + 2176 + l16 / 4, vf[17]);
        if (w < 3) {
          stsm4(xs + KSTG + 1152 + l16, kf[1], kf[3], kf[5], kf[7]);
          stsm4(xs + KSTG + 1152 + 512 + l16, kf[9], kf[11], kf[13], kf[15]);
          sts32(xs + KSTG + 1152 + 1024 + l16 / 4, kf[17]);
        } else if (rb < 15) {
          const uint32_t tag = lds32(SM_EPOCH) * 2 + L + 1;
          const uint32_t ho = l16 + (L * 8 + j) * 3072;
#pragma unroll
          for (int c = 0; c < 3; c++) {
            st16(sb, ho, 2 * STRM + OFF_HALO + c * 512, tag, kf[6 * c + 1], kf[6 * c + 3], kf[6 * c + 5]);
            st16(sb, ho, 2 * STRM + OFF_HALO + 1536 + c * 512, tag, vf[9 + 3 * c], vf[10 + 3 * c], vf[11 + 3 * c]);
          }
          hint_post(sb + 2 * STRM + OFF_HINT + 512 + j * 128);
        }
      }
      bar_arrive(NB_FREE + wg, 160);
      {
        float acc[36];
#pragma unroll
        for (int i = 0; i < 4; i++) asm volatile("xor.b32 %0, %1, %2;" : "=r"(a[i]) : "r"(a[i]), "r"(P.zero2));
        if (wg == 1) bar_sync(NB_ORD1, 256);
        mma_pass<72, PS_Q, 6, 256, 0, false>(acc, a, DESC_Q, 0, rel, -1);
#pragma unroll
        for (int c = 0; c < 9; c++) {
          qf[2 * c] = pack_bf16(acc[4 * c] * r0, acc[4 * c + 1] * r0);
          qf[2 * c + 1] = pack_bf16(acc[4 * c + 2] * r1, acc[4 * c + 3] * r1);
        }
      }
      TS(3 + L * 20);
      uint32_t xr[18];
      {
        uint32_t kh[12], vt[28];
        const int tid = tid_(), g = (tid >> 2) & 7, q = tid & 3;
        bar_sync(NB_HALO + wg, 160);
        {
          const uint32_t xs = slot_addr(12) + wg * SLOT + w * 1152 + (tid & 31) * 16;
#pragma unroll
          for (int i = 0; i < 3; i++) ldsm4(&kh[4 * i], xs + KSTG + i * 512);
#pragma unroll
          for (int i = 0; i < 7; i++) ldsm4t(&vt[4 * i], xs + w * 1152 + i * 512);
        }
        TS(14 + L * 20);
        const bool nohalo = (rb == 0 && w == 0);
        const bool le0 = 2 * q <= g, le1 = 2 * q + 1 <= g;
        const uint32_t M = (le0 ? 0xffffu : 0u) | (le1 ? 0xffff0000u : 0u);
        const float sc = 0.23570226039551584f * 1.4426950408889634f;
        float l[16], t[8];
#pragma unroll
        for (int h = 0; h < 4; h++) {
          const uint32_t qa0 = q >= h ? qf[4 * h] : 0u, qa1 = q >= h ? qf[4 * h + 1] : 0u;
          const uint32_t qc0 = q <= h ? qf[4 * h + 4] : 0u, qc1 = q <= h ? qf[4 * h + 5] : 0u;
          float sm[4] = {0, 0, 0, 0}, s0[4] = {0, 0, 0, 0}, s1[4] = {0, 0, 0, 0};
          mma16816(s0, qa0, qa1, qf[4 * h + 2], qf[4 * h + 3], kf[4 * h], kf[4 * h + 2]);
          mma16816(s1, qa0, qa1, qf[4 * h + 2], qf[4 * h + 3], kf[4 * h + 1], kf[4 * h + 3]);
          mma16816(sm, qa0, qa1, qf[4 * h + 2], qf[4 * h + 3], kh[2 * h], kh[2 * h + 1]);
          mma1688(s0, qc0, qc1, kf[4 * h + 4]);
          mma1688(s1, qc0, qc1, kf[4 * h + 5]);
          mma1688(sm, qc0, qc1, kh[2 * h + 2]);
          if (nohalo) sm[0] = sm[1] = -1e9f / 0.23570226039551584f;
          l[4 * h] = le0 ? s0[0] : sm[0]; l[4 * h + 1] = le1 ? s0[1] : sm[1];
          l[4 * h + 2] = le0 ? s1[2] : s0[2]; l[4 * h + 3] = le1 ? s1[3] : s0[3];
        }
#pragma unroll
        for (int i = 0; i < 8; i++) t[i] = fmaxf(l[2 * i], l[2 * i + 1]);
#pragma unroll
        for (int i = 0; i < 8; i++) t[i] = fmaxf(t[i], __shfl_xor_sync(0xffffffffu, t[i], 1));
#pragma unroll
        for (int i = 0; i < 8; i++) t[i] = fmaxf(t[i], __shfl_xor_sync(0xffffffffu, t[i], 2)) * sc;
#pragma unroll
        for (int i = 0; i < 8; i++) { l[2 * i] = ex2(fmaf(l[2 * i], sc, -t[i])); l[2 * i + 1] = ex2(fmaf(l[2 * i + 1], sc, -t[i])); t[i] = l[2 * i] + l[2 * i + 1]; }
#pragma unroll
        for (int i = 0; i < 8; i++) t[i] += __shfl_xor_sync(0xffffffffu, t[i], 1);
#pragma unroll
        for (int i = 0; i < 8; i++) t[i] += __shfl_xor_sync(0xffffffffu, t[i], 2);
        uint32_t pf[16];
#pragma unroll
        for (int i = 0; i < 8; i++) {
          float r; asm("rcp.approx.ftz.f32 %0, %1;" : "=f"(r) : "f"(t[i]));
          const uint32_t p = pack_bf16(l[2 * i] * r, l[2 * i + 1] * r);
          pf[2 * i] = p & ~M; pf[2 * i + 1] = p & M;
        }
#pragma unroll
        for (int c = 0; c < 9; c++) {
          const int h = c == 8 ? 3 : c >> 1;
          float o[4] = {0, 0, 0, 0};
          mma16816(o, pf[4 * h], 0u, pf[4 * h + 1], pf[4 * h + 2], vt[c], vt[9 + c]);
          mma1688(o, 0u, pf[4 * h + 3], vt[18 + c]);
          if (c == 2 || c == 4 || c == 6) {
            float e[4] = {0, 0, 0, 0};
            mma16816(e, pf[4 * h - 4], 0u, pf[4 * h - 3], pf[4 * h - 2], vt[c], vt[9 + c]);
            mma1688(e, 0u, pf[4 * h - 1], vt[18 + c]);
            if (q < h) { o[0] = e[0]; o[1] = e[1]; o[2] = e[2]; o[3] = e[3]; }
          }
          qf[2 * c] = pack_bf16(o[0], o[1]); qf[2 * c + 1] = pack_bf16(o[2], o[3]);
        }
        store_own(qf, sb, OFF_O, j);
        hint_post(hint);
        bar_arrive(NB_ORD1 - wg, 256);
        if (L == 0) {
          const uint32_t xo = (rb * 128 + wg + (w * 16 + g) * 2) * (2 * DM) + q * 4 + j * 16;
#pragma unroll
          for (int c = 0; c < 9; c++) {
            const int o = c < 8 ? (c >> 1) * 256 + (c & 1) * 16 : 1024;
            xr[2 * c] = ldg4(P.x, c < 8 ? xo + j * 16 : xo, o); xr[2 * c + 1] = ldg4(P.x, c < 8 ? xo + j * 16 : xo, o + 32 * DM);
          }
        } else {
          load_own(xr, sb, OFF_X2, j);
        }
      }
      TS(4 + L * 20);
      {
        hint_wait(hint, hint_target(L * 8));
        TS(5 + L * 20);
        load_frags<6 * D_WO>(a, sb, OFF_O, tid_());
        float acc[36];
        if (wg == 0) bar_sync(NB_ORD0, 256);
        mma_pass<72, PS_WO, 6, 256, D_WO, false>(acc, a, DESC_Q, 0, rel, -1, sb, OFF_O);
        TS(6 + L * 20);
#pragma unroll
        for (int c = 0; c < 9; c++) {
          xr[2 * c] = bf2_add(xr[2 * c], pack_bf16(acc[4 * c], acc[4 * c + 1]));
          xr[2 * c + 1] = bf2_add(xr[2 * c + 1], pack_bf16(acc[4 * c + 2], acc[4 * c + 3]));
        }
        store_own(xr, sb, L * 3 * TILE, j);
        store_stats18(xr, sb, L * 4096 + j * 128);
        hint_post(hint);
      }
      TS(16 + L * 20);
      hint_wait(hint, hint_target(L * 8 + 1));
      TS(15 + L * 20);
      gather_ln<4 * D_T0>(a, sb, L * 3 * TILE, L * 4096, m0, m1, r0, r1);
      TS(7 + L * 20);
      const uint32_t hb = (L ^ 1) * TILE + j * 9216;
      {
        float ka0, kb0, kc0, ka1, kb1, kc1;
        float acc[64];
        uint32_t hf[16];
        auto geglu = [&](auto chains, uint32_t hsm) {
          constexpr int CH = decltype(chains)::value;
          float r[32];
#pragma unroll
          for (int e = 0; e < 32; e++) {
            float x = acc[e];
            if (e >= CH) x = __uint_as_float(__float_as_uint(x) ^ (__float_as_uint(r[e - CH]) & P.zero));
            if (CH != 2 && e < 20) {
              const uint32_t ad = (e < 8 ? slot_addr(12) + e * 2048 + wg * 8192 : slot_addr(7 + (e >> 2)) + (e & 3) * 2048) + hsm;
              lds128(&a[48 + 4 * e], e >= CH ? ad ^ (__float_as_uint(r[e - CH]) & P.zero) : ad);
            }
            const bool hi = e & 2;
            float t = x * fmaf(x * x, hi ? kb1 : kb0, hi ? ka1 : ka0);
            asm("tanh.approx.f32 %0, %0;" : "+f"(t));
            const float u = x * acc[32 + e] * (hi ? kc1 : kc0);
            r[e] = fmaf(u, t, u);
            if (e & 1) hf[e >> 1] = pack_bf16(r[e - 1], r[e]);
          }
        };
        if (wg == 1) bar_sync(NB_ORD1, 256);
        mma_pass<128, PS_FF, 4, 2048, D_T0, true>(acc, a, DESC_SW128, 1, rel, NB_ORD1 - wg, sb, L * 3 * TILE, 0, false, m0, m1);
        TS(8 + L * 20);
        asm volatile("" : "+f"(r0), "+f"(r1));
        ka0 = 0.7978845608028654f * r0; kb0 = 0.035677408136300125f * r0 * r0 * r0; kc0 = 0.5f * r0 * r0;
        ka1 = 0.7978845608028654f * r1; kb1 = 0.035677408136300125f * r1 * r1 * r1; kc1 = 0.5f * r1 * r1;
#pragma unroll 1
        for (int t = 0; t < 8; t++) {
          geglu(IntC<2>(), 0);
          const uint32_t t16 = tid_() * 16;
          if (t < 5) {
            const uint32_t d = (t < 2 ? slot_addr(12) + wg * SLOT + t * 8192 : slot_addr(7) + t * SLOT + wg * 8192) + t16;
#pragma unroll
            for (int i = 0; i < 4; i++)
              sts128(d + i * 2048, hf[4 * i], hf[4 * i + 1], hf[4 * i + 2], hf[4 * i + 3]);
            if (t == 4) asm volatile("fence.proxy.async.shared::cta;" ::: "memory");
          } else {
#pragma unroll
            for (int i = 0; i < 4; i++) st16(sb, hb + (t - 5) * TILE + t16, i * 2048, hf[4 * i], hf[4 * i + 1], hf[4 * i + 2], hf[4 * i + 3]);
          }
          bar_sync(NB_ORD0 + wg, 256);
          mma_pass<128, PS_FF, 4, 2048, 0, false, true>(acc, a, DESC_SW128, t & 1, rel, NB_ORD1 - wg, sb, hb + t16, t == 7);
        }
        TS(9 + L * 20);
        const uint32_t hsm = wg * 8192 + tid_() * 16;
        geglu(IntC<CH_LAST>(), hsm);
#pragma unroll
        for (int i = 0; i < 16; i++) a[128 + i] = hf[i];
      }
      TS(10 + L * 20);
      {
        const uint32_t xs = slot_addr(12) + wg * SLOT;
        {
          bar_sync(NB_ORD0 + wg + ((a[142] | a[143]) & P.zero), 256);
          TS(64 + L * 32);
          rel(9); rel(10); rel(11);
          float acc[32];
          mma_pass<64, PS_FF, 4, 2048, 0, false>(acc, a, DESC_SW128, 0, rel, NB_ORD1 - wg);
          TS(65 + L * 32);
          const uint32_t t8 = tid_() * 8;
#pragma unroll
          for (int i = 0; i < 8; i++) {
            const uint32_t u = pack_bf16(acc[4 * i], acc[4 * i + 1]), v = pack_bf16(acc[4 * i + 2], acc[4 * i + 3]);
            if (i == j) sts64(xs + PBUF + t8 * 2, u, v);
            else st8(sb, ((j - i - 1) & 7) * 1024 + t8, OFF_P + 2 * PBUF + i * PSRC, (u & ~1u) | (L ^ 1), v);
          }
          hint_post(hint);
          if (L == 0 && tid_() == 0) mbar_arrive(bar_empty(13));
          bar_arrive(NB_FREE + wg, 160);
          TS(68 + L * 32);
        }
        uint32_t y[18];
#pragma unroll 1
        for (int p = 1; p < 5; p++) {
          bar_sync(NB_ORD0 + wg, 256);
          TS(64 + L * 32 + p * 5);
          uint32_t in[32];
          const uint32_t t16 = tid_() * 16;
          {
            float acc[64];
            mma_pass<128, PS_FF, 4, 2048, 0, false>(acc, a, DESC_SW128, p & 1, rel, (p == 4 && wg == 1) ? -1 : NB_ORD1 - wg);
            TS(65 + L * 32 + p * 5);
            lds128(&in[28], xs + PBUF + t16);
            mbar_wait(bar_full(12) + wg * 8, (p & 1) ^ 1);
            TS(66 + L * 32 + p * 5);
            {
              const uint32_t flip = p == 1 ? L - 1 : p < 4 ? ~0u : 0u;
              const uint32_t sh = p == 1;
              uint32_t m = 0;
#pragma unroll
              for (int s = 0; s < 7; s++) m |= lds32(xs + ((s * 2048 + t16) >> sh)) ^ flip;
              if (__builtin_expect(__any_sync(0xffffffffu, m & 1), 0)) {
#pragma unroll 1
                for (int s = 0; s < 7; s++) {
                  const uint32_t o = (s * 2048 + t16) >> sh;
                  uint32_t v[4] = {0, 0, 0, 0};
                  do {
                    if (sh) ld8(v, sb, j * PSRC + o, OFF_P + 2 * PBUF);
                    else ld16(v, sb, j * PSRC + (p & 1) * PBUF + o, OFF_P);
                  } while (__any_sync(0xffffffffu, (v[0] ^ flip) & 1));
                  sts64(xs + o, v[0], v[1]);
                  if (!sh) sts64(xs + o + 8, v[2], v[3]);
                }
                asm volatile("fence.proxy.async.shared::cta;" ::: "memory");
              }
            }
#pragma unroll
            for (int i = 0; i < 8; i++) {
              const uint32_t u0 = pack_bf16(acc[8 * i], acc[8 * i + 1]), u1 = pack_bf16(acc[8 * i + 2], acc[8 * i + 3]);
              const uint32_t u2 = pack_bf16(acc[8 * i + 4], acc[8 * i + 5]), u3 = pack_bf16(acc[8 * i + 6], acc[8 * i + 7]);
              if (i == j) sts128(xs + PBUF + t16, u0, u1, u2, u3);
              else st16(sb, ((j - i - 1) & 7) * 2048 + ((p & 1) ^ 1) * PBUF + t16, OFF_P + i * PSRC, (u0 & ~1u) | (p < 3), u1, u2, u3);
            }
          }
          hint_post(hint);
          TS(68 + L * 32 + p * 5);
          if (p == 1) {
#pragma unroll
            for (int s = 0; s < 7; s++) {
              lds64(in[4 * s], in[4 * s + 1], xs + s * 1024 + t16 / 2);
              in[4 * s + 2] = in[4 * s + 3] = 0;
            }
          } else {
#pragma unroll
            for (int s = 0; s < 7; s++) lds128(&in[4 * s], xs + s * 2048 + t16);
          }
          if (p < 4) bar_arrive(NB_FREE + wg, 160);
          reduce4(in, y + 8);
          if (p == 1) sts64(ytail(wg * 2 + (t16 >> 10)) + 2048 + (t16 & 1023) / 2, y[8], y[9]);
          else if (p < 4) sts128(ytail(wg * 2 + p - 2) + t16, y[8], y[9], y[10], y[11]);
          TS(67 + L * 32 + p * 5);
        }
        TS(11 + L * 20);
        const uint32_t t = tid_();
#pragma unroll
        for (int i = 0; i < 2; i++) lds128(&y[4 * i], ytail(wg * 2 + i) + t * 16);
        lds128(&a[28], xs + PBUF + t * 16);
        lds64(y[16], y[17], ytail(wg * 2 + (t >> 6)) + 2048 + (t & 63) * 8);
        load_own(xr, sb, L * 3 * TILE, j);
        hint_wait(hint, hint_target(L * 8 + 6));
        TS(17 + L * 20);
        {
          uint32_t m;
          do {
            m = 0;
#pragma unroll
            for (int s = 0; s < 7; s++) { ld16(&a[4 * s], sb, j * PSRC + t * 16, OFF_P + PBUF + s * 2048); m |= a[4 * s]; }
          } while (__any_sync(0xffffffffu, m & 1));
          TS(12 + L * 20);
          reduce4(a, y + 12);
        }
#pragma unroll
        for (int i = 0; i < 18; i++) xr[i] = bf2_add(xr[i], y[i]);
        TS(18 + L * 20);
        if (L == 0) {
          store_own(xr, sb, OFF_X2, j);
          store_stats18(xr, sb, 8192 + j * 128);
          hint_post(hint);
        } else {
          const uint32_t xo = (rb * 128 + wg + (w * 16 + ((t >> 2) & 7)) * 2) * (2 * DM) + (t & 3) * 4 + j * 16;
#pragma unroll
          for (int c = 0; c < 9; c++) {
            const int o = c < 8 ? (c >> 1) * 256 + (c & 1) * 16 : 1024;
            stg4(P.out, c < 8 ? xo + j * 16 : xo, o, xr[2 * c]); stg4(P.out, c < 8 ? xo + j * 16 : xo, o + 32 * DM, xr[2 * c + 1]);
          }
        }
      }
      TS(13 + L * 20);
    }
    bar_sync(NB_WG + wg, 128);
    if (tid_() == 0) mbar_arrive(bar_empty(12));
  }
}

typedef CUresult (*EncodeFn)(CUtensorMap*, CUtensorMapDataType, cuuint32_t, void*, const cuuint64_t*, const cuuint64_t*, const cuuint32_t*,
                             const cuuint32_t*, CUtensorMapInterleave, CUtensorMapSwizzle, CUtensorMapL2promotion, CUtensorMapFloatOOBfill);

void encode(EncodeFn fn, CUtensorMap* m, const void* p, int rank, const cuuint64_t* dims, const cuuint64_t* str, const cuuint32_t* box) {
  const cuuint32_t es[3] = {1, 1, 1};
  fn(m, CU_TENSOR_MAP_DATA_TYPE_BFLOAT16, rank, const_cast<void*>(p), dims, str, box, es, CU_TENSOR_MAP_INTERLEAVE_NONE,
     CU_TENSOR_MAP_SWIZZLE_128B, CU_TENSOR_MAP_L2_PROMOTION_L2_256B, CU_TENSOR_MAP_FLOAT_OOB_FILL_NONE);
}

}

extern "C" void kernel_launch(void* const* d_in, const int* in_sizes, int n_in, void* d_out, int out_size) {
  (void)in_sizes; (void)n_in; (void)out_size;
  Params P;
  P.x = (const __nv_bfloat16*)d_in[0]; P.wqkv = (const __nv_bfloat16*)d_in[1]; P.wo = (const __nv_bfloat16*)d_in[2];
  P.wg = (const __nv_bfloat16*)d_in[4]; P.wu = (const __nv_bfloat16*)d_in[5]; P.wd = (const __nv_bfloat16*)d_in[6];
  P.out = (__nv_bfloat16*)d_out; P.zero = 0; P.zero2 = 0;
  cudaGetSymbolAddress((void**)&P.scr, g_scr);
  void* fnp = nullptr; cudaDriverEntryPointQueryResult qr;
  cudaGetDriverEntryPoint("cuTensorMapEncodeTiled", &fnp, cudaEnableDefault, &qr);
  EncodeFn fn = (EncodeFn)fnp;
  CUtensorMap mx, mg, mu, md;
  { const cuuint64_t dims[3] = {DM, SEQ / 2, 2}, str[2] = {DM * 4, DM * 2}; const cuuint32_t box[3] = {64, 64, 2}; encode(fn, &mx, P.x, 3, dims, str, box); }
  { const cuuint64_t dims[2] = {DFF, DM}, str[1] = {DFF * 2}; const cuuint32_t box[2] = {64, 64}; encode(fn, &mg, P.wg, 2, dims, str, box); encode(fn, &mu, P.wu, 2, dims, str, box); }
  { const cuuint64_t dims[2] = {DM, DFF}, str[1] = {DM * 2}; const cuuint32_t box[2] = {64, 64}; encode(fn, &md, P.wd, 2, dims, str, box); }
  cudaFuncSetAttribute(fused_kernel, cudaFuncAttributeMaxDynamicSharedMemorySize, SMEM_BYTES);
  fused_kernel<<<128, 384, SMEM_BYTES, cudaStreamPerThread>>>(mx, mg, mu, md, P);
}
```

```cpp
#include <cuda_runtime.h>
#include <cuda_bf16.h>
#include <cuda.h>
#include <stdint.h>

#define KV_LEAD 5
#define D_KV 8
#define D_WO 5
#define D_T0 6
#define PF_AHEAD 3
#define CH_LAST 4
#define TH 2
#define MC 1
#define MAP 1
#define XMODE 0
#define XDL 20
#define TIMING 0

namespace {

constexpr int SEQ = 2048, DM = 576, DFF = 4608;
constexpr uint32_t SB = 1024;
constexpr uint32_t SLOT = 16384;
constexpr uint32_t PSLOT = 13824;
constexpr uint32_t BARS = SB + 14 * SLOT;
constexpr int SMEM_BYTES = 14 * SLOT + 256 + 2560;
__host__ __device__ constexpr uint32_t slot_addr(int s) { return SB + s * SLOT; }
__host__ __device__ constexpr uint32_t bar_full(int s) { return BARS + 8 * s; }
__host__ __device__ constexpr uint32_t bar_empty(int s) { return BARS + 128 + 8 * s; }
enum { NB_ORD0 = 1, NB_ORD1 = 2, NB_WG = 3  , NB_HALO = 5  , NB_FREE = 7   };
constexpr uint32_t SM_EPOCH = BARS + 120;
__host__ __device__ constexpr uint32_t ytail(uint32_t k) { return k < 3 ? slot_addr(9) + PSLOT + k * SLOT : BARS + 256; }
constexpr uint32_t KSTG = 9 * 1152;

constexpr uint32_t TILE = 36 * 2048;
constexpr uint32_t OFF_X1 = 0  , OFF_O = TILE, OFF_X2 = 2 * TILE, OFF_ST = 4 * TILE  ;
constexpr uint32_t PBUF = 7 * 2048, PSRC = 2 * PBUF + PBUF / 2;
constexpr uint32_t OFF_P = OFF_ST + 3 * 4096, OFF_HALO = OFF_P + 8 * PSRC  , OFF_HINT = OFF_HALO + 2 * 8 * 3072  ,
                   STRM = OFF_HINT + 12 * 128;
constexpr uint32_t OFF_WPACK = 32 * STRM, OFF_FLAGS = OFF_WPACK + 8 * 24 * PSLOT;
__device__ __align__(1024) uint8_t g_scr[OFF_FLAGS + (8 + 64 + 128) * 32];

__device__ __forceinline__ uint32_t smem_u32(const void* p) { return (uint32_t)__cvta_generic_to_shared(p); }
extern __shared__ __align__(1024) uint8_t smem_raw[];
__device__ __forceinline__ uint32_t win() { return MC ? (blockIdx.x & 1) << 24 : 0; }
#define SA(A, W) ".reg .u32 sa;\nadd.u32 sa, " A ", " W ";\n"
__device__ __forceinline__ void mbar_init(uint32_t bar, uint32_t cnt) { asm volatile("{\n" SA("%0", "%2") "mbarrier.init.shared::cta.b64 [sa], %1;\n}" ::"r"(bar), "r"(cnt), "r"(win())); }
__device__ __forceinline__ void mbar_expect_tx(uint32_t bar, uint32_t bytes) { asm volatile("{\n" SA("%0", "%2") "mbarrier.arrive.expect_tx.shared::cta.b64 _, [sa], %1;\n}" ::"r"(bar), "r"(bytes), "r"(win()) : "memory"); }
__device__ __forceinline__ void mbar_arrive(uint32_t bar) { asm volatile("{\n" SA("%0", "%1") "mbarrier.arrive.shared::cta.b64 _, [sa];\n}" ::"r"(bar), "r"(win()) : "memory"); }
__device__ __forceinline__ uint32_t lds32(uint32_t a) { uint32_t v; asm volatile("{\n" SA("%1", "%2") "ld.shared.u32 %0, [sa];\n}" : "=r"(v) : "r"(a), "r"(win()) : "memory"); return v; }
__device__ __forceinline__ void lds64(uint32_t& x, uint32_t& y, uint32_t a) { asm volatile("{\n" SA("%2", "%3") "ld.shared.v2.u32 {%0,%1}, [sa];\n}" : "=r"(x), "=r"(y) : "r"(a), "r"(win()) : "memory"); }
__device__ __forceinline__ void lds128(uint32_t* v, uint32_t a) {
  asm volatile("{\n" SA("%4", "%5") "ld.shared.v4.u32 {%0,%1,%2,%3}, [sa];\n}" : "=r"(v[0]), "=r"(v[1]), "=r"(v[2]), "=r"(v[3]) : "r"(a), "r"(win()) : "memory");
}
__device__ __forceinline__ void stsm4(uint32_t a, uint32_t x, uint32_t y, uint32_t z, uint32_t w) {
  asm volatile("{\n" SA("%0", "%5") "stmatrix.sync.aligned.m8n8.x4.shared.b16 [sa], {%1,%2,%3,%4};\n}" ::"r"(a), "r"(x), "r"(y), "r"(z), "r"(w), "r"(win()) : "memory");
}
__device__ __forceinline__ void ldsm4(uint32_t* v, uint32_t a) {
  asm volatile("{\n" SA("%4", "%5") "ldmatrix.sync.aligned.m8n8.x4.shared.b16 {%0,%1,%2,%3}, [sa];\n}" : "=r"(v[0]), "=r"(v[1]), "=r"(v[2]), "=r"(v[3]) : "r"(a), "r"(win()) : "memory");
}
__device__ __forceinline__ void ldsm4t(uint32_t* v, uint32_t a) {
  asm volatile("{\n" SA("%4", "%5") "ldmatrix.sync.aligned.m8n8.x4.trans.shared.b16 {%0,%1,%2,%3}, [sa];\n}" : "=r"(v[0]), "=r"(v[1]), "=r"(v[2]), "=r"(v[3]) : "r"(a), "r"(win()) : "memory");
}
__device__ __forceinline__ void sts32(uint32_t a, uint32_t x) { asm volatile("{\n" SA("%0", "%2") "st.shared.u32 [sa], %1;\n}" ::"r"(a), "r"(x), "r"(win()) : "memory"); }
__device__ __forceinline__ void sts64(uint32_t a, uint32_t x, uint32_t y) { asm volatile("{\n" SA("%0", "%3") "st.shared.v2.u32 [sa], {%1,%2};\n}" ::"r"(a), "r"(x), "r"(y), "r"(win()) : "memory"); }
__device__ __forceinline__ void sts128(uint32_t a, uint32_t x, uint32_t y, uint32_t z, uint32_t w) {
  asm volatile("{\n" SA("%0", "%5") "st.shared.v4.u32 [sa], {%1,%2,%3,%4};\n}" ::"r"(a), "r"(x), "r"(y), "r"(z), "r"(w), "r"(win()) : "memory");
}
__device__ __forceinline__ void mbar_wait(uint32_t bar, uint32_t parity) {
  asm volatile("{\n.reg .pred p;\n" SA("%0", "%2") "LAB_WAIT:\nmbarrier.try_wait.parity.shared::cta.b64 p, [sa], %1;\n@!p bra LAB_WAIT;\n}" ::"r"(bar), "r"(parity), "r"(win()) : "memory");
}
__device__ __forceinline__ void timed_wait(uint32_t bar) {
  asm volatile("{\n.reg .pred p;\n.reg .u64 t0, t1;\nmov.u64 t0, %%globaltimer;\nLAB_WD:\n"
               "mbarrier.try_wait.parity.shared::cta.b64 p, [%0], 0, 100000;\n@p bra LAB_OK;\n"
               "mov.u64 t1, %%globaltimer;\nsub.u64 t1, t1, t0;\nsetp.lt.u64 p, t1, 2000000000;\n@p bra LAB_WD;\ntrap;\nLAB_OK:\n}" ::"r"(bar + win()) : "memory");
}
__device__ __forceinline__ void flag_wait(const unsigned* flag, unsigned target) {
  asm volatile("{\n.reg .pred p;\n.reg .u32 v;\nLAB_WAIT:\nld.acquire.gpu.global.u32 v, [%0];\nsub.u32 v, v, %1;\n"
               "setp.lt.s32 p, v, 0;\n@p nanosleep.u32 100;\n@p bra LAB_WAIT;\n}" ::"l"(flag), "r"(target) : "memory");
}
__device__ __forceinline__ void hint_post(uint8_t* p) {
  __syncwarp();
  asm volatile("{\n.reg .pred p;\nelect.sync _|p, 0xffffffff;\n@p red.relaxed.gpu.global.add.u32 [%0], 1;\n}" ::"l"(p) : "memory");
}
__device__ __forceinline__ void hint_wait(const uint8_t* p, uint32_t target) {
  asm volatile("{\n.reg .pred p;\n.reg .u32 v;\nLAB_WAIT:\nld.relaxed.gpu.global.u32 v, [%0];\nsub.u32 v, v, %1;\n"
               "setp.lt.s32 p, v, 0;\nvote.sync.any.pred p, p, 0xffffffff;\n@p bra LAB_WAIT;\n}" ::"l"(p), "r"(target) : "memory");
}
__device__ __forceinline__ void flag_signal(unsigned* flag) { asm volatile("red.release.gpu.global.add.u32 [%0], 1;" ::"l"(flag) : "memory"); }
struct Rel {
  bool on; uint32_t base;
  __device__ __forceinline__ void operator()(int s) const {
    if (on) {
      if (MC) asm volatile("{\n" SA("%0", "%1") "mbarrier.arrive.shared::cluster.b64 _, [sa];\n}" ::"r"(bar_empty(s)), "r"(base) : "memory");
      else mbar_arrive(bar_empty(s));
    }
  }
};
__device__ __forceinline__ uint32_t cta_window(uint32_t rank) { uint32_t a; asm("mapa.shared::cluster.u32 %0, %1, %2;" : "=r"(a) : "r"(0), "r"(rank)); return a; }
__device__ __forceinline__ void tma_2d_mc(uint32_t dst, const CUtensorMap* m, int c0, int c1, uint32_t bar) {
  asm volatile("cp.async.bulk.tensor.2d.shared::cluster.global.mbarrier::complete_tx::bytes.multicast::cluster [%0], [%1, {%3, %4}], [%2], %5;"
               ::"r"(dst), "l"(m), "r"(bar), "r"(c0), "r"(c1), "h"((uint16_t)3) : "memory");
}
__device__ __forceinline__ void bulk_load_mc(uint32_t dst, const void* src, uint32_t bytes, uint32_t bar) {
  asm volatile("cp.async.bulk.shared::cluster.global.mbarrier::complete_tx::bytes.multicast::cluster [%0], [%1], %2, [%3], %4;"
               ::"r"(dst), "l"(src), "r"(bytes), "r"(bar), "h"((uint16_t)3) : "memory");
}
__device__ __forceinline__ void tma_2d(uint32_t dst, const CUtensorMap* m, int c0, int c1, uint32_t bar) {
  asm volatile("cp.async.bulk.tensor.2d.shared::cluster.global.mbarrier::complete_tx::bytes [%0], [%1, {%3, %4}], [%2];"
               ::"r"(dst), "l"(m), "r"(bar), "r"(c0), "r"(c1) : "memory");
}
__device__ __forceinline__ void tma_3d(uint32_t dst, const CUtensorMap* m, int c0, int c1, int c2, uint32_t bar) {
  asm volatile("cp.async.bulk.tensor.3d.shared::cluster.global.mbarrier::complete_tx::bytes [%0], [%1, {%3, %4, %5}], [%2];"
               ::"r"(dst), "l"(m), "r"(bar), "r"(c0), "r"(c1), "r"(c2) : "memory");
}
__device__ __forceinline__ void bulk_load(uint32_t dst, const void* src, uint32_t bytes, uint32_t bar) {
  asm volatile("cp.async.bulk.shared::cluster.global.mbarrier::complete_tx::bytes [%0], [%1], %2, [%3];" ::"r"(dst), "l"(src), "r"(bytes), "r"(bar) : "memory");
}
__device__ __forceinline__ void l2_prefetch(const void* src, uint32_t bytes) { asm volatile("cp.async.bulk.prefetch.L2.global [%0], %1;" ::"l"(src), "r"(bytes) : "memory"); }
__device__ __forceinline__ void wg_fence() { asm volatile("wgmma.fence.sync.aligned;" ::: "memory"); }
__device__ __forceinline__ void wg_commit() { asm volatile("wgmma.commit_group.sync.aligned;" ::: "memory"); }
template <int N> __device__ __forceinline__ void wg_wait() { asm volatile("wgmma.wait_group.sync.aligned %0;" ::"n"(N) : "memory"); }
__device__ __forceinline__ void bar_sync(int id, int n) { asm volatile("bar.sync %0, %1;" ::"r"(id), "r"(n) : "memory"); }
__device__ __forceinline__ void bar_arrive(int id, int n) { asm volatile("bar.arrive %0, %1;" ::"r"(id), "r"(n) : "memory"); }
__device__ __forceinline__ uint32_t pack_bf16(float lo, float hi) { uint32_t r; asm("cvt.rn.bf16x2.f32 %0, %1, %2;" : "=r"(r) : "f"(hi), "f"(lo)); return r; }
__device__ __forceinline__ float bf_lo(uint32_t w) { return __uint_as_float(w << 16); }
__device__ __forceinline__ float bf_hi(uint32_t w) { return __uint_as_float(w & 0xffff0000u); }
__device__ __forceinline__ float bf_round(float x) { return bf_lo(pack_bf16(x, 0.f)); }
__device__ __forceinline__ uint32_t bf2_sub(uint32_t a, uint32_t b) { uint32_t r; asm("sub.rn.bf16x2 %0, %1, %2;" : "=r"(r) : "r"(a), "r"(b)); return r; }
__device__ __forceinline__ uint32_t bf2_add(uint32_t a, uint32_t b) { uint32_t r; asm("add.rn.bf16x2 %0, %1, %2;" : "=r"(r) : "r"(a), "r"(b)); return r; }
#define GADDR(B, O, I) "cvt.u64.u32 ad, " O ";\nadd.u64 ad, ad, " B ";\nadd.u64 ad, ad, " I ";\n"
__device__ __forceinline__ void ld16(uint32_t* v, const uint8_t* ub, uint32_t off, uint32_t imm) {
  asm volatile("{\n.reg .b128 z;\n.reg .b64 x, y, ad;\n" GADDR("%4", "%5", "%6") "ld.relaxed.gpu.global.b128 z, [ad];\n"
               "mov.b128 {x, y}, z;\nmov.b64 {%0,%1}, x;\nmov.b64 {%2,%3}, y;\n}"
               : "=r"(v[0]), "=r"(v[1]), "=r"(v[2]), "=r"(v[3]) : "l"(ub), "r"(off), "l"((uint64_t)imm) : "memory");
}
__device__ __forceinline__ void ld8(uint32_t* v, const uint8_t* ub, uint32_t off, uint32_t imm) {
  asm volatile("{\n.reg .b64 x, ad;\n" GADDR("%2", "%3", "%4") "ld.relaxed.gpu.global.b64 x, [ad];\nmov.b64 {%0,%1}, x;\n}"
               : "=r"(v[0]), "=r"(v[1]) : "l"(ub), "r"(off), "l"((uint64_t)imm) : "memory");
}
__device__ __forceinline__ void st16(uint8_t* ub, uint32_t off, uint32_t imm, uint32_t a, uint32_t b, uint32_t c, uint32_t d) {
  asm volatile("{\n.reg .b128 z;\n.reg .b64 x, y, ad;\n" GADDR("%0", "%1", "%2") "mov.b64 x, {%3,%4};\nmov.b64 y, {%5,%6};\nmov.b128 z, {x, y};\n"
               "st.relaxed.gpu.global.b128 [ad], z;\n}" ::"l"(ub), "r"(off), "l"((uint64_t)imm), "r"(a), "r"(b), "r"(c), "r"(d) : "memory");
}
__device__ __forceinline__ void st8(uint8_t* ub, uint32_t off, uint32_t imm, uint32_t a, uint32_t b) {
  asm volatile("{\n.reg .b64 x, ad;\n" GADDR("%0", "%1", "%2") "mov.b64 x, {%3,%4};\nst.relaxed.gpu.global.b64 [ad], x;\n}"
               ::"l"(ub), "r"(off), "l"((uint64_t)imm), "r"(a), "r"(b) : "memory");
}
__device__ __forceinline__ uint32_t ldg4(const void* ub, uint32_t off, uint32_t imm) {
  uint32_t v; asm volatile("{\n.reg .b64 ad;\n" GADDR("%1", "%2", "%3") "ld.global.nc.u32 %0, [ad];\n}" : "=r"(v) : "l"(ub), "r"(off), "l"((uint64_t)imm)); return v;
}
__device__ __forceinline__ void stg4(void* ub, uint32_t off, uint32_t imm, uint32_t v) {
  asm volatile("{\n.reg .b64 ad;\n" GADDR("%0", "%1", "%2") "st.global.u32 [ad], %3;\n}" ::"l"(ub), "r"(off), "l"((uint64_t)imm), "r"(v) : "memory");
}
__device__ __forceinline__ uint32_t tid_() { uint32_t t; asm volatile("mov.u32 %0, %%tid.x;" : "=r"(t)); return t & 127; }
__device__ __forceinline__ uint32_t nz(uint32_t w) { return max(w, 1u); }
__device__ __forceinline__ void mma16816(float (&c)[4], uint32_t a0, uint32_t a1, uint32_t a2, uint32_t a3, uint32_t b0, uint32_t b1) {
  asm("mma.sync.aligned.m16n8k16.row.col.f32.bf16.bf16.f32 {%0,%1,%2,%3}, {%4,%5,%6,%7}, {%8,%9}, {%0,%1,%2,%3};"
               : "+f"(c[0]), "+f"(c[1]), "+f"(c[2]), "+f"(c[3]) : "r"(a0), "r"(a1), "r"(a2), "r"(a3), "r"(b0), "r"(b1));
}
__device__ __forceinline__ void mma1688(float (&c)[4], uint32_t a0, uint32_t a1, uint32_t b0) {
  asm("mma.sync.aligned.m16n8k8.row.col.f32.bf16.bf16.f32 {%0,%1,%2,%3}, {%4,%5}, {%6}, {%0,%1,%2,%3};"
               : "+f"(c[0]), "+f"(c[1]), "+f"(c[2]), "+f"(c[3]) : "r"(a0), "r"(a1), "r"(b0));
}
__device__ __forceinline__ float ex2(float x) { float r; asm("ex2.approx.ftz.f32 %0, %1;" : "=f"(r) : "f"(x)); return r; }
__device__ __forceinline__ float quad_sum(float v) { v += __shfl_xor_sync(0xffffffffu, v, 1); v += __shfl_xor_sync(0xffffffffu, v, 2); return v; }
__device__ __forceinline__ float quad_max(float v) { v = fmaxf(v, __shfl_xor_sync(0xffffffffu, v, 1)); v = fmaxf(v, __shfl_xor_sync(0xffffffffu, v, 2)); return v; }

__device__ __forceinline__ void wgmma_rs_n64(float (&d)[32], uint32_t a0, uint32_t a1, uint32_t a2, uint32_t a3, uint64_t desc, int scale_d) {
  asm volatile("{\n.reg .pred p;\nsetp.ne.b32 p, %37, 0;\n"
    "wgmma.mma_async.sync.aligned.m64n64k16.f32.bf16.bf16 "
    "{%0, %1, %2, %3, %4, %5, %6, %7, %8, %9, %10, %11, %12, %13, %14, %15, %16, %17, %18, %19, %20, %21, %22, %23, %24, %25, %26, %27, %28, %29, %30, %31}, "
    "{%32, %33, %34, %35}, %36, p, 1, 1, 1;\n}\n"
    : "+f"(d[0]), "+f"(d[1]), "+f"(d[2]), "+f"(d[3]), "+f"(d[4]), "+f"(d[5]), "+f"(d[6]), "+f"(d[7]), "+f"(d[8]), "+f"(d[9]), "+f"(d[10]), "+f"(d[11]), "+f"(d[12]), "+f"(d[13]), "+f"(d[14]), "+f"(d[15]), "+f"(d[16]), "+f"(d[17]), "+f"(d[18]), "+f"(d[19]), "+f"(d[20]), "+f"(d[21]), "+f"(d[22]), "+f"(d[23]), "+f"(d[24]), "+f"(d[25]), "+f"(d[26]), "+f"(d[27]), "+f"(d[28]), "+f"(d[29]), "+f"(d[30]), "+f"(d[31])
    : "r"(a0), "r"(a1), "r"(a2), "r"(a3), "l"(desc), "r"(scale_d));
}

__device__ __forceinline__ void wgmma_rs_n72(float (&d)[36], uint32_t a0, uint32_t a1, uint32_t a2, uint32_t a3, uint64_t desc, int scale_d) {
  asm volatile("{\n.reg .pred p;\nsetp.ne.b32 p, %41, 0;\n"
    "wgmma.mma_async.sync.aligned.m64n72k16.f32.bf16.bf16 "
    "{%0, %1, %2, %3, %4, %5, %6, %7, %8, %9, %10, %11, %12, %13, %14, %15, %16, %17, %18, %19, %20, %21, %22, %23, %24, %25, %26, %27, %28, %29, %30, %31, %32, %33, %34, %35}, "
    "{%36, %37, %38, %39}, %40, p, 1, 1, 1;\n}\n"
    : "+f"(d[0]), "+f"(d[1]), "+f"(d[2]), "+f"(d[3]), "+f"(d[4]), "+f"(d[5]), "+f"(d[6]), "+f"(d[7]), "+f"(d[8]), "+f"(d[9]), "+f"(d[10]), "+f"(d[11]), "+f"(d[12]), "+f"(d[13]), "+f"(d[14]), "+f"(d[15]), "+f"(d[16]), "+f"(d[17]), "+f"(d[18]), "+f"(d[19]), "+f"(d[20]), "+f"(d[21]), "+f"(d[22]), "+f"(d[23]), "+f"(d[24]), "+f"(d[25]), "+f"(d[26]), "+f"(d[27]), "+f"(d[28]), "+f"(d[29]), "+f"(d[30]), "+f"(d[31]), "+f"(d[32]), "+f"(d[33]), "+f"(d[34]), "+f"(d[35])
    : "r"(a0), "r"(a1), "r"(a2), "r"(a3), "l"(desc), "r"(scale_d));
}

__device__ __forceinline__ void wgmma_rs_n128(float (&d)[64], uint32_t a0, uint32_t a1, uint32_t a2, uint32_t a3, uint64_t desc, int scale_d) {
  asm volatile("{\n.reg .pred p;\nsetp.ne.b32 p, %69, 0;\n"
    "wgmma.mma_async.sync.aligned.m64n128k16.f32.bf16.bf16 "
    "{%0, %1, %2, %3, %4, %5, %6, %7, %8, %9, %10, %11, %12, %13, %14, %15, %16, %17, %18, %19, %20, %21, %22, %23, %24, %25, %26, %27, %28, %29, %30, %31, %32, %33, %34, %35, %36, %37, %38, %39, %40, %41, %42, %43, %44, %45, %46, %47, %48, %49, %50, %51, %52, %53, %54, %55, %56, %57, %58, %59, %60, %61, %62, %63}, "
    "{%64, %65, %66, %67}, %68, p, 1, 1, 1;\n}\n"
    : "+f"(d[0]), "+f"(d[1]), "+f"(d[2]), "+f"(d[3]), "+f"(d[4]), "+f"(d[5]), "+f"(d[6]), "+f"(d[7]), "+f"(d[8]), "+f"(d[9]), "+f"(d[10]), "+f"(d[11]), "+f"(d[12]), "+f"(d[13]), "+f"(d[14]), "+f"(d[15]), "+f"(d[16]), "+f"(d[17]), "+f"(d[18]), "+f"(d[19]), "+f"(d[20]), "+f"(d[21]), "+f"(d[22]), "+f"(d[23]), "+f"(d[24]), "+f"(d[25]), "+f"(d[26]), "+f"(d[27]), "+f"(d[28]), "+f"(d[29]), "+f"(d[30]), "+f"(d[31]), "+f"(d[32]), "+f"(d[33]), "+f"(d[34]), "+f"(d[35]), "+f"(d[36]), "+f"(d[37]), "+f"(d[38]), "+f"(d[39]), "+f"(d[40]), "+f"(d[41]), "+f"(d[42]), "+f"(d[43]), "+f"(d[44]), "+f"(d[45]), "+f"(d[46]), "+f"(d[47]), "+f"(d[48]), "+f"(d[49]), "+f"(d[50]), "+f"(d[51]), "+f"(d[52]), "+f"(d[53]), "+f"(d[54]), "+f"(d[55]), "+f"(d[56]), "+f"(d[57]), "+f"(d[58]), "+f"(d[59]), "+f"(d[60]), "+f"(d[61]), "+f"(d[62]), "+f"(d[63])
    : "r"(a0), "r"(a1), "r"(a2), "r"(a3), "l"(desc), "r"(scale_d));
}

__device__ __forceinline__ void wgmma_rs_n144(float (&d)[72], uint32_t a0, uint32_t a1, uint32_t a2, uint32_t a3, uint64_t desc, int scale_d) {
  asm volatile("{\n.reg .pred p;\nsetp.ne.b32 p, %77, 0;\n"
    "wgmma.mma_async.sync.aligned.m64n144k16.f32.bf16.bf16 "
    "{%0, %1, %2, %3, %4, %5, %6, %7, %8, %9, %10, %11, %12, %13, %14, %15, %16, %17, %18, %19, %20, %21, %22, %23, %24, %25, %26, %27, %28, %29, %30, %31, %32, %33, %34, %35, %36, %37, %38, %39, %40, %41, %42, %43, %44, %45, %46, %47, %48, %49, %50, %51, %52, %53, %54, %55, %56, %57, %58, %59, %60, %61, %62, %63, %64, %65, %66, %67, %68, %69, %70, %71}, "
    "{%72, %73, %74, %75}, %76, p, 1, 1, 1;\n}\n"
    : "+f"(d[0]), "+f"(d[1]), "+f"(d[2]), "+f"(d[3]), "+f"(d[4]), "+f"(d[5]), "+f"(d[6]), "+f"(d[7]), "+f"(d[8]), "+f"(d[9]), "+f"(d[10]), "+f"(d[11]), "+f"(d[12]), "+f"(d[13]), "+f"(d[14]), "+f"(d[15]), "+f"(d[16]), "+f"(d[17]), "+f"(d[18]), "+f"(d[19]), "+f"(d[20]), "+f"(d[21]), "+f"(d[22]), "+f"(d[23]), "+f"(d[24]), "+f"(d[25]), "+f"(d[26]), "+f"(d[27]), "+f"(d[28]), "+f"(d[29]), "+f"(d[30]), "+f"(d[31]), "+f"(d[32]), "+f"(d[33]), "+f"(d[34]), "+f"(d[35]), "+f"(d[36]), "+f"(d[37]), "+f"(d[38]), "+f"(d[39]), "+f"(d[40]), "+f"(d[41]), "+f"(d[42]), "+f"(d[43]), "+f"(d[44]), "+f"(d[45]), "+f"(d[46]), "+f"(d[47]), "+f"(d[48]), "+f"(d[49]), "+f"(d[50]), "+f"(d[51]), "+f"(d[52]), "+f"(d[53]), "+f"(d[54]), "+f"(d[55]), "+f"(d[56]), "+f"(d[57]), "+f"(d[58]), "+f"(d[59]), "+f"(d[60]), "+f"(d[61]), "+f"(d[62]), "+f"(d[63]), "+f"(d[64]), "+f"(d[65]), "+f"(d[66]), "+f"(d[67]), "+f"(d[68]), "+f"(d[69]), "+f"(d[70]), "+f"(d[71])
    : "r"(a0), "r"(a1), "r"(a2), "r"(a3), "l"(desc), "r"(scale_d));
}

template <int N> struct WG;
template <> struct WG<64>  { static __device__ __forceinline__ void f(float (&d)[32], const uint32_t* a, uint64_t ds, int s) { wgmma_rs_n64(d, a[0], a[1], a[2], a[3], ds, s); } };
template <> struct WG<72>  { static __device__ __forceinline__ void f(float (&d)[36], const uint32_t* a, uint64_t ds, int s) { wgmma_rs_n72(d, a[0], a[1], a[2], a[3], ds, s); } };
template <> struct WG<128> { static __device__ __forceinline__ void f(float (&d)[64], const uint32_t* a, uint64_t ds, int s) { wgmma_rs_n128(d, a[0], a[1], a[2], a[3], ds, s); } };
template <> struct WG<144> { static __device__ __forceinline__ void f(float (&d)[72], const uint32_t* a, uint64_t ds, int s) { wgmma_rs_n144(d, a[0], a[1], a[2], a[3], ds, s); } };

constexpr uint64_t DESC_SW128 = ((uint64_t)(8192 >> 4) << 16) | ((uint64_t)(1024 >> 4) << 32) | (1ull << 62);
constexpr uint64_t DESC_KV = ((uint64_t)(128 >> 4) << 16) | ((uint64_t)(768 >> 4) << 32);
constexpr uint64_t DESC_Q = ((uint64_t)(128 >> 4) << 16) | ((uint64_t)(1536 >> 4) << 32);

template <int V> struct IntC { static constexpr int value = V; };
enum { PS_KV, PS_Q, PS_WO, PS_FF };
template <int PS> __host__ __device__ constexpr int pass_slot(int i) {
  return PS == PS_KV ? (i < 3 ? 9 + i : i - 3) : PS == PS_WO ? 6 + i : i;
}

__device__ __forceinline__ void load_frag(uint32_t (&a)[144], int i, const uint8_t* sb, uint32_t uo, uint32_t t) {
  if (i < 32) ld16(&a[4 * i], sb, uo + t * 16, i * 2048);
  else { ld8(&a[4 * i], sb, uo + t * 8, i * 2048); ld8(&a[4 * i + 2], sb, uo + t * 8, i * 2048 + 1024); }
}
__device__ __forceinline__ void store_own(const uint32_t (&y)[18], uint8_t* sb, uint32_t uo, int j) {
  const uint32_t t = tid_() + j * 128;
#pragma unroll
  for (int i = 0; i < 4; i++) st16(sb, uo + t * 16, i * 16384, nz(y[4 * i]), y[4 * i + 1], y[4 * i + 2], y[4 * i + 3]);
  st8(sb, uo + t * 8, 65536, nz(y[16]), y[17]);
}
__device__ __forceinline__ void load_own(uint32_t (&y)[18], const uint8_t* sb, uint32_t uo, int j) {
  const uint32_t t = tid_() + j * 128;
#pragma unroll
  for (int i = 0; i < 4; i++) ld16(&y[4 * i], sb, uo + t * 16, i * 16384);
  ld8(&y[16], sb, uo + t * 8, 65536);
}

template <int N, int PS, int KPS, int KSTEP, int CHK, bool SUB, bool HREL = false>
__device__ __forceinline__ void mma_pass(float (&acc)[N / 2], uint32_t (&a)[144], uint64_t desc, uint32_t par, const Rel& rel, int bar_id,
                                         const uint8_t* sb = nullptr, uint32_t uo = 0, uint32_t nochk = 0, bool noload = false, uint32_t m0 = 0, uint32_t m1 = 0, uint32_t zero = 0) {
  constexpr int NS = 36 / KPS;
  auto check = [&](int s) {
    while (true) {
      uint32_t m = a[4 * s * KPS];
#pragma unroll
      for (int i = s * KPS; i < (s + 1) * KPS; i++) m = min(m, i < 32 ? a[4 * i] : min(a[4 * i], a[4 * i + 2]));
      if (!__any_sync(0xffffffffu, (m | nochk) == 0)) break;
      const uint32_t t = tid_();
#pragma unroll
      for (int i = s * KPS; i < (s + 1) * KPS; i++) load_frag(a, i, sb, uo, t);
    }
  };
#pragma unroll
  for (int s = 0; s < NS; s++) {
    const int sl = pass_slot<PS>(s);
    if (CHK) {
      check(s);
      if (s + CHK < NS && !noload) {
        const uint32_t t = tid_();
#pragma unroll
        for (int i = (s + CHK) * KPS; i < (s + CHK + 1) * KPS; i++) load_frag(a, i, sb, uo, t);
      }
    }
    if (SUB) {
#pragma unroll
      for (int i = s * KPS * 4; i < (s + 1) * KPS * 4; i += 2) { a[i] = bf2_sub(a[i], m0); a[i + 1] = bf2_sub(a[i + 1], m1); }
    }
    mbar_wait(bar_full(sl), sl < 9 ? par : par ^ 1);
    wg_fence();
#pragma unroll
    for (int kk = 0; kk < KPS; kk++)
      WG<N>::f(acc, &a[(s * KPS + kk) * 4], desc + ((slot_addr(sl) + kk * KSTEP) >> 4), (s | kk) ? 1 : 0);
    wg_commit();
    if (s == (PS == PS_KV ? KV_LEAD : NS - 1) && bar_id >= 0) bar_arrive(bar_id, 256);
    if (s > 0) {
      wg_wait<1>();
      if (!(PS == PS_WO && s > 3)) rel(pass_slot<PS>(s - 1));
    }
    if (HREL && s == 3 && nochk) {
#pragma unroll
      for (int i = 0; i < 12; i++) ld16(&a[4 * i], sb, uo, (i >> 2) * TILE + (i & 3) * 2048);
    }
    if (PS == PS_KV && s == 1) {
#pragma unroll
      for (int i = 0; i < 4; i++) asm volatile("xor.b32 %0, %1, %2;" : "=r"(a[i]) : "r"(a[i]), "r"(zero));
    }
  }
  wg_wait<0>();
  if (PS != PS_WO) rel(pass_slot<PS>(NS - 1));
}

template <int NF> __device__ __forceinline__ void load_frags(uint32_t (&a)[144], const uint8_t* sb, uint32_t uo, uint32_t t) {
#pragma unroll
  for (int i = 0; i < NF; i++) load_frag(a, i, sb, uo, t);
}
__device__ __forceinline__ void ln_scalars(float s1, float s2, uint32_t& m, float& var, uint32_t zero) {
  const float mean = s1 * (1.f / DM);
  var = s2 * (1.f / DM) - mean * mean;
  m = pack_bf16(mean, mean) ^ (__float_as_uint(var) & zero);
}
__device__ __forceinline__ float ln_rstd(float var, float after, uint32_t zero) {
  var = __uint_as_float(__float_as_uint(var) ^ (__float_as_uint(after) & zero));
  float sd, r;
  asm("sqrt.approx.ftz.f32 %0, %1;" : "=f"(sd) : "f"(bf_round(bf_round(fmaxf(var, 0.f)) + 1e-5f)));
  asm("rcp.approx.ftz.f32 %0, %1;" : "=f"(r) : "f"(bf_round(sd)));
  return r;
}
template <int NF> __device__ __forceinline__ void gather_ln(uint32_t (&a)[144], const uint8_t* sb, uint32_t uo, uint32_t sto,
                                          uint32_t& m0, uint32_t& m1, float& r0, float& r1, uint32_t zero) {
  uint32_t u[32];
  const uint32_t t = tid_(), so = sto + (t >> 5) * 1024 + (t & 28) * 4;
#pragma unroll
  for (int i = 0; i < 8; i++) ld16(&u[4 * i], sb, so, OFF_ST + i * 128);
  load_frags<NF>(a, sb, uo, t);
  while (true) {
    uint32_t m = u[0];
#pragma unroll
    for (int i = 1; i < 8; i++) m = min(m, u[4 * i]);
    if (!__any_sync(0xffffffffu, m == 0)) break;
#pragma unroll
    for (int i = 0; i < 8; i++) ld16(&u[4 * i], sb, so, OFF_ST + i * 128);
  }
  float v[4];
#pragma unroll
  for (int k = 0; k < 4; k++)
    v[k] = ((__uint_as_float(u[k]) + __uint_as_float(u[4 + k])) + (__uint_as_float(u[8 + k]) + __uint_as_float(u[12 + k]))) +
           ((__uint_as_float(u[16 + k]) + __uint_as_float(u[20 + k])) + (__uint_as_float(u[24 + k]) + __uint_as_float(u[28 + k])));
  ln_scalars(v[1], v[0], m0, r0, zero); ln_scalars(v[3], v[2], m1, r1, zero);
}
struct Stats {
  float s[4] = {0, 0, 0, 0}, d0[4] = {0, 0, 0, 0}, d1[4] = {0, 0, 0, 0};
  __device__ __forceinline__ void add16(const uint32_t* f) {
    mma16816(s, f[0], f[1], f[2], f[3], 0x3f803f80u, 0x3f803f80u);
    mma16816(d0, f[0], f[1], f[2], f[3], f[0], f[2]);
    mma16816(d1, f[0], f[1], f[2], f[3], f[1], f[3]);
  }
  __device__ __forceinline__ float sq0(int g) const { return (g & 1) ? d0[1] : d0[0]; }
  __device__ __forceinline__ float sq1(int g) const { return (g & 1) ? d1[3] : d1[2]; }
};
__device__ __forceinline__ void store_stats18(const uint32_t (&y)[18], uint8_t* sb, uint32_t sto) {
  float s[4] = {0, 0, 0, 0}, u[4] = {0, 0, 0, 0};
#pragma unroll
  for (int i = 0; i < 18; i++) {
    const float lo = bf_lo(y[i]), hi = bf_hi(y[i]);
    const int r = (i & 1) * 2;
    s[r] = fmaf(lo, lo, s[r]); u[r] = fmaf(hi, hi, u[r]); s[r + 1] += lo; u[r + 1] += hi;
  }
#pragma unroll
  for (int i = 0; i < 4; i++) s[i] += u[i];
#pragma unroll
  for (int i = 0; i < 4; i++) s[i] += __shfl_xor_sync(0xffffffffu, s[i], 1);
#pragma unroll
  for (int i = 0; i < 4; i++) s[i] += __shfl_xor_sync(0xffffffffu, s[i], 2);
  const uint32_t t = tid_();
  if ((t & 3) == 0) st16(sb, sto + (t >> 5) * 1024 + (t & 28) * 4, OFF_ST, __float_as_uint(s[0]) | 1u, __float_as_uint(s[1]), __float_as_uint(s[2]), __float_as_uint(s[3]));
}
__device__ __forceinline__ void reduce4(const uint32_t* f, uint32_t* y) {
#pragma unroll
  for (int i = 0; i < 4; i++) {
    float lo = bf_lo(f[i]), hi = bf_hi(f[i]);
#pragma unroll
    for (int s = 1; s < 8; s++) { lo += bf_lo(f[4 * s + i]); hi += bf_hi(f[4 * s + i]); }
    y[i] = pack_bf16(lo, hi);
  }
}

#define TS(i) do {} while (0)
#define TSP(i) do {} while (0)
#define TSH(i) do {} while (0)

__host__ __device__ constexpr int role_j(int c) {
  return MAP == 0 ? (MC ? (c >> 1) & 7 : c & 7) : MAP == 1 ? c >> 4 : MAP == 2 ? ((c >> 6) << 2) | ((c >> 1) & 3)
       : MAP == 3 ? ((c >> 5) << 1) | ((c >> 2) & 1) : ((c >> 3) & 3) * 2 + ((c >> 2) & 1);
}
__host__ __device__ constexpr int role_rb(int c) {
  return MAP == 0 ? (MC ? (c >> 4) * 2 + (c & 1) : c >> 3) : MAP == 1 ? c & 15 : MAP == 2 ? ((c >> 3) & 7) * 2 + (c & 1)
       : MAP == 3 ? ((c >> 3) & 3) * 4 + (c & 3) : (c >> 5) * 4 + (c & 3);
}

struct Params {
  const __nv_bfloat16 *x, *wqkv, *wo, *wg, *wu, *wd;
  __nv_bfloat16* out;
  uint8_t* scr;
  uint8_t* times;
  unsigned zero, zero2;
};

__device__ __forceinline__ void tma_prefetch(const CUtensorMap* m, int c0, int c1) {
  asm volatile("cp.async.bulk.prefetch.tensor.2d.L2.global [%0, {%1, %2}];" ::"l"(m), "r"(c0), "r"(c1) : "memory");
}
__device__ __forceinline__ void fill_packed(int sl, uint32_t par, const uint8_t* src, uint32_t rank, uint32_t own) {
  mbar_wait(bar_empty(sl), par);
  mbar_expect_tx(bar_full(sl), PSLOT);
  if (MC) bulk_load_mc(own + slot_addr(sl) + rank * (PSLOT / 2), src + rank * (PSLOT / 2), PSLOT / 2, own + bar_full(sl));
  else bulk_load(slot_addr(sl), src, PSLOT, bar_full(sl));
}

__cluster_dims__(2, 1, 1)
__global__ void __launch_bounds__(384, 1)
fused_kernel(const __grid_constant__ CUtensorMap map_x, const __grid_constant__ CUtensorMap map_wg,
             const __grid_constant__ CUtensorMap map_wu, const __grid_constant__ CUtensorMap map_wd, const Params P) {
  const int wg = __shfl_sync(0xffffffffu, threadIdx.x >> 7, 0);
  const int cta = blockIdx.x, rank = MC ? cta & 1 : 0, j = role_j(cta), rb = role_rb(cta);
  const uint32_t own = win();
  unsigned* const flags = (unsigned*)(P.scr + OFF_FLAGS);
  if (__shfl_sync(0xffffffffu, threadIdx.x >> 5, 0) == 11) {
    if (threadIdx.x == 352) {
#pragma unroll
      for (int i = 0; i < 14; i++) { mbar_init(bar_full(i), 1); mbar_init(bar_empty(i), MC && i < 12 ? 4 : 2); }
      mbar_init(bar_full(14), 1); mbar_init(bar_empty(14), 1);
      asm volatile("fence.mbarrier_init.release.cluster;" ::: "memory");
      if (smem_u32(smem_raw) != own + SB) asm volatile("trap;");
    }
    __syncwarp();
    bar_arrive(0, 384);
    if (MC) asm volatile("barrier.cluster.arrive.relaxed.aligned;" ::: "memory");
    if (threadIdx.x == 352) {
#pragma unroll 1
      for (int c = 0; c < 9; c++) {
        mbar_expect_tx(bar_full(c), SLOT);
        tma_3d(own + slot_addr(c), &map_x, c * 64, rb * 64, 0, own + bar_full(c));
      }
    }

  } else {
    const unsigned ep0 = *(volatile unsigned*)&flags[(72 + cta) * 8];
    {
      const bool on = threadIdx.x < 324;
      const int k = rb * 36 + (on ? threadIdx.x / 36 : 0) * 4 + (threadIdx.x & 3), u = (threadIdx.x % 36) >> 2;
      const uint4* s = (const uint4*)(P.wqkv + k * 1728 + j * 72 + u * 8);
      const uint4 vk = __ldg(s + 72), vv = __ldg(s + 144), vq = __ldg(s);
      const int ko = k < 512 ? ((k >> 4) & 7) * 72 + (k >> 7) * 16 + (k & 15) : ((k >> 3) & 7) * 72 + 64 + (k & 7);
      const uint4 vo = __ldg((const uint4*)(P.wo + ko * 576 + (u < 8 ? (u >> 1) * 128 + j * 16 + (u & 1) * 8 : 512 + j * 8)));
      uint8_t* d = P.scr + OFF_WPACK + j * 24 * PSLOT;
      const uint32_t dkv = (k / 48) * PSLOT + u * 768 + (k % 48) * 16, dq = (k / 96) * PSLOT + u * 1536 + (k % 96) * 16;
      if (MC) asm volatile("barrier.cluster.arrive.relaxed.aligned;" ::: "memory");
      if (on) {
        st16(d, dkv, 0, vk.x, vk.y, vk.z, vk.w);
        st16(d, dkv, 9 * 768, vv.x, vv.y, vv.z, vv.w);
        st16(d, dq, 12 * PSLOT, vq.x, vq.y, vq.z, vq.w);
        st16(d, dq, 18 * PSLOT, vo.x, vo.y, vo.z, vo.w);
      }
      if (threadIdx.x == 351) sts32(SM_EPOCH, ep0);
      if (threadIdx.x == 0) TSP(3);
      asm volatile("fence.proxy.async.global;" ::: "memory");
    }
    bar_sync(0, 384);
  }
  __syncwarp();
  if (MC) asm volatile("barrier.cluster.wait.acquire.aligned;" ::: "memory");

  if (wg == 2) {
    asm volatile("setmaxnreg.dec.sync.aligned.u32 24;");
    const int pw = __shfl_sync(0xffffffffu, (threadIdx.x >> 5) & 3, 0), lane = threadIdx.x & 31;
    auto tile_col = [](int t, int j) { return t < 9 ? j * 576 + t * 64 : t == 9 ? 512 : (t - 10) * 128; };
    auto prefetch_tile = [&](int t) {
#pragma unroll 1
      for (int b = rb; b < 18; b += 16) {
        const int h = b & 1, k = b >> 1;
        if (t < 9) tma_prefetch(h ? &map_wu : &map_wg, tile_col(t, j), k * 64);
        else if (t != 9 || !h) tma_prefetch(&map_wd, tile_col(t, j) + h * 64, j * 576 + k * 64);
      }
    };
    if (pw == 0) {
      if (lane == 0) {
        TSP(5);
        flag_signal(&flags[j * 8]);
        TSP(6);
        flag_wait(&flags[j * 8], (lds32(SM_EPOCH) + 1) * 16);
        TSP(7);
        asm volatile("fence.proxy.async.global;" ::: "memory");
        const uint8_t* wp = P.scr + OFF_WPACK + j * 24 * PSLOT;
#pragma unroll 1
        for (int s = 0; s < 3; s++) fill_packed(9 + s, 1, wp + s * PSLOT, rank, own);
#pragma unroll 1
        for (int L = 0; L < 2; L++) {
#pragma unroll 1
          for (int s = 0; s < 21; s++) {
            if (TH && s >= TH) { const int o = s - TH; mbar_wait(bar_full(o < 9 ? o : o - 9), o < 9 || o >= 18); }
            fill_packed(s < 9 ? s : s - 9, s >= 9 && s < 18, wp + (s + 3) * PSLOT, rank, own);
          }
#pragma unroll 1
          for (int t = 0; t < 14; t++) {
            const int p = t - 9;
            const CUtensorMap* ma = p < 0 ? &map_wg : &map_wd;
            const CUtensorMap* mb = p < 0 ? &map_wu : &map_wd;
            const int ca = tile_col(t, j), cb = p < 0 ? ca : ca + 64, r0 = p < 0 ? 0 : j * 576;
            if (L * 14 + t + PF_AHEAD < 28) prefetch_tile((t + PF_AHEAD) % 14);
#pragma unroll 1
            for (int k = 0; k < 9; k++) {
              if (TH && t == 0) mbar_wait(bar_full(k >= TH ? k - TH : k + 12 - TH), 1);
              mbar_wait(bar_empty(k), t & 1);
              mbar_expect_tx(bar_full(k), p == 0 ? 8192 : SLOT);
              const int r = r0 + (p < 0 || k == 8 ? k : k < 3 ? k + 5 : k - 3) * 64;
              if (MC) {
                if (p != 0) tma_2d_mc(own + slot_addr(k) + rank * 8192, rank ? mb : ma, rank ? cb : ca, r, own + bar_full(k));
                else if ((k & 1) == rank) tma_2d_mc(own + slot_addr(k), ma, ca, r, own + bar_full(k));
              } else {
                tma_2d(slot_addr(k), ma, ca, r, bar_full(k));
                if (p != 0) tma_2d(slot_addr(k) + 8192, mb, cb, r, bar_full(k));
              }
            }
            if (p == 1 && L == 0) {
              l2_prefetch(wp + rb * (24 * PSLOT / 16), 24 * PSLOT / 16);
#pragma unroll 1
              for (int s = 0; s < 3; s++) fill_packed(9 + s, 1, wp + s * PSLOT, rank, own);
            }
          }
        }
        flags[(72 + cta) * 8] = lds32(SM_EPOCH) + 1;
      }
    } else if (pw < 3) {
      const int hw = pw - 1;
      const uint32_t ep = __shfl_sync(0xffffffffu, lds32(SM_EPOCH), 0);
      uint8_t* const sb = P.scr + (rb * 2 + hw) * STRM;
      const uint32_t xs = slot_addr(12) + hw * SLOT, fb = bar_full(12) + hw * 8;
      uint32_t hph = 0;
#pragma unroll 1
      for (int L = 0; L < 2; L++) {
        const uint32_t tag = ep * 2 + L + 1;
        if (L == 0) flag_wait(flags + (8 + rb) * 8, (ep + 1) * 8);
        bar_sync(NB_FREE + hw, 160);
        if (rb > 0) hint_wait(sb + OFF_HINT + 512 + j * 128, tag);
        uint32_t bad;
        do {
          if (rb > 0) {
            if (lane == 0) {
              mbar_expect_tx(bar_full(14) + hw * 128, 3072);
              bulk_load(own + ytail(hw * 2), sb + OFF_HALO + (L * 8 + j) * 3072, 1536, own + bar_full(14) + hw * 128);
              bulk_load(own + ytail(hw * 2 + 1), sb + OFF_HALO + (L * 8 + j) * 3072 + 1536, 1536, own + bar_full(14) + hw * 128);
            }
            mbar_wait(bar_full(14) + hw * 128, hph);
            hph ^= 1;
          }
          bad = 0;
#pragma unroll 1
          for (int c = 0; c < 3; c++) {
            uint32_t u[4] = {tag, 0, 0, 0}, v[4] = {tag, 0, 0, 0};
            if (rb > 0) { lds128(u, ytail(hw * 2) + c * 512 + lane * 16); lds128(v, ytail(hw * 2 + 1) + c * 512 + lane * 16); }
            bad |= (u[0] ^ tag) | (v[0] ^ tag);
#pragma unroll
            for (int i = 0; i < 3; i++) { sts32(xs + KSTG + (c * 3 + i) * 128 + lane * 4, u[i + 1]); sts32(xs + (c * 3 + i) * 128 + lane * 4, v[i + 1]); }
          }
        } while (__any_sync(0xffffffffu, bad != 0));
        bar_arrive(NB_HALO + hw, 160);
#pragma unroll 1
        for (int p = 0; p < 4; p++) {
          if (L == 0 && p == 3) flag_wait(flags + (40 + rb) * 8, (ep + 1) * 8);
          bar_sync(NB_FREE + hw, 160);
          TSH(L * 12 + p * 3);
          hint_wait(sb + OFF_HINT + (lane & 3) * 128, (ep * 15 + L * 8 + p + 3) * 8);
          TSH(L * 12 + p * 3 + 1);
          if (lane == 0) {
            mbar_expect_tx(fb, p ? PBUF : PBUF / 2);
            bulk_load(own + xs, sb + OFF_P + j * PSRC + (p ? (p == 2) * PBUF : 2 * PBUF), p ? PBUF : PBUF / 2, own + fb);
          }
          TSH(L * 12 + p * 3 + 2);
        }
      }
    } else {
      timed_wait(bar_full(9));
      if (lane == 0) {
#pragma unroll 1
        for (int t = 0; t < PF_AHEAD; t++) prefetch_tile(t);
      }
#pragma unroll 1
      for (int r = 0; r < 2; r++) {
#pragma unroll 1
        for (int t = r; t < 2 + 2 * r; t++) {
          const uint32_t so = rb * 2 * STRM + lane * 16;
#pragma unroll 1
          for (int i = 0; i < 18; i++) {
            st16(P.scr, so + t * TILE + j * 9216 + i * 512, 0, 0, 0, 0, 0);
            st16(P.scr, so + t * TILE + j * 9216 + i * 512, STRM, 0, 0, 0, 0);
            if (r || (i & 1)) __nanosleep(0);
          }
          if (t != 1) {
            st16(P.scr, so + (t ? t - 1 : 0) * 4096 + j * 512, OFF_ST, 0, 0, 0, 0);
            st16(P.scr, so + (t ? t - 1 : 0) * 4096 + j * 512, OFF_ST + STRM, 0, 0, 0, 0);
          }
        }
        __syncwarp();
        if (lane == 0) flag_signal(flags + (8 + r * 32 + rb) * 8);
        timed_wait(bar_empty(13) - r * 8);
      }
      if (MC) asm volatile("barrier.cluster.arrive.relaxed.aligned;\nbarrier.cluster.wait.aligned;" ::: "memory");
    }
  } else {
    asm volatile("setmaxnreg.inc.sync.aligned.u32 240;");
    const int w = __shfl_sync(0xffffffffu, (threadIdx.x >> 5) & 3, 0);
    const bool leader = (threadIdx.x & 127) == 0;
    const Rel rel{MC ? (threadIdx.x & 95) == 0 : leader, MC ? cta_window(w & 1) : 0};
    uint8_t* const sb = P.scr + (rb * 2 + wg) * STRM;
    uint8_t* const hint = sb + OFF_HINT + w * 128;
    auto hint_target = [](int e) { return (lds32(SM_EPOCH) * 15 + e + 1) * 8; };
    uint32_t a[144];
    TS(0);
#pragma unroll 1
    for (int L = 0; L < 2; L++) {
      uint32_t m0, m1; float r0, r1;
      if (L == 0) {
        Stats t;
        const int lane = tid_() & 31, g = lane >> 2;
        const int row = w * 16 + (lane & 15);
        const uint32_t ra = SB + wg * 8192 + row * 128;
#pragma unroll
        for (int c = 0; c < 9; c++) {
          mbar_wait(bar_full(c), 0);
          if (c == 0) TS(60); if (c == 4) TS(61); if (c == 8) TS(62);
#pragma unroll
          for (int kk = 0; kk < 4; kk++) {
            const int i = c * 16 + kk * 4;
            ldsm4(&a[i], ra + (((kk * 2 + (lane >> 4)) ^ (row & 7)) << 4) + c * SLOT);
          }
#pragma unroll
          for (int kk = 0; kk < 4; kk++) t.add16(&a[c * 16 + kk * 4]);
          if (c % 3 == 2) {
            bar_sync(NB_WG + wg, 128);
            rel(c - 2); rel(c - 1); rel(c);
          }
        }
        const int dl = (lane & ~3) | (g >> 1);
        ln_scalars(t.s[0], __shfl_sync(0xffffffffu, t.sq0(g), dl), m0, r0, P.zero);
        ln_scalars(t.s[2], __shfl_sync(0xffffffffu, t.sq1(g), dl), m1, r1, P.zero);
      } else {
#pragma unroll
        for (int i = 12 * D_KV; i < 144; i++) a[i] = 0;
        hint_wait(hint, hint_target(7));
        gather_ln<3 * D_KV>(a, sb, OFF_X2, 8192, m0, m1, r0, r1, P.zero);
      }
      TS(1 + L * 20);
      uint32_t kf[18], qf[18];
      {
        float acc[72];
        if (wg == 1) bar_sync(NB_ORD1, 256);
        mma_pass<144, PS_KV, 3, 256, D_KV, true>(acc, a, DESC_KV, 1, rel, wg == 0 ? NB_ORD1 : -1, sb, OFF_X2, L ^ 1, L == 0, m0, m1, P.zero);
        r0 = ln_rstd(r0, acc[0], P.zero); r1 = ln_rstd(r1, acc[0], P.zero);
        uint32_t vf[18];
#pragma unroll
        for (int c = 0; c < 9; c++) {
          kf[2 * c] = pack_bf16(acc[4 * c] * r0, acc[4 * c + 1] * r0);
          kf[2 * c + 1] = pack_bf16(acc[4 * c + 2] * r1, acc[4 * c + 3] * r1);
          vf[c] = pack_bf16(acc[36 + 4 * c] * r0, acc[36 + 4 * c + 1] * r0);
          vf[9 + c] = pack_bf16(acc[36 + 4 * c + 2] * r1, acc[36 + 4 * c + 3] * r1);
        }
        TS(2 + L * 20);
        const uint32_t l16 = (tid_() & 31) * 16, xs = slot_addr(12) + wg * SLOT + w * 1152;
#pragma unroll
        for (int i = 0; i < 4; i++) stsm4(xs + w * 1152 + 1152 + i * 512 + l16, vf[4 * i], vf[4 * i + 1], vf[4 * i + 2], vf[4 * i + 3]);
        sts32(xs + w * 1152 + 1152 + 2048 + l16 / 4, vf[16]); sts32(xs + w * 1152 + 1152 + 2176 + l16 / 4, vf[17]);
        if (w < 3) {
          stsm4(xs + KSTG + 1152 + l16, kf[1], kf[3], kf[5], kf[7]);
          stsm4(xs + KSTG + 1152 + 512 + l16, kf[9], kf[11], kf[13], kf[15]);
          sts32(xs + KSTG + 1152 + 1024 + l16 / 4, kf[17]);
        } else if (rb < 15) {
          const uint32_t tag = lds32(SM_EPOCH) * 2 + L + 1;
          const uint32_t ho = l16 + (L * 8 + j) * 3072;
#pragma unroll
          for (int c = 0; c < 3; c++) {
            st16(sb, ho, 2 * STRM + OFF_HALO + c * 512, tag, kf[6 * c + 1], kf[6 * c + 3], kf[6 * c + 5]);
            st16(sb, ho, 2 * STRM + OFF_HALO + 1536 + c * 512, tag, vf[9 + 3 * c], vf[10 + 3 * c], vf[11 + 3 * c]);
          }
          hint_post(sb + 2 * STRM + OFF_HINT + 512 + j * 128);
        }
      }
      bar_arrive(NB_FREE + wg, 160);
      {
        float acc[36];
#pragma unroll
        for (int i = 0; i < 4; i++) asm volatile("xor.b32 %0, %1, %2;" : "=r"(a[i]) : "r"(a[i]), "r"(P.zero2));
        if (wg == 1) bar_sync(NB_ORD1, 256);
        mma_pass<72, PS_Q, 6, 256, 0, false>(acc, a, DESC_Q, 0, rel, -1);
#pragma unroll
        for (int c = 0; c < 9; c++) {
          qf[2 * c] = pack_bf16(acc[4 * c] * r0, acc[4 * c + 1] * r0);
          qf[2 * c + 1] = pack_bf16(acc[4 * c + 2] * r1, acc[4 * c + 3] * r1);
        }
      }
      TS(3 + L * 20);
      uint32_t xr[18];
      {
        uint32_t kh[12], vt[28];
        const int tid = tid_(), g = (tid >> 2) & 7, q = tid & 3;
        bar_sync(NB_HALO + wg, 160);
        {
          const uint32_t xs = slot_addr(12) + wg * SLOT + w * 1152 + (tid & 31) * 16;
#pragma unroll
          for (int i = 0; i < 3; i++) ldsm4(&kh[4 * i], xs + KSTG + i * 512);
#pragma unroll
          for (int i = 0; i < 7; i++) ldsm4t(&vt[4 * i], xs + w * 1152 + i * 512);
        }
        TS(14 + L * 20);
        const bool nohalo = (rb == 0 && w == 0);
        const bool le0 = 2 * q <= g, le1 = 2 * q + 1 <= g;
        const uint32_t M = (le0 ? 0xffffu : 0u) | (le1 ? 0xffff0000u : 0u);
        const float sc = 0.23570226039551584f * 1.4426950408889634f;
        float l[16], t[8];
#pragma unroll
        for (int h = 0; h < 4; h++) {
          const uint32_t qa0 = q >= h ? qf[4 * h] : 0u, qa1 = q >= h ? qf[4 * h + 1] : 0u;
          const uint32_t qc0 = q <= h ? qf[4 * h + 4] : 0u, qc1 = q <= h ? qf[4 * h + 5] : 0u;
          float sm[4] = {0, 0, 0, 0}, s0[4] = {0, 0, 0, 0}, s1[4] = {0, 0, 0, 0};
          mma16816(s0, qa0, qa1, qf[4 * h + 2], qf[4 * h + 3], kf[4 * h], kf[4 * h + 2]);
          mma16816(s1, qa0, qa1, qf[4 * h + 2], qf[4 * h + 3], kf[4 * h + 1], kf[4 * h + 3]);
          mma16816(sm, qa0, qa1, qf[4 * h + 2], qf[4 * h + 3], kh[2 * h], kh[2 * h + 1]);
          mma1688(s0, qc0, qc1, kf[4 * h + 4]);
          mma1688(s1, qc0, qc1, kf[4 * h + 5]);
          mma1688(sm, qc0, qc1, kh[2 * h + 2]);
          if (nohalo) sm[0] = sm[1] = -1e9f / 0.23570226039551584f;
          l[4 * h] = le0 ? s0[0] : sm[0]; l[4 * h + 1] = le1 ? s0[1] : sm[1];
          l[4 * h + 2] = le0 ? s1[2] : s0[2]; l[4 * h + 3] = le1 ? s1[3] : s0[3];
        }
#pragma unroll
        for (int i = 0; i < 8; i++) t[i] = fmaxf(l[2 * i], l[2 * i + 1]);
#pragma unroll
        for (int i = 0; i < 8; i++) t[i] = fmaxf(t[i], __shfl_xor_sync(0xffffffffu, t[i], 1));
#pragma unroll
        for (int i = 0; i < 8; i++) t[i] = fmaxf(t[i], __shfl_xor_sync(0xffffffffu, t[i], 2)) * sc;
#pragma unroll
        for (int i = 0; i < 8; i++) { l[2 * i] = ex2(fmaf(l[2 * i], sc, -t[i])); l[2 * i + 1] = ex2(fmaf(l[2 * i + 1], sc, -t[i])); t[i] = l[2 * i] + l[2 * i + 1]; }
#pragma unroll
        for (int i = 0; i < 8; i++) t[i] += __shfl_xor_sync(0xffffffffu, t[i], 1);
#pragma unroll
        for (int i = 0; i < 8; i++) t[i] += __shfl_xor_sync(0xffffffffu, t[i], 2);
        uint32_t pf[16];
#pragma unroll
        for (int i = 0; i < 8; i++) {
          float r; asm("rcp.approx.ftz.f32 %0, %1;" : "=f"(r) : "f"(t[i]));
          const uint32_t p = pack_bf16(l[2 * i] * r, l[2 * i + 1] * r);
          pf[2 * i] = p & ~M; pf[2 * i + 1] = p & M;
        }
#pragma unroll
        for (int c = 0; c < 9; c++) {
          const int h = c == 8 ? 3 : c >> 1;
          float o[4] = {0, 0, 0, 0};
          mma16816(o, pf[4 * h], 0u, pf[4 * h + 1], pf[4 * h + 2], vt[c], vt[9 + c]);
          mma1688(o, 0u, pf[4 * h + 3], vt[18 + c]);
          if (c == 2 || c == 4 || c == 6) {
            float e[4] = {0, 0, 0, 0};
            mma16816(e, pf[4 * h - 4], 0u, pf[4 * h - 3], pf[4 * h - 2], vt[c], vt[9 + c]);
            mma1688(e, 0u, pf[4 * h - 1], vt[18 + c]);
            if (q < h) { o[0] = e[0]; o[1] = e[1]; o[2] = e[2]; o[3] = e[3]; }
          }
          qf[2 * c] = pack_bf16(o[0], o[1]); qf[2 * c + 1] = pack_bf16(o[2], o[3]);
        }
        store_own(qf, sb, OFF_O, j);
        hint_post(hint);
        bar_arrive(NB_ORD1 - wg, 256);
        if (L == 0) {
          const uint32_t xo = (rb * 128 + wg + (w * 16 + g) * 2) * (2 * DM) + q * 4 + j * 16;
#pragma unroll
          for (int c = 0; c < 9; c++) {
            const int o = c < 8 ? (c >> 1) * 256 + (c & 1) * 16 : 1024;
            xr[2 * c] = ldg4(P.x, c < 8 ? xo + j * 16 : xo, o); xr[2 * c + 1] = ldg4(P.x, c < 8 ? xo + j * 16 : xo, o + 32 * DM);
          }
        } else {
          load_own(xr, sb, OFF_X2, j);
        }
      }
      TS(4 + L * 20);
      {
        hint_wait(hint, hint_target(L * 8));
        TS(5 + L * 20);
        load_frags<6 * D_WO>(a, sb, OFF_O, tid_());
        float acc[36];
        if (wg == 0) bar_sync(NB_ORD0, 256);
        mma_pass<72, PS_WO, 6, 256, D_WO, false>(acc, a, DESC_Q, 0, rel, -1, sb, OFF_O);
        TS(6 + L * 20);
#pragma unroll
        for (int c = 0; c < 9; c++) {
          xr[2 * c] = bf2_add(xr[2 * c], pack_bf16(acc[4 * c], acc[4 * c + 1]));
          xr[2 * c + 1] = bf2_add(xr[2 * c + 1], pack_bf16(acc[4 * c + 2], acc[4 * c + 3]));
        }
        store_own(xr, sb, L * 3 * TILE, j);
        store_stats18(xr, sb, L * 4096 + j * 128);
        hint_post(hint);
      }
      TS(16 + L * 20);
      hint_wait(hint, hint_target(L * 8 + 1));
      TS(15 + L * 20);
      gather_ln<4 * D_T0>(a, sb, L * 3 * TILE, L * 4096, m0, m1, r0, r1, P.zero);
      TS(7 + L * 20);
      const uint32_t hb = (L ^ 1) * TILE + j * 9216;
      {
        float ka0, kb0, kc0, ka1, kb1, kc1;
        float acc[64];
        uint32_t hf[16];
        auto geglu = [&](auto chains, uint32_t hsm) {
          constexpr int CH = decltype(chains)::value;
          float r[32];
#pragma unroll
          for (int e = 0; e < 32; e++) {
            float x = acc[e];
            if (e >= CH) x = __uint_as_float(__float_as_uint(x) ^ (__float_as_uint(r[e - CH]) & P.zero));
            if (CH != 2 && e < 20) {
              const uint32_t ad = (e < 8 ? slot_addr(12) + e * 2048 + wg * 8192 : slot_addr(7 + (e >> 2)) + (e & 3) * 2048) + hsm;
              lds128(&a[48 + 4 * e], e >= CH ? ad ^ (__float_as_uint(r[e - CH]) & P.zero) : ad);
            }
            const bool hi = e & 2;
            float t = x * fmaf(x * x, hi ? kb1 : kb0, hi ? ka1 : ka0);
            asm("tanh.approx.f32 %0, %0;" : "+f"(t));
            const float u = x * acc[32 + e] * (hi ? kc1 : kc0);
            r[e] = fmaf(u, t, u);
            if (e & 1) hf[e >> 1] = pack_bf16(r[e - 1], r[e]);
          }
        };
        if (wg == 1) bar_sync(NB_ORD1, 256);
        mma_pass<128, PS_FF, 4, 2048, D_T0, true>(acc, a, DESC_SW128, 1, rel, NB_ORD1 - wg, sb, L * 3 * TILE, 0, false, m0, m1);
        TS(8 + L * 20);
        r0 = ln_rstd(r0, acc[0], P.zero); r1 = ln_rstd(r1, acc[0], P.zero);
        ka0 = 0.7978845608028654f * r0; kb0 = 0.035677408136300125f * r0 * r0 * r0; kc0 = 0.5f * r0 * r0;
        ka1 = 0.7978845608028654f * r1; kb1 = 0.035677408136300125f * r1 * r1 * r1; kc1 = 0.5f * r1 * r1;
#pragma unroll 1
        for (int t = 0; t < 8; t++) {
          geglu(IntC<2>(), 0);
          const uint32_t t16 = tid_() * 16;
          if (t < 5) {
            const uint32_t d = (t < 2 ? slot_addr(12) + wg * SLOT + t * 8192 : slot_addr(7) + t * SLOT + wg * 8192) + t16;
#pragma unroll
            for (int i = 0; i < 4; i++)
              sts128(d + i * 2048, hf[4 * i], hf[4 * i + 1], hf[4 * i + 2], hf[4 * i + 3]);
            if (t == 4) asm volatile("fence.proxy.async.shared::cta;" ::: "memory");
          } else {
#pragma unroll
            for (int i = 0; i < 4; i++) st16(sb, hb + (t - 5) * TILE + t16, i * 2048, hf[4 * i], hf[4 * i + 1], hf[4 * i + 2], hf[4 * i + 3]);
          }
          bar_sync(NB_ORD0 + wg, 256);
          mma_pass<128, PS_FF, 4, 2048, 0, false, true>(acc, a, DESC_SW128, t & 1, rel, NB_ORD1 - wg, sb, hb + t16, t == 7);
        }
        TS(9 + L * 20);
        const uint32_t hsm = wg * 8192 + tid_() * 16;
        geglu(IntC<CH_LAST>(), hsm);
#pragma unroll
        for (int i = 0; i < 16; i++) a[128 + i] = hf[i];
      }
      TS(10 + L * 20);
      {
        const uint32_t xs = slot_addr(12) + wg * SLOT;
        {
          bar_sync(NB_ORD0 + wg + ((a[142] | a[143]) & P.zero), 256);
          TS(64 + L * 32);
          rel(9); rel(10); rel(11);
          float acc[32];
          mma_pass<64, PS_FF, 4, 2048, 0, false>(acc, a, DESC_SW128, 0, rel, NB_ORD1 - wg);
          TS(65 + L * 32);
          const uint32_t t8 = tid_() * 8;
#pragma unroll
          for (int i = 0; i < 8; i++) {
            const uint32_t u = pack_bf16(acc[4 * i], acc[4 * i + 1]), v = pack_bf16(acc[4 * i + 2], acc[4 * i + 3]);
            if (i == j) sts64(xs + PBUF + t8 * 2, u, v);
            else st8(sb, ((j - i - 1) & 7) * 1024 + t8, OFF_P + 2 * PBUF + i * PSRC, (u & ~1u) | (L ^ 1), v);
          }
          hint_post(hint);
          if (L == 0 && tid_() == 0) mbar_arrive(bar_empty(13));
          bar_arrive(NB_FREE + wg, 160);
          TS(68 + L * 32);
        }
        uint32_t y[18];
#pragma unroll 1
        for (int p = 1; p < 5; p++) {
          bar_sync(NB_ORD0 + wg, 256);
          TS(64 + L * 32 + p * 5);
          uint32_t in[32];
          const uint32_t t16 = tid_() * 16;
          {
            float acc[64];
            mma_pass<128, PS_FF, 4, 2048, 0, false>(acc, a, DESC_SW128, p & 1, rel, (p == 4 && wg == 1) ? -1 : NB_ORD1 - wg);
            TS(65 + L * 32 + p * 5);
            lds128(&in[28], xs + PBUF + t16);
            mbar_wait(bar_full(12) + wg * 8, (p & 1) ^ 1);
            TS(66 + L * 32 + p * 5);
            {
              const uint32_t flip = p == 1 ? L - 1 : p < 4 ? ~0u : 0u;
              const uint32_t sh = p == 1;
              uint32_t m = 0;
#pragma unroll
              for (int s = 0; s < 7; s++) m |= lds32(xs + ((s * 2048 + t16) >> sh)) ^ flip;
              if (__builtin_expect(__any_sync(0xffffffffu, m & 1), 0)) {
#pragma unroll 1
                for (int s = 0; s < 7; s++) {
                  const uint32_t o = (s * 2048 + t16) >> sh;
                  uint32_t v[4] = {0, 0, 0, 0};
                  do {
                    if (sh) ld8(v, sb, j * PSRC + o, OFF_P + 2 * PBUF);
                    else ld16(v, sb, j * PSRC + (p & 1) * PBUF + o, OFF_P);
                  } while (__any_sync(0xffffffffu, (v[0] ^ flip) & 1));
                  sts64(xs + o, v[0], v[1]);
                  if (!sh) sts64(xs + o + 8, v[2], v[3]);
                }
                asm volatile("fence.proxy.async.shared::cta;" ::: "memory");
              }
            }
#pragma unroll
            for (int i = 0; i < 8; i++) {
              const uint32_t u0 = pack_bf16(acc[8 * i], acc[8 * i + 1]), u1 = pack_bf16(acc[8 * i + 2], acc[8 * i + 3]);
              const uint32_t u2 = pack_bf16(acc[8 * i + 4], acc[8 * i + 5]), u3 = pack_bf16(acc[8 * i + 6], acc[8 * i + 7]);
              if (i == j) sts128(xs + PBUF + t16, u0, u1, u2, u3);
              else st16(sb, ((j - i - 1) & 7) * 2048 + ((p & 1) ^ 1) * PBUF + t16, OFF_P + i * PSRC, (u0 & ~1u) | (p < 3), u1, u2, u3);
            }
          }
          hint_post(hint);
          TS(68 + L * 32 + p * 5);
          if (p == 1) {
#pragma unroll
            for (int s = 0; s < 7; s++) {
              lds64(in[4 * s], in[4 * s + 1], xs + s * 1024 + t16 / 2);
              in[4 * s + 2] = in[4 * s + 3] = 0;
            }
          } else {
#pragma unroll
            for (int s = 0; s < 7; s++) lds128(&in[4 * s], xs + s * 2048 + t16);
          }
          if (p < 4) bar_arrive(NB_FREE + wg, 160);
          reduce4(in, y + 8);
          if (p == 1) sts64(ytail(wg * 2 + (t16 >> 10)) + 2048 + (t16 & 1023) / 2, y[8], y[9]);
          else if (p < 4) sts128(ytail(wg * 2 + p - 2) + t16, y[8], y[9], y[10], y[11]);
          TS(67 + L * 32 + p * 5);
        }
        TS(11 + L * 20);
        const uint32_t t = tid_();
#pragma unroll
        for (int i = 0; i < 2; i++) lds128(&y[4 * i], ytail(wg * 2 + i) + t * 16);
        lds128(&a[28], xs + PBUF + t * 16);
        lds64(y[16], y[17], ytail(wg * 2 + (t >> 6)) + 2048 + (t & 63) * 8);
        load_own(xr, sb, L * 3 * TILE, j);
        hint_wait(hint, hint_target(L * 8 + 6));
        TS(17 + L * 20);
        {
          uint32_t m;
          do {
            m = 0;
#pragma unroll
            for (int s = 0; s < 7; s++) { ld16(&a[4 * s], sb, j * PSRC + t * 16, OFF_P + PBUF + s * 2048); m |= a[4 * s]; }
          } while (__any_sync(0xffffffffu, m & 1));
          TS(12 + L * 20);
          reduce4(a, y + 12);
        }
#pragma unroll
        for (int i = 0; i < 18; i++) xr[i] = bf2_add(xr[i], y[i]);
        TS(18 + L * 20);
        if (L == 0) {
          store_own(xr, sb, OFF_X2, j);
          store_stats18(xr, sb, 8192 + j * 128);
          hint_post(hint);
        } else {
          const uint32_t xo = (rb * 128 + wg + (w * 16 + ((t >> 2) & 7)) * 2) * (2 * DM) + (t & 3) * 4 + j * 16;
#pragma unroll
          for (int c = 0; c < 9; c++) {
            const int o = c < 8 ? (c >> 1) * 256 + (c & 1) * 16 : 1024;
            stg4(P.out, c < 8 ? xo + j * 16 : xo, o, xr[2 * c]); stg4(P.out, c < 8 ? xo + j * 16 : xo, o + 32 * DM, xr[2 * c + 1]);
          }
        }
      }
      TS(13 + L * 20);
    }
    bar_sync(NB_WG + wg, 128);
    if (tid_() == 0) mbar_arrive(bar_empty(12));
  }
}

typedef CUresult (*EncodeFn)(CUtensorMap*, CUtensorMapDataType, cuuint32_t, void*, const cuuint64_t*, const cuuint64_t*, const cuuint32_t*,
                             const cuuint32_t*, CUtensorMapInterleave, CUtensorMapSwizzle, CUtensorMapL2promotion, CUtensorMapFloatOOBfill);

void encode(EncodeFn fn, CUtensorMap* m, const void* p, int rank, const cuuint64_t* dims, const cuuint64_t* str, const cuuint32_t* box) {
  const cuuint32_t es[3] = {1, 1, 1};
  fn(m, CU_TENSOR_MAP_DATA_TYPE_BFLOAT16, rank, const_cast<void*>(p), dims, str, box, es, CU_TENSOR_MAP_INTERLEAVE_NONE,
     CU_TENSOR_MAP_SWIZZLE_128B, CU_TENSOR_MAP_L2_PROMOTION_L2_256B, CU_TENSOR_MAP_FLOAT_OOB_FILL_NONE);
}

}

extern "C" void kernel_launch(void* const* d_in, const int* in_sizes, int n_in, void* d_out, int out_size) {
  (void)in_sizes; (void)n_in; (void)out_size;
  Params P;
  P.x = (const __nv_bfloat16*)d_in[0]; P.wqkv = (const __nv_bfloat16*)d_in[1]; P.wo = (const __nv_bfloat16*)d_in[2];
  P.wg = (const __nv_bfloat16*)d_in[4]; P.wu = (const __nv_bfloat16*)d_in[5]; P.wd = (const __nv_bfloat16*)d_in[6];
  P.out = (__nv_bfloat16*)d_out; P.zero = 0; P.zero2 = 0;
  cudaGetSymbolAddress((void**)&P.scr, g_scr);
  void* fnp = nullptr; cudaDriverEntryPointQueryResult qr;
  cudaGetDriverEntryPoint("cuTensorMapEncodeTiled", &fnp, cudaEnableDefault, &qr);
  EncodeFn fn = (EncodeFn)fnp;
  CUtensorMap mx, mg, mu, md;
  { const cuuint64_t dims[3] = {DM, SEQ / 2, 2}, str[2] = {DM * 4, DM * 2}; const cuuint32_t box[3] = {64, 64, 2}; encode(fn, &mx, P.x, 3, dims, str, box); }
  { const cuuint64_t dims[2] = {DFF, DM}, str[1] = {DFF * 2}; const cuuint32_t box[2] = {64, 64}; encode(fn, &mg, P.wg, 2, dims, str, box); encode(fn, &mu, P.wu, 2, dims, str, box); }
  { const cuuint64_t dims[2] = {DM, DFF}, str[1] = {DM * 2}; const cuuint32_t box[2] = {64, 64}; encode(fn, &md, P.wd, 2, dims, str, box); }
  cudaFuncSetAttribute(fused_kernel, cudaFuncAttributeMaxDynamicSharedMemorySize, SMEM_BYTES);
  fused_kernel<<<128, 384, SMEM_BYTES, cudaStreamPerThread>>>(mx, mg, mu, md, P);
}
```

```cpp
#include <cuda_runtime.h>
#include <cuda_bf16.h>
#include <cuda.h>
#include <stdint.h>

#define KV_LEAD 5
#define D_KV 8
#define D_WO 5
#define D_T0 6
#define PF_AHEAD 3
#define CH_LAST 4
#define MC 0
#define MAP 3
#define TIMING 0

namespace {

constexpr int SEQ = 2048, DM = 576, DFF = 4608;
constexpr uint32_t SB = 1024;
constexpr uint32_t SLOT = 16384;
constexpr uint32_t PSLOT = 13824;
constexpr uint32_t BARS = SB + 14 * SLOT;
constexpr int SMEM_BYTES = 14 * SLOT + 256 + 2560;
__host__ __device__ constexpr uint32_t slot_addr(int s) { return SB + s * SLOT; }
__host__ __device__ constexpr uint32_t bar_full(int s) { return BARS + 8 * s; }
__host__ __device__ constexpr uint32_t bar_empty(int s) { return BARS + 128 + 8 * s; }
enum { NB_ORD0 = 1, NB_ORD1 = 2, NB_WG = 3  , NB_HALO = 5  , NB_FREE = 7  , NB_PUB = 9   };
constexpr uint32_t SM_EPOCH = BARS + 120;
__host__ __device__ constexpr uint32_t ytail(uint32_t k) { return k < 3 ? slot_addr(9) + PSLOT + k * SLOT : BARS + 256; }
constexpr uint32_t KSTG = 9 * 1152;

constexpr uint32_t TILE = 36 * 2048;
constexpr uint32_t OFF_X1 = 0  , OFF_O = TILE, OFF_X2 = 2 * TILE, OFF_ST = 4 * TILE  ;
constexpr uint32_t PBUF = 7 * 2048, PSRC = 2 * PBUF + PBUF / 2;
constexpr uint32_t OFF_P = OFF_ST + 3 * 4096, OFF_HALO = OFF_P + 8 * PSRC  , OFF_HINT = OFF_HALO + 2 * 8 * 3072  ,
                   STRM = OFF_HINT + 12 * 128;
constexpr uint32_t OFF_WPACK = 32 * STRM, OFF_FLAGS = OFF_WPACK + 8 * 24 * PSLOT;
__device__ __align__(1024) uint8_t g_scr[OFF_FLAGS + (8 + 64 + 128) * 32];

__device__ __forceinline__ uint32_t smem_u32(const void* p) { return (uint32_t)__cvta_generic_to_shared(p); }
extern __shared__ __align__(1024) uint8_t smem_raw[];
__device__ __forceinline__ uint32_t win() { return MC ? (blockIdx.x & 1) << 24 : 0; }
#define SA(A, W) ".reg .u32 sa;\nadd.u32 sa, " A ", " W ";\n"
__device__ __forceinline__ void mbar_init(uint32_t bar, uint32_t cnt) { asm volatile("{\n" SA("%0", "%2") "mbarrier.init.shared::cta.b64 [sa], %1;\n}" ::"r"(bar), "r"(cnt), "r"(win())); }
__device__ __forceinline__ void mbar_expect_tx(uint32_t bar, uint32_t bytes) { asm volatile("{\n" SA("%0", "%2") "mbarrier.arrive.expect_tx.shared::cta.b64 _, [sa], %1;\n}" ::"r"(bar), "r"(bytes), "r"(win()) : "memory"); }
__device__ __forceinline__ void mbar_arrive(uint32_t bar) { asm volatile("{\n" SA("%0", "%1") "mbarrier.arrive.shared::cta.b64 _, [sa];\n}" ::"r"(bar), "r"(win()) : "memory"); }
__device__ __forceinline__ uint32_t lds32(uint32_t a) { uint32_t v; asm volatile("{\n" SA("%1", "%2") "ld.shared.u32 %0, [sa];\n}" : "=r"(v) : "r"(a), "r"(win()) : "memory"); return v; }
__device__ __forceinline__ void lds64(uint32_t& x, uint32_t& y, uint32_t a) { asm volatile("{\n" SA("%2", "%3") "ld.shared.v2.u32 {%0,%1}, [sa];\n}" : "=r"(x), "=r"(y) : "r"(a), "r"(win()) : "memory"); }
__device__ __forceinline__ void lds128(uint32_t* v, uint32_t a) {
  asm volatile("{\n" SA("%4", "%5") "ld.shared.v4.u32 {%0,%1,%2,%3}, [sa];\n}" : "=r"(v[0]), "=r"(v[1]), "=r"(v[2]), "=r"(v[3]) : "r"(a), "r"(win()) : "memory");
}
__device__ __forceinline__ void stsm4(uint32_t a, uint32_t x, uint32_t y, uint32_t z, uint32_t w) {
  asm volatile("{\n" SA("%0", "%5") "stmatrix.sync.aligned.m8n8.x4.shared.b16 [sa], {%1,%2,%3,%4};\n}" ::"r"(a), "r"(x), "r"(y), "r"(z), "r"(w), "r"(win()) : "memory");
}
__device__ __forceinline__ void ldsm4(uint32_t* v, uint32_t a) {
  asm volatile("{\n" SA("%4", "%5") "ldmatrix.sync.aligned.m8n8.x4.shared.b16 {%0,%1,%2,%3}, [sa];\n}" : "=r"(v[0]), "=r"(v[1]), "=r"(v[2]), "=r"(v[3]) : "r"(a), "r"(win()) : "memory");
}
__device__ __forceinline__ void ldsm4t(uint32_t* v, uint32_t a) {
  asm volatile("{\n" SA("%4", "%5") "ldmatrix.sync.aligned.m8n8.x4.trans.shared.b16 {%0,%1,%2,%3}, [sa];\n}" : "=r"(v[0]), "=r"(v[1]), "=r"(v[2]), "=r"(v[3]) : "r"(a), "r"(win()) : "memory");
}
__device__ __forceinline__ void sts32(uint32_t a, uint32_t x) { asm volatile("{\n" SA("%0", "%2") "st.shared.u32 [sa], %1;\n}" ::"r"(a), "r"(x), "r"(win()) : "memory"); }
__device__ __forceinline__ void sts64(uint32_t a, uint32_t x, uint32_t y) { asm volatile("{\n" SA("%0", "%3") "st.shared.v2.u32 [sa], {%1,%2};\n}" ::"r"(a), "r"(x), "r"(y), "r"(win()) : "memory"); }
__device__ __forceinline__ void sts128(uint32_t a, uint32_t x, uint32_t y, uint32_t z, uint32_t w) {
  asm volatile("{\n" SA("%0", "%5") "st.shared.v4.u32 [sa], {%1,%2,%3,%4};\n}" ::"r"(a), "r"(x), "r"(y), "r"(z), "r"(w), "r"(win()) : "memory");
}
__device__ __forceinline__ void mbar_wait(uint32_t bar, uint32_t parity) {
  asm volatile("{\n.reg .pred p;\n" SA("%0", "%2") "LAB_WAIT:\nmbarrier.try_wait.parity.shared::cta.b64 p, [sa], %1;\n@!p bra LAB_WAIT;\n}" ::"r"(bar), "r"(parity), "r"(win()) : "memory");
}
__device__ __forceinline__ void timed_wait(uint32_t bar, uint32_t par) {
  asm volatile("{\n.reg .pred p;\n.reg .u64 t0, t1;\nmov.u64 t0, %%globaltimer;\nLAB_WD:\n"
               "mbarrier.try_wait.parity.shared::cta.b64 p, [%0], %1, 100000;\n@p bra LAB_OK;\n"
               "mov.u64 t1, %%globaltimer;\nsub.u64 t1, t1, t0;\nsetp.lt.u64 p, t1, 2000000000;\n@p bra LAB_WD;\ntrap;\nLAB_OK:\n}" ::"r"(bar + win()), "r"(par) : "memory");
}
__device__ __forceinline__ void flag_wait(const unsigned* flag, unsigned target) {
  asm volatile("{\n.reg .pred p;\n.reg .u32 v;\nLAB_WAIT:\nld.acquire.gpu.global.u32 v, [%0];\nsub.u32 v, v, %1;\n"
               "setp.lt.s32 p, v, 0;\n@p nanosleep.u32 100;\n@p bra LAB_WAIT;\n}" ::"l"(flag), "r"(target) : "memory");
}
__device__ __forceinline__ void hint_post(uint8_t* p) {
  __syncwarp();
  asm volatile("{\n.reg .pred p;\nelect.sync _|p, 0xffffffff;\n@p red.relaxed.gpu.global.add.u32 [%0], 1;\n}" ::"l"(p) : "memory");
}
__device__ __forceinline__ void hint_wait(const uint8_t* p, uint32_t target) {
  asm volatile("{\n.reg .pred p;\n.reg .u32 v;\nLAB_WAIT:\nld.relaxed.gpu.global.u32 v, [%0];\nsub.u32 v, v, %1;\n"
               "setp.lt.s32 p, v, 0;\nvote.sync.any.pred p, p, 0xffffffff;\n@p bra LAB_WAIT;\n}" ::"l"(p), "r"(target) : "memory");
}
__device__ __forceinline__ void flag_signal(unsigned* flag) { asm volatile("red.release.gpu.global.add.u32 [%0], 1;" ::"l"(flag) : "memory"); }
struct Rel {
  bool on; uint32_t base;
  __device__ __forceinline__ void operator()(int s) const {
    if (on) {
      if (MC) asm volatile("{\n" SA("%0", "%1") "mbarrier.arrive.shared::cluster.b64 _, [sa];\n}" ::"r"(bar_empty(s)), "r"(base) : "memory");
      else mbar_arrive(bar_empty(s));
    }
  }
};
__device__ __forceinline__ uint32_t cta_window(uint32_t rank) { uint32_t a; asm("mapa.shared::cluster.u32 %0, %1, %2;" : "=r"(a) : "r"(0), "r"(rank)); return a; }
__device__ __forceinline__ void tma_2d_mc(uint32_t dst, const CUtensorMap* m, int c0, int c1, uint32_t bar) {
  asm volatile("cp.async.bulk.tensor.2d.shared::cluster.global.mbarrier::complete_tx::bytes.multicast::cluster [%0], [%1, {%3, %4}], [%2], %5;"
               ::"r"(dst), "l"(m), "r"(bar), "r"(c0), "r"(c1), "h"((uint16_t)3) : "memory");
}
__device__ __forceinline__ void bulk_load_mc(uint32_t dst, const void* src, uint32_t bytes, uint32_t bar) {
  asm volatile("cp.async.bulk.shared::cluster.global.mbarrier::complete_tx::bytes.multicast::cluster [%0], [%1], %2, [%3], %4;"
               ::"r"(dst), "l"(src), "r"(bytes), "r"(bar), "h"((uint16_t)3) : "memory");
}
__device__ __forceinline__ void tma_2d(uint32_t dst, const CUtensorMap* m, int c0, int c1, uint32_t bar) {
  asm volatile("cp.async.bulk.tensor.2d.shared::cluster.global.mbarrier::complete_tx::bytes [%0], [%1, {%3, %4}], [%2];"
               ::"r"(dst), "l"(m), "r"(bar), "r"(c0), "r"(c1) : "memory");
}
__device__ __forceinline__ void tma_3d(uint32_t dst, const CUtensorMap* m, int c0, int c1, int c2, uint32_t bar) {
  asm volatile("cp.async.bulk.tensor.3d.shared::cluster.global.mbarrier::complete_tx::bytes [%0], [%1, {%3, %4, %5}], [%2];"
               ::"r"(dst), "l"(m), "r"(bar), "r"(c0), "r"(c1), "r"(c2) : "memory");
}
__device__ __forceinline__ void bulk_load(uint32_t dst, const void* src, uint32_t bytes, uint32_t bar) {
  asm volatile("cp.async.bulk.shared::cluster.global.mbarrier::complete_tx::bytes [%0], [%1], %2, [%3];" ::"r"(dst), "l"(src), "r"(bytes), "r"(bar) : "memory");
}
__device__ __forceinline__ void l2_prefetch(const void* src, uint32_t bytes) { asm volatile("cp.async.bulk.prefetch.L2.global [%0], %1;" ::"l"(src), "r"(bytes) : "memory"); }
__device__ __forceinline__ void wg_fence() { asm volatile("wgmma.fence.sync.aligned;" ::: "memory"); }
__device__ __forceinline__ void wg_commit() { asm volatile("wgmma.commit_group.sync.aligned;" ::: "memory"); }
template <int N> __device__ __forceinline__ void wg_wait() { asm volatile("wgmma.wait_group.sync.aligned %0;" ::"n"(N) : "memory"); }
__device__ __forceinline__ void bar_sync(int id, int n) { asm volatile("bar.sync %0, %1;" ::"r"(id), "r"(n) : "memory"); }
__device__ __forceinline__ void bar_arrive(int id, int n) { asm volatile("bar.arrive %0, %1;" ::"r"(id), "r"(n) : "memory"); }
__device__ __forceinline__ uint32_t pack_bf16(float lo, float hi) { uint32_t r; asm("cvt.rn.bf16x2.f32 %0, %1, %2;" : "=r"(r) : "f"(hi), "f"(lo)); return r; }
__device__ __forceinline__ float bf_lo(uint32_t w) { return __uint_as_float(w << 16); }
__device__ __forceinline__ float bf_hi(uint32_t w) { return __uint_as_float(w & 0xffff0000u); }
__device__ __forceinline__ float bf_round(float x) { return bf_lo(pack_bf16(x, 0.f)); }
__device__ __forceinline__ uint32_t bf2_sub(uint32_t a, uint32_t b) { uint32_t r; asm("sub.rn.bf16x2 %0, %1, %2;" : "=r"(r) : "r"(a), "r"(b)); return r; }
__device__ __forceinline__ uint32_t bf2_add(uint32_t a, uint32_t b) { uint32_t r; asm("add.rn.bf16x2 %0, %1, %2;" : "=r"(r) : "r"(a), "r"(b)); return r; }
#define GADDR(B, O, I) "cvt.u64.u32 ad, " O ";\nadd.u64 ad, ad, " B ";\nadd.u64 ad, ad, " I ";\n"
__device__ __forceinline__ void ld16(uint32_t* v, const uint8_t* ub, uint32_t off, uint32_t imm) {
  asm volatile("{\n.reg .b128 z;\n.reg .b64 x, y, ad;\n" GADDR("%4", "%5", "%6") "ld.relaxed.gpu.global.b128 z, [ad];\n"
               "mov.b128 {x, y}, z;\nmov.b64 {%0,%1}, x;\nmov.b64 {%2,%3}, y;\n}"
               : "=r"(v[0]), "=r"(v[1]), "=r"(v[2]), "=r"(v[3]) : "l"(ub), "r"(off), "l"((uint64_t)imm) : "memory");
}
__device__ __forceinline__ void ld8(uint32_t* v, const uint8_t* ub, uint32_t off, uint32_t imm) {
  asm volatile("{\n.reg .b64 x, ad;\n" GADDR("%2", "%3", "%4") "ld.relaxed.gpu.global.b64 x, [ad];\nmov.b64 {%0,%1}, x;\n}"
               : "=r"(v[0]), "=r"(v[1]) : "l"(ub), "r"(off), "l"((uint64_t)imm) : "memory");
}
__device__ __forceinline__ void st16(uint8_t* ub, uint32_t off, uint32_t imm, uint32_t a, uint32_t b, uint32_t c, uint32_t d) {
  asm volatile("{\n.reg .b128 z;\n.reg .b64 x, y, ad;\n" GADDR("%0", "%1", "%2") "mov.b64 x, {%3,%4};\nmov.b64 y, {%5,%6};\nmov.b128 z, {x, y};\n"
               "st.relaxed.gpu.global.b128 [ad], z;\n}" ::"l"(ub), "r"(off), "l"((uint64_t)imm), "r"(a), "r"(b), "r"(c), "r"(d) : "memory");
}
__device__ __forceinline__ void st8(uint8_t* ub, uint32_t off, uint32_t imm, uint32_t a, uint32_t b) {
  asm volatile("{\n.reg .b64 x, ad;\n" GADDR("%0", "%1", "%2") "mov.b64 x, {%3,%4};\nst.relaxed.gpu.global.b64 [ad], x;\n}"
               ::"l"(ub), "r"(off), "l"((uint64_t)imm), "r"(a), "r"(b) : "memory");
}
__device__ __forceinline__ uint4 ldg_line(const void* p) {
  uint4 v; asm volatile("ld.global.nc.L2::128B.v4.u32 {%0,%1,%2,%3}, [%4];" : "=r"(v.x), "=r"(v.y), "=r"(v.z), "=r"(v.w) : "l"(p)); return v;
}
__device__ __forceinline__ void stg4(void* ub, uint32_t off, uint32_t imm, uint32_t v) {
  asm volatile("{\n.reg .b64 ad;\n" GADDR("%0", "%1", "%2") "st.global.u32 [ad], %3;\n}" ::"l"(ub), "r"(off), "l"((uint64_t)imm), "r"(v) : "memory");
}
__device__ __forceinline__ uint32_t tid_() { uint32_t t; asm volatile("mov.u32 %0, %%tid.x;" : "=r"(t)); return t & 127; }
__device__ __forceinline__ uint32_t nz(uint32_t w) { return max(w, 1u); }
__device__ __forceinline__ void mma16816(float (&c)[4], uint32_t a0, uint32_t a1, uint32_t a2, uint32_t a3, uint32_t b0, uint32_t b1) {
  asm("mma.sync.aligned.m16n8k16.row.col.f32.bf16.bf16.f32 {%0,%1,%2,%3}, {%4,%5,%6,%7}, {%8,%9}, {%0,%1,%2,%3};"
               : "+f"(c[0]), "+f"(c[1]), "+f"(c[2]), "+f"(c[3]) : "r"(a0), "r"(a1), "r"(a2), "r"(a3), "r"(b0), "r"(b1));
}
__device__ __forceinline__ void mma1688(float (&c)[4], uint32_t a0, uint32_t a1, uint32_t b0) {
  asm("mma.sync.aligned.m16n8k8.row.col.f32.bf16.bf16.f32 {%0,%1,%2,%3}, {%4,%5}, {%6}, {%0,%1,%2,%3};"
               : "+f"(c[0]), "+f"(c[1]), "+f"(c[2]), "+f"(c[3]) : "r"(a0), "r"(a1), "r"(b0));
}
__device__ __forceinline__ float ex2(float x) { float r; asm("ex2.approx.ftz.f32 %0, %1;" : "=f"(r) : "f"(x)); return r; }
__device__ __forceinline__ float quad_sum(float v) { v += __shfl_xor_sync(0xffffffffu, v, 1); v += __shfl_xor_sync(0xffffffffu, v, 2); return v; }
__device__ __forceinline__ float quad_max(float v) { v = fmaxf(v, __shfl_xor_sync(0xffffffffu, v, 1)); v = fmaxf(v, __shfl_xor_sync(0xffffffffu, v, 2)); return v; }

__device__ __forceinline__ void wgmma_rs_n64(float (&d)[32], uint32_t a0, uint32_t a1, uint32_t a2, uint32_t a3, uint64_t desc, int scale_d) {
  asm volatile("{\n.reg .pred p;\nsetp.ne.b32 p, %37, 0;\n"
    "wgmma.mma_async.sync.aligned.m64n64k16.f32.bf16.bf16 "
    "{%0, %1, %2, %3, %4, %5, %6, %7, %8, %9, %10, %11, %12, %13, %14, %15, %16, %17, %18, %19, %20, %21, %22, %23, %24, %25, %26, %27, %28, %29, %30, %31}, "
    "{%32, %33, %34, %35}, %36, p, 1, 1, 1;\n}\n"
    : "+f"(d[0]), "+f"(d[1]), "+f"(d[2]), "+f"(d[3]), "+f"(d[4]), "+f"(d[5]), "+f"(d[6]), "+f"(d[7]), "+f"(d[8]), "+f"(d[9]), "+f"(d[10]), "+f"(d[11]), "+f"(d[12]), "+f"(d[13]), "+f"(d[14]), "+f"(d[15]), "+f"(d[16]), "+f"(d[17]), "+f"(d[18]), "+f"(d[19]), "+f"(d[20]), "+f"(d[21]), "+f"(d[22]), "+f"(d[23]), "+f"(d[24]), "+f"(d[25]), "+f"(d[26]), "+f"(d[27]), "+f"(d[28]), "+f"(d[29]), "+f"(d[30]), "+f"(d[31])
    : "r"(a0), "r"(a1), "r"(a2), "r"(a3), "l"(desc), "r"(scale_d));
}

__device__ __forceinline__ void wgmma_rs_n72(float (&d)[36], uint32_t a0, uint32_t a1, uint32_t a2, uint32_t a3, uint64_t desc, int scale_d) {
  asm volatile("{\n.reg .pred p;\nsetp.ne.b32 p, %41, 0;\n"
    "wgmma.mma_async.sync.aligned.m64n72k16.f32.bf16.bf16 "
    "{%0, %1, %2, %3, %4, %5, %6, %7, %8, %9, %10, %11, %12, %13, %14, %15, %16, %17, %18, %19, %20, %21, %22, %23, %24, %25, %26, %27, %28, %29, %30, %31, %32, %33, %34, %35}, "
    "{%36, %37, %38, %39}, %40, p, 1, 1, 1;\n}\n"
    : "+f"(d[0]), "+f"(d[1]), "+f"(d[2]), "+f"(d[3]), "+f"(d[4]), "+f"(d[5]), "+f"(d[6]), "+f"(d[7]), "+f"(d[8]), "+f"(d[9]), "+f"(d[10]), "+f"(d[11]), "+f"(d[12]), "+f"(d[13]), "+f"(d[14]), "+f"(d[15]), "+f"(d[16]), "+f"(d[17]), "+f"(d[18]), "+f"(d[19]), "+f"(d[20]), "+f"(d[21]), "+f"(d[22]), "+f"(d[23]), "+f"(d[24]), "+f"(d[25]), "+f"(d[26]), "+f"(d[27]), "+f"(d[28]), "+f"(d[29]), "+f"(d[30]), "+f"(d[31]), "+f"(d[32]), "+f"(d[33]), "+f"(d[34]), "+f"(d[35])
    : "r"(a0), "r"(a1), "r"(a2), "r"(a3), "l"(desc), "r"(scale_d));
}

__device__ __forceinline__ void wgmma_rs_n128(float (&d)[64], uint32_t a0, uint32_t a1, uint32_t a2, uint32_t a3, uint64_t desc, int scale_d) {
  asm volatile("{\n.reg .pred p;\nsetp.ne.b32 p, %69, 0;\n"
    "wgmma.mma_async.sync.aligned.m64n128k16.f32.bf16.bf16 "
    "{%0, %1, %2, %3, %4, %5, %6, %7, %8, %9, %10, %11, %12, %13, %14, %15, %16, %17, %18, %19, %20, %21, %22, %23, %24, %25, %26, %27, %28, %29, %30, %31, %32, %33, %34, %35, %36, %37, %38, %39, %40, %41, %42, %43, %44, %45, %46, %47, %48, %49, %50, %51, %52, %53, %54, %55, %56, %57, %58, %59, %60, %61, %62, %63}, "
    "{%64, %65, %66, %67}, %68, p, 1, 1, 1;\n}\n"
    : "+f"(d[0]), "+f"(d[1]), "+f"(d[2]), "+f"(d[3]), "+f"(d[4]), "+f"(d[5]), "+f"(d[6]), "+f"(d[7]), "+f"(d[8]), "+f"(d[9]), "+f"(d[10]), "+f"(d[11]), "+f"(d[12]), "+f"(d[13]), "+f"(d[14]), "+f"(d[15]), "+f"(d[16]), "+f"(d[17]), "+f"(d[18]), "+f"(d[19]), "+f"(d[20]), "+f"(d[21]), "+f"(d[22]), "+f"(d[23]), "+f"(d[24]), "+f"(d[25]), "+f"(d[26]), "+f"(d[27]), "+f"(d[28]), "+f"(d[29]), "+f"(d[30]), "+f"(d[31]), "+f"(d[32]), "+f"(d[33]), "+f"(d[34]), "+f"(d[35]), "+f"(d[36]), "+f"(d[37]), "+f"(d[38]), "+f"(d[39]), "+f"(d[40]), "+f"(d[41]), "+f"(d[42]), "+f"(d[43]), "+f"(d[44]), "+f"(d[45]), "+f"(d[46]), "+f"(d[47]), "+f"(d[48]), "+f"(d[49]), "+f"(d[50]), "+f"(d[51]), "+f"(d[52]), "+f"(d[53]), "+f"(d[54]), "+f"(d[55]), "+f"(d[56]), "+f"(d[57]), "+f"(d[58]), "+f"(d[59]), "+f"(d[60]), "+f"(d[61]), "+f"(d[62]), "+f"(d[63])
    : "r"(a0), "r"(a1), "r"(a2), "r"(a3), "l"(desc), "r"(scale_d));
}

__device__ __forceinline__ void wgmma_rs_n144(float (&d)[72], uint32_t a0, uint32_t a1, uint32_t a2, uint32_t a3, uint64_t desc, int scale_d) {
  asm volatile("{\n.reg .pred p;\nsetp.ne.b32 p, %77, 0;\n"
    "wgmma.mma_async.sync.aligned.m64n144k16.f32.bf16.bf16 "
    "{%0, %1, %2, %3, %4, %5, %6, %7, %8, %9, %10, %11, %12, %13, %14, %15, %16, %17, %18, %19, %20, %21, %22, %23, %24, %25, %26, %27, %28, %29, %30, %31, %32, %33, %34, %35, %36, %37, %38, %39, %40, %41, %42, %43, %44, %45, %46, %47, %48, %49, %50, %51, %52, %53, %54, %55, %56, %57, %58, %59, %60, %61, %62, %63, %64, %65, %66, %67, %68, %69, %70, %71}, "
    "{%72, %73, %74, %75}, %76, p, 1, 1, 1;\n}\n"
    : "+f"(d[0]), "+f"(d[1]), "+f"(d[2]), "+f"(d[3]), "+f"(d[4]), "+f"(d[5]), "+f"(d[6]), "+f"(d[7]), "+f"(d[8]), "+f"(d[9]), "+f"(d[10]), "+f"(d[11]), "+f"(d[12]), "+f"(d[13]), "+f"(d[14]), "+f"(d[15]), "+f"(d[16]), "+f"(d[17]), "+f"(d[18]), "+f"(d[19]), "+f"(d[20]), "+f"(d[21]), "+f"(d[22]), "+f"(d[23]), "+f"(d[24]), "+f"(d[25]), "+f"(d[26]), "+f"(d[27]), "+f"(d[28]), "+f"(d[29]), "+f"(d[30]), "+f"(d[31]), "+f"(d[32]), "+f"(d[33]), "+f"(d[34]), "+f"(d[35]), "+f"(d[36]), "+f"(d[37]), "+f"(d[38]), "+f"(d[39]), "+f"(d[40]), "+f"(d[41]), "+f"(d[42]), "+f"(d[43]), "+f"(d[44]), "+f"(d[45]), "+f"(d[46]), "+f"(d[47]), "+f"(d[48]), "+f"(d[49]), "+f"(d[50]), "+f"(d[51]), "+f"(d[52]), "+f"(d[53]), "+f"(d[54]), "+f"(d[55]), "+f"(d[56]), "+f"(d[57]), "+f"(d[58]), "+f"(d[59]), "+f"(d[60]), "+f"(d[61]), "+f"(d[62]), "+f"(d[63]), "+f"(d[64]), "+f"(d[65]), "+f"(d[66]), "+f"(d[67]), "+f"(d[68]), "+f"(d[69]), "+f"(d[70]), "+f"(d[71])
    : "r"(a0), "r"(a1), "r"(a2), "r"(a3), "l"(desc), "r"(scale_d));
}

template <int N> struct WG;
template <> struct WG<64>  { static __device__ __forceinline__ void f(float (&d)[32], const uint32_t* a, uint64_t ds, int s) { wgmma_rs_n64(d, a[0], a[1], a[2], a[3], ds, s); } };
template <> struct WG<72>  { static __device__ __forceinline__ void f(float (&d)[36], const uint32_t* a, uint64_t ds, int s) { wgmma_rs_n72(d, a[0], a[1], a[2], a[3], ds, s); } };
template <> struct WG<128> { static __device__ __forceinline__ void f(float (&d)[64], const uint32_t* a, uint64_t ds, int s) { wgmma_rs_n128(d, a[0], a[1], a[2], a[3], ds, s); } };
template <> struct WG<144> { static __device__ __forceinline__ void f(float (&d)[72], const uint32_t* a, uint64_t ds, int s) { wgmma_rs_n144(d, a[0], a[1], a[2], a[3], ds, s); } };

constexpr uint64_t DESC_SW128 = ((uint64_t)(8192 >> 4) << 16) | ((uint64_t)(1024 >> 4) << 32) | (1ull << 62);
constexpr uint64_t DESC_KV = ((uint64_t)(128 >> 4) << 16) | ((uint64_t)(768 >> 4) << 32);
constexpr uint64_t DESC_Q = ((uint64_t)(128 >> 4) << 16) | ((uint64_t)(1536 >> 4) << 32);

template <int V> struct IntC { static constexpr int value = V; };
enum { PS_KV, PS_Q, PS_WO, PS_FF };
template <int PS> __host__ __device__ constexpr int pass_slot(int i) {
  return PS == PS_KV ? (i < 3 ? 9 + i : i - 3) : PS == PS_WO ? 6 + i : i;
}

__device__ __forceinline__ void load_frag(uint32_t (&a)[144], int i, const uint8_t* sb, uint32_t uo, uint32_t t) {
  if (i < 32) ld16(&a[4 * i], sb, uo + t * 16, i * 2048);
  else { ld8(&a[4 * i], sb, uo + t * 8, i * 2048); ld8(&a[4 * i + 2], sb, uo + t * 8, i * 2048 + 1024); }
}
__device__ __forceinline__ void store_own(const uint32_t (&y)[18], uint8_t* sb, uint32_t uo, int j, uint32_t t) {
  t += j * 128;
#pragma unroll
  for (int i = 0; i < 4; i++) st16(sb, uo + t * 16, i * 16384, nz(y[4 * i]), y[4 * i + 1], y[4 * i + 2], y[4 * i + 3]);
  st8(sb, uo + t * 8, 65536, nz(y[16]), y[17]);
}
__device__ __forceinline__ void load_own(uint32_t (&y)[18], const uint8_t* sb, uint32_t uo, int j) {
  const uint32_t t = tid_() + j * 128;
#pragma unroll
  for (int i = 0; i < 4; i++) ld16(&y[4 * i], sb, uo + t * 16, i * 16384);
  ld8(&y[16], sb, uo + t * 8, 65536);
}

template <int N, int PS, int KPS, int KSTEP, int CHK, bool SUB, bool HREL = false>
__device__ __forceinline__ void mma_pass(float (&acc)[N / 2], uint32_t (&a)[144], uint64_t desc, uint32_t par, const Rel& rel, int bar_id,
                                         const uint8_t* sb = nullptr, uint32_t uo = 0, uint32_t flag = 0, uint32_t m0 = 0, uint32_t m1 = 0, uint32_t park = 0) {
  constexpr int NS = 36 / KPS;
  auto check = [&](int s) {
    while (true) {
      uint32_t m = a[4 * s * KPS];
#pragma unroll
      for (int i = s * KPS; i < (s + 1) * KPS; i++) m = min(m, i < 32 ? a[4 * i] : min(a[4 * i], a[4 * i + 2]));
      if (!__any_sync(0xffffffffu, (m | flag) == 0)) break;
      const uint32_t t = tid_();
#pragma unroll
      for (int i = s * KPS; i < (s + 1) * KPS; i++) load_frag(a, i, sb, uo, t);
    }
  };
#pragma unroll
  for (int s = 0; s < NS; s++) {
    const int sl = pass_slot<PS>(s);
    if (CHK) {
      check(s);
      if (s + CHK < NS && !flag) {
        const uint32_t t = tid_();
#pragma unroll
        for (int i = (s + CHK) * KPS; i < (s + CHK + 1) * KPS; i++) load_frag(a, i, sb, uo, t);
      }
    }
    if (SUB) {
#pragma unroll
      for (int i = s * KPS * 4; i < (s + 1) * KPS * 4; i += 2) { a[i] = bf2_sub(a[i], m0); a[i + 1] = bf2_sub(a[i + 1], m1); }
    }
    if (PS == PS_KV && s == 0) sts128(park + tid_() * 16, a[0], a[1], a[2], a[3]);
    mbar_wait(bar_full(sl), sl < 9 ? par : par ^ 1);
    wg_fence();
#pragma unroll
    for (int kk = 0; kk < KPS; kk++)
      WG<N>::f(acc, &a[(s * KPS + kk) * 4], desc + ((slot_addr(sl) + kk * KSTEP) >> 4), (s | kk) ? 1 : 0);
    wg_commit();
    if (s == (PS == PS_KV ? KV_LEAD : NS - 1) && bar_id >= 0) bar_arrive(bar_id, 256);
    if (s > 0) {
      wg_wait<1>();
      if (!(PS == PS_WO && s > 3)) rel(pass_slot<PS>(s - 1));
    }
    if (HREL && s == 3 && flag) {
#pragma unroll
      for (int i = 0; i < 12; i++) ld16(&a[4 * i], sb, uo, (i >> 2) * TILE + (i & 3) * 2048);
    }
  }
  wg_wait<0>();
  if (PS != PS_WO) rel(pass_slot<PS>(NS - 1));
}

template <int NF> __device__ __forceinline__ void load_frags(uint32_t (&a)[144], const uint8_t* sb, uint32_t uo, uint32_t t) {
#pragma unroll
  for (int i = 0; i < NF; i++) load_frag(a, i, sb, uo, t);
}
__device__ __forceinline__ void ln_scalars(float s1, float s2, uint32_t& m, float& var, uint32_t zero) {
  const float mean = s1 * (1.f / DM);
  var = s2 * (1.f / DM) - mean * mean;
  m = pack_bf16(mean, mean) ^ (__float_as_uint(var) & zero);
}
__device__ __forceinline__ float ln_rstd(float var, float after, uint32_t zero) {
  var = __uint_as_float(__float_as_uint(var) ^ (__float_as_uint(after) & zero));
  float sd, r;
  asm("sqrt.approx.ftz.f32 %0, %1;" : "=f"(sd) : "f"(bf_round(bf_round(fmaxf(var, 0.f)) + 1e-5f)));
  asm("rcp.approx.ftz.f32 %0, %1;" : "=f"(r) : "f"(bf_round(sd)));
  return r;
}
template <int NF> __device__ __forceinline__ void gather_ln(uint32_t (&a)[144], const uint8_t* sb, uint32_t uo, uint32_t sto,
                                          uint32_t& m0, uint32_t& m1, float& r0, float& r1, uint32_t zero) {
  uint32_t u[32];
  const uint32_t t = tid_(), so = sto + (t >> 5) * 1024 + (t & 28) * 4;
#pragma unroll
  for (int i = 0; i < 8; i++) ld16(&u[4 * i], sb, so, OFF_ST + i * 128);
  load_frags<NF>(a, sb, uo, t);
  while (true) {
    uint32_t m = u[0];
#pragma unroll
    for (int i = 1; i < 8; i++) m = min(m, u[4 * i]);
    if (!__any_sync(0xffffffffu, m == 0)) break;
#pragma unroll
    for (int i = 0; i < 8; i++) ld16(&u[4 * i], sb, so, OFF_ST + i * 128);
  }
  float v[4];
#pragma unroll
  for (int k = 0; k < 4; k++)
    v[k] = ((__uint_as_float(u[k]) + __uint_as_float(u[4 + k])) + (__uint_as_float(u[8 + k]) + __uint_as_float(u[12 + k]))) +
           ((__uint_as_float(u[16 + k]) + __uint_as_float(u[20 + k])) + (__uint_as_float(u[24 + k]) + __uint_as_float(u[28 + k])));
  ln_scalars(v[1], v[0], m0, r0, zero); ln_scalars(v[3], v[2], m1, r1, zero);
}
struct Stats {
  float s[4] = {0, 0, 0, 0}, d0[4] = {0, 0, 0, 0}, d1[4] = {0, 0, 0, 0};
  __device__ __forceinline__ void add16(const uint32_t* f) {
    mma16816(s, f[0], f[1], f[2], f[3], 0x3f803f80u, 0x3f803f80u);
    mma16816(d0, f[0], f[1], f[2], f[3], f[0], f[2]);
    mma16816(d1, f[0], f[1], f[2], f[3], f[1], f[3]);
  }
  __device__ __forceinline__ float sq0(int g) const { return (g & 1) ? d0[1] : d0[0]; }
  __device__ __forceinline__ float sq1(int g) const { return (g & 1) ? d1[3] : d1[2]; }
};
__device__ __forceinline__ void store_stats18(const uint32_t (&y)[18], uint8_t* sb, uint32_t sto, uint32_t t) {
  float s[4] = {0, 0, 0, 0}, u[4] = {0, 0, 0, 0};
#pragma unroll
  for (int i = 0; i < 18; i++) {
    const float lo = bf_lo(y[i]), hi = bf_hi(y[i]);
    const int r = (i & 1) * 2;
    s[r] = fmaf(lo, lo, s[r]); u[r] = fmaf(hi, hi, u[r]); s[r + 1] += lo; u[r + 1] += hi;
  }
#pragma unroll
  for (int i = 0; i < 4; i++) s[i] += u[i];
#pragma unroll
  for (int i = 0; i < 4; i++) s[i] += __shfl_xor_sync(0xffffffffu, s[i], 1);
#pragma unroll
  for (int i = 0; i < 4; i++) s[i] += __shfl_xor_sync(0xffffffffu, s[i], 2);
  if ((t & 3) == 0) st16(sb, sto + (t >> 5) * 1024 + (t & 28) * 4, OFF_ST, __float_as_uint(s[0]) | 1u, __float_as_uint(s[1]), __float_as_uint(s[2]), __float_as_uint(s[3]));
}
__device__ __forceinline__ void reduce4(const uint32_t* f, uint32_t* y) {
#pragma unroll
  for (int i = 0; i < 4; i++) {
    float lo = bf_lo(f[i]), hi = bf_hi(f[i]);
#pragma unroll
    for (int s = 1; s < 8; s++) { lo += bf_lo(f[4 * s + i]); hi += bf_hi(f[4 * s + i]); }
    y[i] = pack_bf16(lo, hi);
  }
}

#define TS(i) do {} while (0)
#define TSP(i) do {} while (0)
#define TSH(i) do {} while (0)

__host__ __device__ constexpr int role_j(int c) {
  return MAP == 0 ? (MC ? (c >> 1) & 7 : c & 7) : MAP == 1 ? c >> 4 : MAP == 2 ? ((c >> 6) << 2) | ((c >> 1) & 3)
       : MAP == 3 ? ((c >> 5) << 1) | ((c >> 2) & 1) : ((c >> 3) & 3) * 2 + ((c >> 2) & 1);
}
__host__ __device__ constexpr int role_rb(int c) {
  return MAP == 0 ? (MC ? (c >> 4) * 2 + (c & 1) : c >> 3) : MAP == 1 ? c & 15 : MAP == 2 ? ((c >> 3) & 7) * 2 + (c & 1)
       : MAP == 3 ? ((c >> 3) & 3) * 4 + (c & 3) : (c >> 5) * 4 + (c & 3);
}

__device__ __forceinline__ uint32_t row_off(int rb, int wg, uint32_t t) { return (rb * 128 + wg + ((t >> 5) * 16 + (t & 15)) * 2) * (2 * DM); }

__device__ __forceinline__ const __nv_bfloat16* wo_src(const __nv_bfloat16* wo, int k, int u, int j) {
  const int ko = k < 512 ? ((k >> 4) & 7) * 72 + (k >> 7) * 16 + (k & 15) : ((k >> 3) & 7) * 72 + 64 + (k & 7);
  return wo + ko * 576 + (u < 8 ? (u >> 1) * 128 + j * 16 + (u & 1) * 8 : 512 + j * 8);
}

struct Params {
  const __nv_bfloat16 *x, *wqkv, *wo, *wg, *wu, *wd;
  __nv_bfloat16* out;
  uint8_t* scr;
  uint8_t* times;
  unsigned zero;
};

__device__ __forceinline__ void tma_prefetch(const CUtensorMap* m, int c0, int c1) {
  asm volatile("cp.async.bulk.prefetch.tensor.2d.L2.global [%0, {%1, %2}];" ::"l"(m), "r"(c0), "r"(c1) : "memory");
}
__device__ __forceinline__ void fill_packed(int sl, uint32_t par, const uint8_t* src, uint32_t rank, uint32_t own) {
  mbar_wait(bar_empty(sl), par);
  mbar_expect_tx(bar_full(sl), PSLOT);
  if (MC) bulk_load_mc(own + slot_addr(sl) + rank * (PSLOT / 2), src + rank * (PSLOT / 2), PSLOT / 2, own + bar_full(sl));
  else bulk_load(slot_addr(sl), src, PSLOT, bar_full(sl));
}

__global__ void __launch_bounds__(384, 1)
fused_kernel(const __grid_constant__ CUtensorMap map_x, const __grid_constant__ CUtensorMap map_wg,
             const __grid_constant__ CUtensorMap map_wu, const __grid_constant__ CUtensorMap map_wd, const Params P) {
  const int wg = __shfl_sync(0xffffffffu, threadIdx.x >> 7, 0);
  const int cta = blockIdx.x, rank = MC ? cta & 1 : 0, j = role_j(cta), rb = role_rb(cta);
  const uint32_t own = win();
  unsigned* const flags = (unsigned*)(P.scr + OFF_FLAGS);
  if (__shfl_sync(0xffffffffu, threadIdx.x >> 5, 0) == 11) {
    if (threadIdx.x == 352) {
#pragma unroll
      for (int i = 0; i < 14; i++) { mbar_init(bar_full(i), 1); mbar_init(bar_empty(i), MC && i < 12 ? 4 : 2); }
      mbar_init(bar_full(14), 1); mbar_init(bar_empty(14), 1);
      asm volatile("fence.mbarrier_init.release.cluster;" ::: "memory");
      if (smem_u32(smem_raw) != own + SB) asm volatile("trap;");
    }
    __syncwarp();
    bar_arrive(0, 384);
    if (MC) asm volatile("barrier.cluster.arrive.relaxed.aligned;" ::: "memory");
    if (threadIdx.x == 352) {
#pragma unroll 1
      for (int c = 0; c < 9; c++) {
        mbar_expect_tx(bar_full(c), SLOT);
        tma_3d(own + slot_addr(c), &map_x, c * 64, rb * 64, 0, own + bar_full(c));
      }
    }
  } else {
    const bool on = threadIdx.x < 324;
    const int k = rb * 36 + (on ? threadIdx.x / 36 : 0) * 4 + (threadIdx.x & 3), u = (threadIdx.x % 36) >> 2;
    const uint4* s = (const uint4*)(P.wqkv + k * 1728 + j * 72 + u * 8);
    const uint4 vk = ldg_line(s + 72), vv = ldg_line(s + 144);
    const unsigned ep0 = *(volatile unsigned*)&flags[(72 + cta) * 8];
    if (MC) asm volatile("barrier.cluster.arrive.relaxed.aligned;" ::: "memory");
    bar_sync(0, 384);
    uint8_t* d = P.scr + OFF_WPACK + j * 24 * PSLOT;
    if (on) {
      const uint32_t dkv = (k / 48) * PSLOT + u * 768 + (k % 48) * 16;
      st16(d, dkv, 0, vk.x, vk.y, vk.z, vk.w);
      st16(d, dkv, 9 * 768, vv.x, vv.y, vv.z, vv.w);
    }
    asm volatile("fence.proxy.async.global;" ::: "memory");
    bar_arrive(NB_PUB + 3, 384);
    if (threadIdx.x == 351) sts32(SM_EPOCH, ep0);
    if (wg == 2) bar_sync(NB_PUB + 1, 96);
  }
  __syncwarp();
  if (MC) asm volatile("barrier.cluster.wait.acquire.aligned;" ::: "memory");

  if (wg == 2) {
    asm volatile("setmaxnreg.dec.sync.aligned.u32 24;");
    const int pw = __shfl_sync(0xffffffffu, (threadIdx.x >> 5) & 3, 0), lane = threadIdx.x & 31;
    auto tile_col = [](int t, int j) { return t < 9 ? j * 576 + t * 64 : t == 9 ? 512 : (t - 10) * 128; };
    auto prefetch_tile = [&](int t) {
#pragma unroll 1
      for (int b = rb; b < 18; b += 16) {
        const int h = b & 1, k = b >> 1;
        if (t < 9) tma_prefetch(h ? &map_wu : &map_wg, tile_col(t, j), k * 64);
        else if (t != 9 || !h) tma_prefetch(&map_wd, tile_col(t, j) + h * 64, j * 576 + k * 64);
      }
    };
    if (pw == 0) {
      if (lane == 0) {
        flag_wait(&flags[j * 8], (lds32(SM_EPOCH) + 1) * 16);
        TSP(7);
        asm volatile("fence.proxy.async.global;" ::: "memory");
        const uint8_t* wp = P.scr + OFF_WPACK + j * 24 * PSLOT;
#pragma unroll 1
        for (int s = 0; s < 3; s++) fill_packed(9 + s, 1, wp + s * PSLOT, rank, own);
#pragma unroll 1
        for (int L = 0; L < 2; L++) {
#pragma unroll 1
          for (int s = 0; s < 21; s++) {
            if (s == 9 && L == 0) { flag_wait(&flags[(56 + j) * 8], (lds32(SM_EPOCH) + 1) * 16); asm volatile("fence.proxy.async.global;" ::: "memory"); }
            fill_packed(s < 9 ? s : s - 9, s >= 9 && s < 18, wp + (s + 3) * PSLOT, rank, own);
          }
#pragma unroll 1
          for (int t = 0; t < 14; t++) {
            const int p = t - 9;
            const CUtensorMap* ma = p < 0 ? &map_wg : &map_wd;
            const CUtensorMap* mb = p < 0 ? &map_wu : &map_wd;
            const int ca = tile_col(t, j), cb = p < 0 ? ca : ca + 64, r0 = p < 0 ? 0 : j * 576;
            if (L * 14 + t + PF_AHEAD < 28) prefetch_tile((t + PF_AHEAD) % 14);
#pragma unroll 1
            for (int k = 0; k < 9; k++) {
              mbar_wait(bar_empty(k), t & 1);
              mbar_expect_tx(bar_full(k), p == 0 ? 8192 : SLOT);
              const int r = r0 + (p < 0 || k == 8 ? k : k < 3 ? k + 5 : k - 3) * 64;
              if (MC) {
                if (p != 0) tma_2d_mc(own + slot_addr(k) + rank * 8192, rank ? mb : ma, rank ? cb : ca, r, own + bar_full(k));
                else if ((k & 1) == rank) tma_2d_mc(own + slot_addr(k), ma, ca, r, own + bar_full(k));
              } else {
                tma_2d(slot_addr(k), ma, ca, r, bar_full(k));
                if (p != 0) tma_2d(slot_addr(k) + 8192, mb, cb, r, bar_full(k));
              }
            }
            if (p == 1 && L == 0) {
              l2_prefetch(wp + rb * (24 * PSLOT / 16), 24 * PSLOT / 16);
#pragma unroll 1
              for (int s = 0; s < 3; s++) fill_packed(9 + s, 1, wp + s * PSLOT, rank, own);
            }
          }
        }
        flags[(72 + cta) * 8] = lds32(SM_EPOCH) + 1;
      }
    } else if (pw < 3) {
      const int hw = pw - 1;
      const uint32_t ep = __shfl_sync(0xffffffffu, lds32(SM_EPOCH), 0);
      uint8_t* const sb = P.scr + (rb * 2 + hw) * STRM;
      const uint32_t xs = slot_addr(12) + hw * SLOT, fb = bar_full(12) + hw * 8;
      uint32_t hph = 0;
#pragma unroll 1
      for (int L = 0; L < 2; L++) {
        const uint32_t tag = ep * 2 + L + 1;
        bar_sync(NB_FREE + hw, 160);
        if (rb > 0) hint_wait(sb + OFF_HINT + 512 + j * 128, tag);
        uint32_t bad;
        do {
          if (rb > 0) {
            if (lane == 0) {
              mbar_expect_tx(bar_full(14) + hw * 128, 3072);
              bulk_load(own + ytail(hw * 2), sb + OFF_HALO + (L * 8 + j) * 3072, 1536, own + bar_full(14) + hw * 128);
              bulk_load(own + ytail(hw * 2 + 1), sb + OFF_HALO + (L * 8 + j) * 3072 + 1536, 1536, own + bar_full(14) + hw * 128);
            }
            mbar_wait(bar_full(14) + hw * 128, hph);
            hph ^= 1;
          }
          bad = 0;
#pragma unroll 1
          for (int c = 0; c < 3; c++) {
            uint32_t u[4] = {tag, 0, 0, 0}, v[4] = {tag, 0, 0, 0};
            if (rb > 0) { lds128(u, ytail(hw * 2) + c * 512 + lane * 16); lds128(v, ytail(hw * 2 + 1) + c * 512 + lane * 16); }
            bad |= (u[0] ^ tag) | (v[0] ^ tag);
#pragma unroll
            for (int i = 0; i < 3; i++) { sts32(xs + KSTG + (c * 3 + i) * 128 + lane * 4, u[i + 1]); sts32(xs + (c * 3 + i) * 128 + lane * 4, v[i + 1]); }
          }
        } while (__any_sync(0xffffffffu, bad != 0));
        bar_arrive(NB_HALO + hw, 160);
#pragma unroll 1
        for (int p = 0; p < 4; p++) {
          if (L == 0 && p == 3) flag_wait(flags + (40 + rb) * 8, (ep + 1) * 8);
          bar_sync(NB_FREE + hw, 160);
          TSH(L * 12 + p * 3);
          hint_wait(sb + OFF_HINT + (lane & 3) * 128, (ep * 15 + L * 8 + p + 3) * 8);
          TSH(L * 12 + p * 3 + 1);
          if (lane == 0) {
            mbar_expect_tx(fb, p ? PBUF : PBUF / 2);
            bulk_load(own + xs, sb + OFF_P + j * PSRC + (p ? (p == 2) * PBUF : 2 * PBUF), p ? PBUF : PBUF / 2, own + fb);
          }
          TSH(L * 12 + p * 3 + 2);
        }
      }
    } else {
      auto clear = [&](int t) {
        const uint32_t so = rb * 2 * STRM + (threadIdx.x & 31) * 16;
#pragma unroll 1
        for (int i = 0; i < 18; i++) {
          st16(P.scr, so + t * TILE + j * 9216 + i * 512, 0, 0, 0, 0, 0);
          st16(P.scr, so + t * TILE + j * 9216 + i * 512, STRM, 0, 0, 0, 0);
          __nanosleep(0);
        }
        if (t != 1) {
          st16(P.scr, so + (t ? t - 1 : 0) * 4096 + j * 512, OFF_ST, 0, 0, 0, 0);
          st16(P.scr, so + (t ? t - 1 : 0) * 4096 + j * 512, OFF_ST + STRM, 0, 0, 0, 0);
        }
      };
      bar_sync(NB_PUB + 3, 384);
      if (lane == 0) flag_signal(&flags[j * 8]);
      TSP(5);
      bar_sync(NB_PUB + 2, 288);
      if (lane == 0) flag_signal(&flags[(56 + j) * 8]);
      TSP(4);
      if (lane == 0) {
#pragma unroll 1
        for (int t = 0; t < PF_AHEAD; t++) prefetch_tile(t);
      }
      __syncwarp();
#pragma unroll 1
      for (int L = 0; L < 2; L++) {
        timed_wait(bar_empty(13), L);
#pragma unroll 1
        for (int t = L ^ 1; t < 4 - 2 * L; t++) clear(t);
        __syncwarp();
        if (lane == 0 && L == 0) flag_signal(flags + (40 + rb) * 8);
      }
      timed_wait(bar_empty(12), 0);
      if (MC) asm volatile("barrier.cluster.arrive.relaxed.aligned;\nbarrier.cluster.wait.aligned;" ::: "memory");
    }
  } else {
    asm volatile("setmaxnreg.inc.sync.aligned.u32 240;");
    const int w = __shfl_sync(0xffffffffu, (threadIdx.x >> 5) & 3, 0);
    const bool leader = (threadIdx.x & 127) == 0;
    const Rel rel{MC ? (threadIdx.x & 95) == 0 : leader, MC ? cta_window(w & 1) : 0};
    uint8_t* const sb = P.scr + (rb * 2 + wg) * STRM;
    uint8_t* const hint = sb + OFF_HINT + w * 128;
    auto hint_target = [](int e) { return (lds32(SM_EPOCH) * 15 + e + 1) * 8; };
    TS(0);
    uint32_t a[144];
#pragma unroll 1
    for (int L = 0; L < 2; L++) {
      uint32_t m0, m1; float r0, r1;
      if (L == 0) {
        Stats st;
        const int lane = tid_() & 31, g = lane >> 2;
        const int row = w * 16 + (lane & 15);
        const uint32_t ra = SB + wg * 8192 + row * 128;
        const uint32_t pt = tid_(), pu = (pt % 36) >> 2, pk = rb * 36 + (pt < 108 ? pt / 36 : 0) * 4 + (pt & 3);
        uint4 pv[3];
#pragma unroll
        for (int i = 0; i < 3; i++) pv[i] = ldg_line(wg ? wo_src(P.wo, pk + i * 12, pu, j) : P.wqkv + (pk + i * 12) * 1728 + j * 72 + pu * 8);
#pragma unroll
        for (int c = 0; c < 9; c++) {
          mbar_wait(bar_full(c), 0);
          if (c == 0) TS(60); if (c == 8) TS(62);
#pragma unroll
          for (int kk = 0; kk < 4; kk++) ldsm4(&a[c * 16 + kk * 4], ra + (((kk * 2 + (lane >> 4)) ^ (row & 7)) << 4) + c * SLOT);
          if (c == 8) {
            uint32_t y[18], z[4];
#pragma unroll
            for (int i = 0; i < 4; i++) ldsm4(&y[4 * i], ra + ((((j & 3) * 2 + (lane >> 4)) ^ (row & 7)) << 4) + (2 * i + (j >> 2)) * SLOT);
            ldsm4(z, ra + ((j ^ (row & 7)) << 4) + 8 * SLOT);
            y[16] = z[0]; y[17] = z[1];
            bar_sync(NB_WG + wg, 128);
#pragma unroll
            for (int i = 0; i < 9; i++) rel(i);
            if (pt < 108) {
#pragma unroll
              for (int i = 0; i < 3; i++) {
                const uint32_t k = pk + i * 12;
                st16(P.scr, (j * 24 + wg * 6 + k / 96) * PSLOT + pu * 1536 + (k % 96) * 16, OFF_WPACK + 12 * PSLOT, pv[i].x, pv[i].y, pv[i].z, pv[i].w);
              }
            }
            asm volatile("fence.proxy.async.global;" ::: "memory");
            bar_arrive(NB_PUB + 2, 288);
            store_own(y, sb, OFF_X2, j, tid_());
          }
#pragma unroll
          for (int kk = 0; kk < 4; kk++) st.add16(&a[c * 16 + kk * 4]);
        }
        const int dl = (lane & ~3) | (g >> 1);
        ln_scalars(st.s[0], __shfl_sync(0xffffffffu, st.sq0(g), dl), m0, r0, P.zero);
        ln_scalars(st.s[2], __shfl_sync(0xffffffffu, st.sq1(g), dl), m1, r1, P.zero);
      } else {
#pragma unroll
        for (int i = 12 * D_KV; i < 144; i++) a[i] = 0;
        hint_wait(hint, hint_target(7));
        TS(61);
        gather_ln<3 * D_KV>(a, sb, OFF_X2, 8192, m0, m1, r0, r1, P.zero);
      }
      TS(1 + L * 20);
      uint32_t kf[18], qf[18];
      {
        float acc[72];
        if (wg == 1) bar_sync(NB_ORD1, 256);
        mma_pass<144, PS_KV, 3, 256, D_KV, true>(acc, a, DESC_KV, 1, rel, wg == 0 ? NB_ORD1 : -1, sb, OFF_X2, L ^ 1, m0, m1, ytail(wg * 2));
        r0 = ln_rstd(r0, acc[0], P.zero); r1 = ln_rstd(r1, acc[0], P.zero);
        uint32_t vf[18];
#pragma unroll
        for (int c = 0; c < 9; c++) {
          kf[2 * c] = pack_bf16(acc[4 * c] * r0, acc[4 * c + 1] * r0);
          kf[2 * c + 1] = pack_bf16(acc[4 * c + 2] * r1, acc[4 * c + 3] * r1);
          vf[c] = pack_bf16(acc[36 + 4 * c] * r0, acc[36 + 4 * c + 1] * r0);
          vf[9 + c] = pack_bf16(acc[36 + 4 * c + 2] * r1, acc[36 + 4 * c + 3] * r1);
        }
        TS(2 + L * 20);
        const uint32_t l16 = (tid_() & 31) * 16, xs = slot_addr(12) + wg * SLOT + w * 1152;
#pragma unroll
        for (int i = 0; i < 4; i++) stsm4(xs + w * 1152 + 1152 + i * 512 + l16, vf[4 * i], vf[4 * i + 1], vf[4 * i + 2], vf[4 * i + 3]);
        sts32(xs + w * 1152 + 1152 + 2048 + l16 / 4, vf[16]); sts32(xs + w * 1152 + 1152 + 2176 + l16 / 4, vf[17]);
        if (w < 3) {
          stsm4(xs + KSTG + 1152 + l16, kf[1], kf[3], kf[5], kf[7]);
          stsm4(xs + KSTG + 1152 + 512 + l16, kf[9], kf[11], kf[13], kf[15]);
          sts32(xs + KSTG + 1152 + 1024 + l16 / 4, kf[17]);
        } else if (rb < 15) {
          const uint32_t tag = lds32(SM_EPOCH) * 2 + L + 1;
          const uint32_t ho = l16 + (L * 8 + j) * 3072;
#pragma unroll
          for (int c = 0; c < 3; c++) {
            st16(sb, ho, 2 * STRM + OFF_HALO + c * 512, tag, kf[6 * c + 1], kf[6 * c + 3], kf[6 * c + 5]);
            st16(sb, ho, 2 * STRM + OFF_HALO + 1536 + c * 512, tag, vf[9 + 3 * c], vf[10 + 3 * c], vf[11 + 3 * c]);
          }
          hint_post(sb + 2 * STRM + OFF_HINT + 512 + j * 128);
        }
      }
      lds128(a, ytail(wg * 2) + tid_() * 16);
      bar_arrive(NB_FREE + wg, 160);
      {
        float acc[36];
        if (wg == 1) bar_sync(NB_ORD1, 256);
        mma_pass<72, PS_Q, 6, 256, 0, false>(acc, a, DESC_Q, 0, rel, -1);
#pragma unroll
        for (int c = 0; c < 9; c++) {
          qf[2 * c] = pack_bf16(acc[4 * c] * r0, acc[4 * c + 1] * r0);
          qf[2 * c + 1] = pack_bf16(acc[4 * c + 2] * r1, acc[4 * c + 3] * r1);
        }
      }
      TS(3 + L * 20);
      uint32_t xr[18];
      {
        uint32_t kh[12], vt[28];
        const int tid = tid_(), g = (tid >> 2) & 7, q = tid & 3;
        bar_sync(NB_HALO + wg, 160);
        {
          const uint32_t xs = slot_addr(12) + wg * SLOT + w * 1152 + (tid & 31) * 16;
#pragma unroll
          for (int i = 0; i < 3; i++) ldsm4(&kh[4 * i], xs + KSTG + i * 512);
#pragma unroll
          for (int i = 0; i < 7; i++) ldsm4t(&vt[4 * i], xs + w * 1152 + i * 512);
        }
        TS(14 + L * 20);
        const bool nohalo = (rb == 0 && w == 0);
        const bool le0 = 2 * q <= g, le1 = 2 * q + 1 <= g;
        const uint32_t M = (le0 ? 0xffffu : 0u) | (le1 ? 0xffff0000u : 0u);
        const float sc = 0.23570226039551584f * 1.4426950408889634f;
        float l[16], t[8];
#pragma unroll
        for (int h = 0; h < 4; h++) {
          const uint32_t qa0 = q >= h ? qf[4 * h] : 0u, qa1 = q >= h ? qf[4 * h + 1] : 0u;
          const uint32_t qc0 = q <= h ? qf[4 * h + 4] : 0u, qc1 = q <= h ? qf[4 * h + 5] : 0u;
          float sm[4] = {0, 0, 0, 0}, s0[4] = {0, 0, 0, 0}, s1[4] = {0, 0, 0, 0};
          mma16816(s0, qa0, qa1, qf[4 * h + 2], qf[4 * h + 3], kf[4 * h], kf[4 * h + 2]);
          mma16816(s1, qa0, qa1, qf[4 * h + 2], qf[4 * h + 3], kf[4 * h + 1], kf[4 * h + 3]);
          mma16816(sm, qa0, qa1, qf[4 * h + 2], qf[4 * h + 3], kh[2 * h], kh[2 * h + 1]);
          mma1688(s0, qc0, qc1, kf[4 * h + 4]);
          mma1688(s1, qc0, qc1, kf[4 * h + 5]);
          mma1688(sm, qc0, qc1, kh[2 * h + 2]);
          if (nohalo) sm[0] = sm[1] = -1e9f / 0.23570226039551584f;
          l[4 * h] = le0 ? s0[0] : sm[0]; l[4 * h + 1] = le1 ? s0[1] : sm[1];
          l[4 * h + 2] = le0 ? s1[2] : s0[2]; l[4 * h + 3] = le1 ? s1[3] : s0[3];
        }
#pragma unroll
        for (int i = 0; i < 8; i++) t[i] = fmaxf(l[2 * i], l[2 * i + 1]);
#pragma unroll
        for (int i = 0; i < 8; i++) t[i] = fmaxf(t[i], __shfl_xor_sync(0xffffffffu, t[i], 1));
#pragma unroll
        for (int i = 0; i < 8; i++) t[i] = fmaxf(t[i], __shfl_xor_sync(0xffffffffu, t[i], 2)) * sc;
#pragma unroll
        for (int i = 0; i < 8; i++) { l[2 * i] = ex2(fmaf(l[2 * i], sc, -t[i])); l[2 * i + 1] = ex2(fmaf(l[2 * i + 1], sc, -t[i])); t[i] = l[2 * i] + l[2 * i + 1]; }
#pragma unroll
        for (int i = 0; i < 8; i++) t[i] += __shfl_xor_sync(0xffffffffu, t[i], 1);
#pragma unroll
        for (int i = 0; i < 8; i++) t[i] += __shfl_xor_sync(0xffffffffu, t[i], 2);
        uint32_t pf[16];
#pragma unroll
        for (int i = 0; i < 8; i++) {
          float r; asm("rcp.approx.ftz.f32 %0, %1;" : "=f"(r) : "f"(t[i]));
          const uint32_t p = pack_bf16(l[2 * i] * r, l[2 * i + 1] * r);
          pf[2 * i] = p & ~M; pf[2 * i + 1] = p & M;
        }
#pragma unroll
        for (int c = 0; c < 9; c++) {
          const int h = c == 8 ? 3 : c >> 1;
          float o[4] = {0, 0, 0, 0};
          mma16816(o, pf[4 * h], 0u, pf[4 * h + 1], pf[4 * h + 2], vt[c], vt[9 + c]);
          mma1688(o, 0u, pf[4 * h + 3], vt[18 + c]);
          if (c == 2 || c == 4 || c == 6) {
            float e[4] = {0, 0, 0, 0};
            mma16816(e, pf[4 * h - 4], 0u, pf[4 * h - 3], pf[4 * h - 2], vt[c], vt[9 + c]);
            mma1688(e, 0u, pf[4 * h - 1], vt[18 + c]);
            if (q < h) { o[0] = e[0]; o[1] = e[1]; o[2] = e[2]; o[3] = e[3]; }
          }
          qf[2 * c] = pack_bf16(o[0], o[1]); qf[2 * c + 1] = pack_bf16(o[2], o[3]);
        }
        store_own(qf, sb, OFF_O, j, tid);
        hint_post(hint);
        bar_arrive(NB_ORD1 - wg, 256);
        load_own(xr, sb, OFF_X2, j);
      }
      TS(4 + L * 20);
      {
        hint_wait(hint, hint_target(L * 8));
        TS(5 + L * 20);
        load_frags<6 * D_WO>(a, sb, OFF_O, tid_());
        float acc[36];
        if (wg == 0) bar_sync(NB_ORD0, 256);
        mma_pass<72, PS_WO, 6, 256, D_WO, false>(acc, a, DESC_Q, 0, rel, -1, sb, OFF_O);
        TS(6 + L * 20);
#pragma unroll
        for (int c = 0; c < 9; c++) {
          xr[2 * c] = bf2_add(xr[2 * c], pack_bf16(acc[4 * c], acc[4 * c + 1]));
          xr[2 * c + 1] = bf2_add(xr[2 * c + 1], pack_bf16(acc[4 * c + 2], acc[4 * c + 3]));
        }
        store_own(xr, sb, L * 3 * TILE, j, tid_());
        store_stats18(xr, sb, L * 4096 + j * 128, tid_());
        hint_post(hint);
      }
      TS(16 + L * 20);
      hint_wait(hint, hint_target(L * 8 + 1));
      TS(15 + L * 20);
      gather_ln<4 * D_T0>(a, sb, L * 3 * TILE, L * 4096, m0, m1, r0, r1, P.zero);
      TS(7 + L * 20);
      const uint32_t hb = (L ^ 1) * TILE + j * 9216;
      {
        float ka0, kb0, kc0, ka1, kb1, kc1;
        float acc[64];
        uint32_t hf[16];
        auto geglu = [&](auto chains, uint32_t hsm) {
          constexpr int CH = decltype(chains)::value;
          float r[32];
#pragma unroll
          for (int e = 0; e < 32; e++) {
            float x = acc[e];
            if (e >= CH) x = __uint_as_float(__float_as_uint(x) ^ (__float_as_uint(r[e - CH]) & P.zero));
            if (CH != 2 && e < 20) {
              const uint32_t ad = (e < 8 ? slot_addr(12) + e * 2048 + wg * 8192 : slot_addr(7 + (e >> 2)) + (e & 3) * 2048) + hsm;
              lds128(&a[48 + 4 * e], e >= CH ? ad ^ (__float_as_uint(r[e - CH]) & P.zero) : ad);
            }
            const bool hi = e & 2;
            float t = x * fmaf(x * x, hi ? kb1 : kb0, hi ? ka1 : ka0);
            asm("tanh.approx.f32 %0, %0;" : "+f"(t));
            const float u = x * acc[32 + e] * (hi ? kc1 : kc0);
            r[e] = fmaf(u, t, u);
            if (e & 1) hf[e >> 1] = pack_bf16(r[e - 1], r[e]);
          }
        };
        if (wg == 1) bar_sync(NB_ORD1, 256);
        mma_pass<128, PS_FF, 4, 2048, D_T0, true>(acc, a, DESC_SW128, 1, rel, NB_ORD1 - wg, sb, L * 3 * TILE, 0, m0, m1);
        TS(8 + L * 20);
        r0 = ln_rstd(r0, acc[0], P.zero); r1 = ln_rstd(r1, acc[0], P.zero);
        ka0 = 0.7978845608028654f * r0; kb0 = 0.035677408136300125f * r0 * r0 * r0; kc0 = 0.5f * r0 * r0;
        ka1 = 0.7978845608028654f * r1; kb1 = 0.035677408136300125f * r1 * r1 * r1; kc1 = 0.5f * r1 * r1;
#pragma unroll 1
        for (int t = 0; t < 8; t++) {
          geglu(IntC<2>(), 0);
          const uint32_t t16 = tid_() * 16;
          if (t < 5) {
            const uint32_t d = (t < 2 ? slot_addr(12) + wg * SLOT + t * 8192 : slot_addr(7) + t * SLOT + wg * 8192) + t16;
#pragma unroll
            for (int i = 0; i < 4; i++)
              sts128(d + i * 2048, hf[4 * i], hf[4 * i + 1], hf[4 * i + 2], hf[4 * i + 3]);
            if (t == 4) asm volatile("fence.proxy.async.shared::cta;" ::: "memory");
          } else {
#pragma unroll
            for (int i = 0; i < 4; i++) st16(sb, hb + (t - 5) * TILE + t16, i * 2048, hf[4 * i], hf[4 * i + 1], hf[4 * i + 2], hf[4 * i + 3]);
          }
          bar_sync(NB_ORD0 + wg, 256);
          mma_pass<128, PS_FF, 4, 2048, 0, false, true>(acc, a, DESC_SW128, t & 1, rel, NB_ORD1 - wg, sb, hb + t16, t == 7);
        }
        TS(9 + L * 20);
        const uint32_t hsm = wg * 8192 + tid_() * 16;
        geglu(IntC<CH_LAST>(), hsm);
#pragma unroll
        for (int i = 0; i < 16; i++) a[128 + i] = hf[i];
      }
      TS(10 + L * 20);
      {
        const uint32_t xs = slot_addr(12) + wg * SLOT;
        {
          bar_sync(NB_ORD0 + wg + ((a[142] | a[143]) & P.zero), 256);
          TS(64 + L * 32);
          rel(9); rel(10); rel(11);
          float acc[32];
          mma_pass<64, PS_FF, 4, 2048, 0, false>(acc, a, DESC_SW128, 0, rel, NB_ORD1 - wg);
          TS(65 + L * 32);
          const uint32_t t8 = tid_() * 8;
#pragma unroll
          for (int i = 0; i < 8; i++) {
            const uint32_t u = pack_bf16(acc[4 * i], acc[4 * i + 1]), v = pack_bf16(acc[4 * i + 2], acc[4 * i + 3]);
            if (i == j) sts64(xs + PBUF + t8 * 2, u, v);
            else st8(sb, ((j - i - 1) & 7) * 1024 + t8, OFF_P + 2 * PBUF + i * PSRC, (u & ~1u) | (L ^ 1), v);
          }
          hint_post(hint);
          if (tid_() == 0) mbar_arrive(bar_empty(13));
          bar_arrive(NB_FREE + wg, 160);
          TS(68 + L * 32);
        }
        uint32_t y[18];
#pragma unroll 1
        for (int p = 1; p < 5; p++) {
          bar_sync(NB_ORD0 + wg, 256);
          TS(64 + L * 32 + p * 5);
          uint32_t in[32];
          const uint32_t t16 = tid_() * 16;
          {
            float acc[64];
            mma_pass<128, PS_FF, 4, 2048, 0, false>(acc, a, DESC_SW128, p & 1, rel, (p == 4 && wg == 1) ? -1 : NB_ORD1 - wg);
            TS(65 + L * 32 + p * 5);
            lds128(&in[28], xs + PBUF + t16);
            mbar_wait(bar_full(12) + wg * 8, (p & 1) ^ 1);
            TS(66 + L * 32 + p * 5);
            {
              const uint32_t flip = p == 1 ? L - 1 : p < 4 ? ~0u : 0u;
              const uint32_t sh = p == 1;
              uint32_t m = 0;
#pragma unroll
              for (int s = 0; s < 7; s++) m |= lds32(xs + ((s * 2048 + t16) >> sh)) ^ flip;
              if (__builtin_expect(__any_sync(0xffffffffu, m & 1), 0)) {
#pragma unroll 1
                for (int s = 0; s < 7; s++) {
                  const uint32_t o = (s * 2048 + t16) >> sh;
                  uint32_t v[4] = {0, 0, 0, 0};
                  do {
                    if (sh) ld8(v, sb, j * PSRC + o, OFF_P + 2 * PBUF);
                    else ld16(v, sb, j * PSRC + (p & 1) * PBUF + o, OFF_P);
                  } while (__any_sync(0xffffffffu, (v[0] ^ flip) & 1));
                  sts64(xs + o, v[0], v[1]);
                  if (!sh) sts64(xs + o + 8, v[2], v[3]);
                }
                asm volatile("fence.proxy.async.shared::cta;" ::: "memory");
              }
            }
#pragma unroll
            for (int i = 0; i < 8; i++) {
              const uint32_t u0 = pack_bf16(acc[8 * i], acc[8 * i + 1]), u1 = pack_bf16(acc[8 * i + 2], acc[8 * i + 3]);
              const uint32_t u2 = pack_bf16(acc[8 * i + 4], acc[8 * i + 5]), u3 = pack_bf16(acc[8 * i + 6], acc[8 * i + 7]);
              if (i == j) sts128(xs + PBUF + t16, u0, u1, u2, u3);
              else st16(sb, ((j - i - 1) & 7) * 2048 + ((p & 1) ^ 1) * PBUF + t16, OFF_P + i * PSRC, (u0 & ~1u) | (p < 3), u1, u2, u3);
            }
          }
          hint_post(hint);
          TS(68 + L * 32 + p * 5);
          if (p == 1) {
#pragma unroll
            for (int s = 0; s < 7; s++) {
              lds64(in[4 * s], in[4 * s + 1], xs + s * 1024 + t16 / 2);
              in[4 * s + 2] = in[4 * s + 3] = 0;
            }
          } else {
#pragma unroll
            for (int s = 0; s < 7; s++) lds128(&in[4 * s], xs + s * 2048 + t16);
          }
          if (p < 4) bar_arrive(NB_FREE + wg, 160);
          reduce4(in, y + 8);
          if (p == 1) sts64(ytail(wg * 2 + (t16 >> 10)) + 2048 + (t16 & 1023) / 2, y[8], y[9]);
          else if (p < 4) sts128(ytail(wg * 2 + p - 2) + t16, y[8], y[9], y[10], y[11]);
          TS(67 + L * 32 + p * 5);
        }
        TS(11 + L * 20);
        const uint32_t t = tid_();
#pragma unroll
        for (int i = 0; i < 2; i++) lds128(&y[4 * i], ytail(wg * 2 + i) + t * 16);
        lds128(&a[28], xs + PBUF + t * 16);
        lds64(y[16], y[17], ytail(wg * 2 + (t >> 6)) + 2048 + (t & 63) * 8);
        load_own(xr, sb, L * 3 * TILE, j);
        hint_wait(hint, hint_target(L * 8 + 6));
        TS(17 + L * 20);
        {
          uint32_t m;
          do {
            m = 0;
#pragma unroll
            for (int s = 0; s < 7; s++) { ld16(&a[4 * s], sb, j * PSRC + t * 16, OFF_P + PBUF + s * 2048); m |= a[4 * s]; }
          } while (__any_sync(0xffffffffu, m & 1));
          TS(12 + L * 20);
          reduce4(a, y + 12);
        }
#pragma unroll
        for (int i = 0; i < 18; i++) xr[i] = bf2_add(xr[i], y[i]);
        TS(18 + L * 20);
        if (L == 0) {
          store_own(xr, sb, OFF_X2, j, t);
          store_stats18(xr, sb, 8192 + j * 128, t);
          hint_post(hint);
        } else {
          const uint32_t st = xs + w * 2048 + t * 16;
          bar_sync(NB_WG + wg, 128);
#pragma unroll
          for (int i = 0; i < 4; i++) stsm4(st + i * 512, xr[4 * i], xr[4 * i + 1], xr[4 * i + 2], xr[4 * i + 3]);
          stsm4(st + 2048, xr[16], xr[17], 0, 0);
          __syncwarp();
          uint8_t* op = (uint8_t*)P.out + row_off(rb, wg, t);
#pragma unroll
          for (int i = 0; i < 5; i++) {
            uint32_t v[4];
            lds128(v, st + i * 512);
            if (i < 4) *(uint4*)(op + i * 256 + j * 32 + (t & 16)) = make_uint4(v[0], v[1], v[2], v[3]);
            else if (!(t & 16)) *(uint4*)(op + 1024 + j * 16) = make_uint4(v[0], v[1], v[2], v[3]);
          }
        }
      }
      TS(13 + L * 20);
    }
    bar_sync(NB_WG + wg, 128);
    if (tid_() == 0) mbar_arrive(bar_empty(12));
  }
}

typedef CUresult (*EncodeFn)(CUtensorMap*, CUtensorMapDataType, cuuint32_t, void*, const cuuint64_t*, const cuuint64_t*, const cuuint32_t*,
                             const cuuint32_t*, CUtensorMapInterleave, CUtensorMapSwizzle, CUtensorMapL2promotion, CUtensorMapFloatOOBfill);

void encode(EncodeFn fn, CUtensorMap* m, const void* p, int rank, const cuuint64_t* dims, const cuuint64_t* str, const cuuint32_t* box) {
  const cuuint32_t es[3] = {1, 1, 1};
  fn(m, CU_TENSOR_MAP_DATA_TYPE_BFLOAT16, rank, const_cast<void*>(p), dims, str, box, es, CU_TENSOR_MAP_INTERLEAVE_NONE,
     CU_TENSOR_MAP_SWIZZLE_128B, CU_TENSOR_MAP_L2_PROMOTION_L2_256B, CU_TENSOR_MAP_FLOAT_OOB_FILL_NONE);
}

}

extern "C" void kernel_launch(void* const* d_in, const int* in_sizes, int n_in, void* d_out, int out_size) {
  (void)in_sizes; (void)n_in; (void)out_size;
  Params P;
  P.x = (const __nv_bfloat16*)d_in[0]; P.wqkv = (const __nv_bfloat16*)d_in[1]; P.wo = (const __nv_bfloat16*)d_in[2];
  P.wg = (const __nv_bfloat16*)d_in[4]; P.wu = (const __nv_bfloat16*)d_in[5]; P.wd = (const __nv_bfloat16*)d_in[6];
  P.out = (__nv_bfloat16*)d_out; P.zero = 0;
  cudaGetSymbolAddress((void**)&P.scr, g_scr);
  void* fnp = nullptr; cudaDriverEntryPointQueryResult qr;
  cudaGetDriverEntryPoint("cuTensorMapEncodeTiled", &fnp, cudaEnableDefault, &qr);
  EncodeFn fn = (EncodeFn)fnp;
  CUtensorMap mx, mg, mu, md;
  { const cuuint64_t dims[3] = {DM, SEQ / 2, 2}, str[2] = {DM * 4, DM * 2}; const cuuint32_t box[3] = {64, 64, 2}; encode(fn, &mx, P.x, 3, dims, str, box); }
  { const cuuint64_t dims[2] = {DFF, DM}, str[1] = {DFF * 2}; const cuuint32_t box[2] = {64, 64}; encode(fn, &mg, P.wg, 2, dims, str, box); encode(fn, &mu, P.wu, 2, dims, str, box); }
  { const cuuint64_t dims[2] = {DM, DFF}, str[1] = {DM * 2}; const cuuint32_t box[2] = {64, 64}; encode(fn, &md, P.wd, 2, dims, str, box); }
  cudaFuncSetAttribute(fused_kernel, cudaFuncAttributeMaxDynamicSharedMemorySize, SMEM_BYTES);
  fused_kernel<<<128, 384, SMEM_BYTES, cudaStreamPerThread>>>(mx, mg, mu, md, P);
}
```

```cpp
#include <cuda_runtime.h>
#include <cuda_bf16.h>
#include <cuda.h>
#include <stdint.h>

#define KV_LEAD 5
#define D_KV 8
#define D_WO 5
#define D_T0 6
#define PF_AHEAD 3
#define CH_LAST 4
#define MC 0
#define MAP 3
#define TIMING 0

namespace {

constexpr int SEQ = 2048, DM = 576, DFF = 4608;
constexpr uint32_t SB = 1024;
constexpr uint32_t SLOT = 16384;
constexpr uint32_t PSLOT = 13824;
constexpr uint32_t BARS = SB + 14 * SLOT;
constexpr int SMEM_BYTES = 14 * SLOT + 256 + 2560;
__host__ __device__ constexpr uint32_t slot_addr(int s) { return SB + s * SLOT; }
__host__ __device__ constexpr uint32_t bar_full(int s) { return BARS + 8 * s; }
__host__ __device__ constexpr uint32_t bar_empty(int s) { return BARS + 128 + 8 * s; }
enum { NB_ORD0 = 1, NB_ORD1 = 2, NB_WG = 3  , NB_HALO = 5  , NB_FREE = 7  , NB_PUB = 9   };
constexpr uint32_t SM_EPOCH = BARS + 120;
__host__ __device__ constexpr uint32_t ytail(uint32_t k) { return k < 3 ? slot_addr(9) + PSLOT + k * SLOT : BARS + 256; }
constexpr uint32_t KSTG = 9 * 1152;

constexpr uint32_t TILE = 36 * 2048;
constexpr uint32_t OFF_X1 = 0  , OFF_O = TILE, OFF_X2 = 2 * TILE, OFF_ST = 4 * TILE  ;
constexpr uint32_t PBUF = 7 * 2048, PSRC = 2 * PBUF + PBUF / 2;
constexpr uint32_t OFF_P = OFF_ST + 3 * 4096, OFF_HALO = OFF_P + 8 * PSRC  , OFF_HINT = OFF_HALO + 2 * 8 * 3072  ,
                   STRM = OFF_HINT + 12 * 128;
constexpr uint32_t OFF_WPACK = 32 * STRM, OFF_FLAGS = OFF_WPACK + 8 * 24 * PSLOT;
__device__ __align__(1024) uint8_t g_scr[OFF_FLAGS + (8 + 64 + 128) * 32];

__device__ __forceinline__ uint32_t smem_u32(const void* p) { return (uint32_t)__cvta_generic_to_shared(p); }
extern __shared__ __align__(1024) uint8_t smem_raw[];
__device__ __forceinline__ uint32_t win() { return MC ? (blockIdx.x & 1) << 24 : 0; }
#define SA(A, W) ".reg .u32 sa;\nadd.u32 sa, " A ", " W ";\n"
__device__ __forceinline__ void mbar_init(uint32_t bar, uint32_t cnt) { asm volatile("{\n" SA("%0", "%2") "mbarrier.init.shared::cta.b64 [sa], %1;\n}" ::"r"(bar), "r"(cnt), "r"(win())); }
__device__ __forceinline__ void mbar_expect_tx(uint32_t bar, uint32_t bytes) { asm volatile("{\n" SA("%0", "%2") "mbarrier.arrive.expect_tx.shared::cta.b64 _, [sa], %1;\n}" ::"r"(bar), "r"(bytes), "r"(win()) : "memory"); }
__device__ __forceinline__ void mbar_arrive(uint32_t bar) { asm volatile("{\n" SA("%0", "%1") "mbarrier.arrive.shared::cta.b64 _, [sa];\n}" ::"r"(bar), "r"(win()) : "memory"); }
__device__ __forceinline__ uint32_t lds32(uint32_t a) { uint32_t v; asm volatile("{\n" SA("%1", "%2") "ld.shared.u32 %0, [sa];\n}" : "=r"(v) : "r"(a), "r"(win()) : "memory"); return v; }
__device__ __forceinline__ void lds64(uint32_t& x, uint32_t& y, uint32_t a) { asm volatile("{\n" SA("%2", "%3") "ld.shared.v2.u32 {%0,%1}, [sa];\n}" : "=r"(x), "=r"(y) : "r"(a), "r"(win()) : "memory"); }
__device__ __forceinline__ void lds128(uint32_t* v, uint32_t a) {
  asm volatile("{\n" SA("%4", "%5") "ld.shared.v4.u32 {%0,%1,%2,%3}, [sa];\n}" : "=r"(v[0]), "=r"(v[1]), "=r"(v[2]), "=r"(v[3]) : "r"(a), "r"(win()) : "memory");
}
__device__ __forceinline__ void stsm4(uint32_t a, uint32_t x, uint32_t y, uint32_t z, uint32_t w) {
  asm volatile("{\n" SA("%0", "%5") "stmatrix.sync.aligned.m8n8.x4.shared.b16 [sa], {%1,%2,%3,%4};\n}" ::"r"(a), "r"(x), "r"(y), "r"(z), "r"(w), "r"(win()) : "memory");
}
__device__ __forceinline__ void ldsm4(uint32_t* v, uint32_t a) {
  asm volatile("{\n" SA("%4", "%5") "ldmatrix.sync.aligned.m8n8.x4.shared.b16 {%0,%1,%2,%3}, [sa];\n}" : "=r"(v[0]), "=r"(v[1]), "=r"(v[2]), "=r"(v[3]) : "r"(a), "r"(win()) : "memory");
}
__device__ __forceinline__ void ldsm4t(uint32_t* v, uint32_t a) {
  asm volatile("{\n" SA("%4", "%5") "ldmatrix.sync.aligned.m8n8.x4.trans.shared.b16 {%0,%1,%2,%3}, [sa];\n}" : "=r"(v[0]), "=r"(v[1]), "=r"(v[2]), "=r"(v[3]) : "r"(a), "r"(win()) : "memory");
}
__device__ __forceinline__ void sts32(uint32_t a, uint32_t x) { asm volatile("{\n" SA("%0", "%2") "st.shared.u32 [sa], %1;\n}" ::"r"(a), "r"(x), "r"(win()) : "memory"); }
__device__ __forceinline__ void sts64(uint32_t a, uint32_t x, uint32_t y) { asm volatile("{\n" SA("%0", "%3") "st.shared.v2.u32 [sa], {%1,%2};\n}" ::"r"(a), "r"(x), "r"(y), "r"(win()) : "memory"); }
__device__ __forceinline__ void sts128(uint32_t a, uint32_t x, uint32_t y, uint32_t z, uint32_t w) {
  asm volatile("{\n" SA("%0", "%5") "st.shared.v4.u32 [sa], {%1,%2,%3,%4};\n}" ::"r"(a), "r"(x), "r"(y), "r"(z), "r"(w), "r"(win()) : "memory");
}
__device__ __forceinline__ void mbar_wait(uint32_t bar, uint32_t parity) {
  asm volatile("{\n.reg .pred p;\n" SA("%0", "%2") "LAB_WAIT:\nmbarrier.try_wait.parity.shared::cta.b64 p, [sa], %1;\n@!p bra LAB_WAIT;\n}" ::"r"(bar), "r"(parity), "r"(win()) : "memory");
}
__device__ __forceinline__ void timed_wait(uint32_t bar, uint32_t par) {
  asm volatile("{\n.reg .pred p;\n.reg .u64 t0, t1;\nmov.u64 t0, %%globaltimer;\nLAB_WD:\n"
               "mbarrier.try_wait.parity.shared::cta.b64 p, [%0], %1, 100000;\n@p bra LAB_OK;\n"
               "mov.u64 t1, %%globaltimer;\nsub.u64 t1, t1, t0;\nsetp.lt.u64 p, t1, 2000000000;\n@p bra LAB_WD;\ntrap;\nLAB_OK:\n}" ::"r"(bar + win()), "r"(par) : "memory");
}
__device__ __forceinline__ void flag_wait(const unsigned* flag, unsigned target) {
  asm volatile("{\n.reg .pred p;\n.reg .u32 v;\nLAB_WAIT:\nld.acquire.gpu.global.u32 v, [%0];\nsub.u32 v, v, %1;\n"
               "setp.lt.s32 p, v, 0;\n@p nanosleep.u32 100;\n@p bra LAB_WAIT;\n}" ::"l"(flag), "r"(target) : "memory");
}
__device__ __forceinline__ void hint_post(uint8_t* p) {
  __syncwarp();
  asm volatile("{\n.reg .pred p;\nelect.sync _|p, 0xffffffff;\n@p red.relaxed.gpu.global.add.u32 [%0], 1;\n}" ::"l"(p) : "memory");
}
__device__ __forceinline__ void hint_wait(const uint8_t* p, uint32_t target) {
  asm volatile("{\n.reg .pred p;\n.reg .u32 v;\nLAB_WAIT:\nld.relaxed.gpu.global.u32 v, [%0];\nsub.u32 v, v, %1;\n"
               "setp.lt.s32 p, v, 0;\nvote.sync.any.pred p, p, 0xffffffff;\n@p bra LAB_WAIT;\n}" ::"l"(p), "r"(target) : "memory");
}
__device__ __forceinline__ void flag_signal(unsigned* flag) { asm volatile("red.release.gpu.global.add.u32 [%0], 1;" ::"l"(flag) : "memory"); }
struct Rel {
  bool on; uint32_t base;
  __device__ __forceinline__ void operator()(int s) const {
    if (on) {
      if (MC) asm volatile("{\n" SA("%0", "%1") "mbarrier.arrive.shared::cluster.b64 _, [sa];\n}" ::"r"(bar_empty(s)), "r"(base) : "memory");
      else mbar_arrive(bar_empty(s));
    }
  }
};
__device__ __forceinline__ uint32_t cta_window(uint32_t rank) { uint32_t a; asm("mapa.shared::cluster.u32 %0, %1, %2;" : "=r"(a) : "r"(0), "r"(rank)); return a; }
__device__ __forceinline__ void tma_2d_mc(uint32_t dst, const CUtensorMap* m, int c0, int c1, uint32_t bar) {
  asm volatile("cp.async.bulk.tensor.2d.shared::cluster.global.mbarrier::complete_tx::bytes.multicast::cluster [%0], [%1, {%3, %4}], [%2], %5;"
               ::"r"(dst), "l"(m), "r"(bar), "r"(c0), "r"(c1), "h"((uint16_t)3) : "memory");
}
__device__ __forceinline__ void bulk_load_mc(uint32_t dst, const void* src, uint32_t bytes, uint32_t bar) {
  asm volatile("cp.async.bulk.shared::cluster.global.mbarrier::complete_tx::bytes.multicast::cluster [%0], [%1], %2, [%3], %4;"
               ::"r"(dst), "l"(src), "r"(bytes), "r"(bar), "h"((uint16_t)3) : "memory");
}
__device__ __forceinline__ void tma_2d(uint32_t dst, const CUtensorMap* m, int c0, int c1, uint32_t bar) {
  asm volatile("cp.async.bulk.tensor.2d.shared::cluster.global.mbarrier::complete_tx::bytes [%0], [%1, {%3, %4}], [%2];"
               ::"r"(dst), "l"(m), "r"(bar), "r"(c0), "r"(c1) : "memory");
}
__device__ __forceinline__ void tma_3d(uint32_t dst, const CUtensorMap* m, int c0, int c1, int c2, uint32_t bar) {
  asm volatile("cp.async.bulk.tensor.3d.shared::cluster.global.mbarrier::complete_tx::bytes [%0], [%1, {%3, %4, %5}], [%2];"
               ::"r"(dst), "l"(m), "r"(bar), "r"(c0), "r"(c1), "r"(c2) : "memory");
}
__device__ __forceinline__ void bulk_load(uint32_t dst, const void* src, uint32_t bytes, uint32_t bar) {
  asm volatile("cp.async.bulk.shared::cluster.global.mbarrier::complete_tx::bytes [%0], [%1], %2, [%3];" ::"r"(dst), "l"(src), "r"(bytes), "r"(bar) : "memory");
}
__device__ __forceinline__ void l2_prefetch(const void* src, uint32_t bytes) { asm volatile("cp.async.bulk.prefetch.L2.global [%0], %1;" ::"l"(src), "r"(bytes) : "memory"); }
__device__ __forceinline__ void wg_fence() { asm volatile("wgmma.fence.sync.aligned;" ::: "memory"); }
__device__ __forceinline__ void wg_commit() { asm volatile("wgmma.commit_group.sync.aligned;" ::: "memory"); }
template <int N> __device__ __forceinline__ void wg_wait() { asm volatile("wgmma.wait_group.sync.aligned %0;" ::"n"(N) : "memory"); }
__device__ __forceinline__ void bar_sync(int id, int n) { asm volatile("bar.sync %0, %1;" ::"r"(id), "r"(n) : "memory"); }
__device__ __forceinline__ void bar_arrive(int id, int n) { asm volatile("bar.arrive %0, %1;" ::"r"(id), "r"(n) : "memory"); }
__device__ __forceinline__ uint32_t pack_bf16(float lo, float hi) { uint32_t r; asm("cvt.rn.bf16x2.f32 %0, %1, %2;" : "=r"(r) : "f"(hi), "f"(lo)); return r; }
__device__ __forceinline__ float bf_lo(uint32_t w) { return __uint_as_float(w << 16); }
__device__ __forceinline__ float bf_hi(uint32_t w) { return __uint_as_float(w & 0xffff0000u); }
__device__ __forceinline__ float bf_round(float x) { return bf_lo(pack_bf16(x, 0.f)); }
__device__ __forceinline__ uint32_t bf2_sub(uint32_t a, uint32_t b) { uint32_t r; asm("sub.rn.bf16x2 %0, %1, %2;" : "=r"(r) : "r"(a), "r"(b)); return r; }
__device__ __forceinline__ uint32_t bf2_add(uint32_t a, uint32_t b) { uint32_t r; asm("add.rn.bf16x2 %0, %1, %2;" : "=r"(r) : "r"(a), "r"(b)); return r; }
#define GADDR(B, O, I) "cvt.u64.u32 ad, " O ";\nadd.u64 ad, ad, " B ";\nadd.u64 ad, ad, " I ";\n"
__device__ __forceinline__ void ld16(uint32_t* v, const uint8_t* ub, uint32_t off, uint32_t imm) {
  asm volatile("{\n.reg .b128 z;\n.reg .b64 x, y, ad;\n" GADDR("%4", "%5", "%6") "ld.relaxed.gpu.global.b128 z, [ad];\n"
               "mov.b128 {x, y}, z;\nmov.b64 {%0,%1}, x;\nmov.b64 {%2,%3}, y;\n}"
               : "=r"(v[0]), "=r"(v[1]), "=r"(v[2]), "=r"(v[3]) : "l"(ub), "r"(off), "l"((uint64_t)imm) : "memory");
}
__device__ __forceinline__ void ld8(uint32_t* v, const uint8_t* ub, uint32_t off, uint32_t imm) {
  asm volatile("{\n.reg .b64 x, ad;\n" GADDR("%2", "%3", "%4") "ld.relaxed.gpu.global.b64 x, [ad];\nmov.b64 {%0,%1}, x;\n}"
               : "=r"(v[0]), "=r"(v[1]) : "l"(ub), "r"(off), "l"((uint64_t)imm) : "memory");
}
__device__ __forceinline__ void st16(uint8_t* ub, uint32_t off, uint32_t imm, uint32_t a, uint32_t b, uint32_t c, uint32_t d) {
  asm volatile("{\n.reg .b128 z;\n.reg .b64 x, y, ad;\n" GADDR("%0", "%1", "%2") "mov.b64 x, {%3,%4};\nmov.b64 y, {%5,%6};\nmov.b128 z, {x, y};\n"
               "st.relaxed.gpu.global.b128 [ad], z;\n}" ::"l"(ub), "r"(off), "l"((uint64_t)imm), "r"(a), "r"(b), "r"(c), "r"(d) : "memory");
}
__device__ __forceinline__ void st8(uint8_t* ub, uint32_t off, uint32_t imm, uint32_t a, uint32_t b) {
  asm volatile("{\n.reg .b64 x, ad;\n" GADDR("%0", "%1", "%2") "mov.b64 x, {%3,%4};\nst.relaxed.gpu.global.b64 [ad], x;\n}"
               ::"l"(ub), "r"(off), "l"((uint64_t)imm), "r"(a), "r"(b) : "memory");
}
__device__ __forceinline__ void send16(uint8_t* ub, uint32_t off, uint32_t imm, uint32_t sm, int i, int j, uint32_t a, uint32_t b, uint32_t c, uint32_t d) {
  asm volatile("{\n.reg .pred p, q, e;\n.reg .b128 z;\n.reg .b64 x, y, ad;\n" SA("%3", "%10") GADDR("%0", "%1", "%2")
               "setp.lt.s32 p, %4, %5;\nsetp.gt.s32 q, %4, %5;\nsetp.eq.s32 e, %4, %5;\nmov.b64 x, {%6,%7};\nmov.b64 y, {%8,%9};\nmov.b128 z, {x, y};\n"
               "@p st.relaxed.gpu.global.b128 [ad+-2048], z;\n@q st.relaxed.gpu.global.b128 [ad], z;\n@e st.shared.v4.u32 [sa], {%6,%7,%8,%9};\n}"
               ::"l"(ub), "r"(off), "l"((uint64_t)imm), "r"(sm), "r"(i), "r"(j), "r"(a), "r"(b), "r"(c), "r"(d), "r"(win()) : "memory");
}
__device__ __forceinline__ void send8(uint8_t* ub, uint32_t off, uint32_t imm, uint32_t sm, int i, int j, uint32_t a, uint32_t b) {
  asm volatile("{\n.reg .pred p, q, e;\n.reg .b64 x, ad;\n" SA("%3", "%8") GADDR("%0", "%1", "%2")
               "setp.lt.s32 p, %4, %5;\nsetp.gt.s32 q, %4, %5;\nsetp.eq.s32 e, %4, %5;\nmov.b64 x, {%6,%7};\n"
               "@p st.relaxed.gpu.global.b64 [ad+-1024], x;\n@q st.relaxed.gpu.global.b64 [ad], x;\n@e st.shared.v2.u32 [sa], {%6,%7};\n}"
               ::"l"(ub), "r"(off), "l"((uint64_t)imm), "r"(sm), "r"(i), "r"(j), "r"(a), "r"(b), "r"(win()) : "memory");
}
__device__ __forceinline__ uint4 ldg_line(const void* p) {
  uint4 v; asm volatile("ld.global.nc.L2::128B.v4.u32 {%0,%1,%2,%3}, [%4];" : "=r"(v.x), "=r"(v.y), "=r"(v.z), "=r"(v.w) : "l"(p)); return v;
}
__device__ __forceinline__ void stg4(void* ub, uint32_t off, uint32_t imm, uint32_t v) {
  asm volatile("{\n.reg .b64 ad;\n" GADDR("%0", "%1", "%2") "st.global.u32 [ad], %3;\n}" ::"l"(ub), "r"(off), "l"((uint64_t)imm), "r"(v) : "memory");
}
__device__ __forceinline__ uint32_t tid_() { uint32_t t; asm volatile("mov.u32 %0, %%tid.x;" : "=r"(t)); return t & 127; }
__device__ __forceinline__ uint32_t nz(uint32_t w) { return max(w, 1u); }
__device__ __forceinline__ void mma16816(float (&c)[4], uint32_t a0, uint32_t a1, uint32_t a2, uint32_t a3, uint32_t b0, uint32_t b1) {
  asm("mma.sync.aligned.m16n8k16.row.col.f32.bf16.bf16.f32 {%0,%1,%2,%3}, {%4,%5,%6,%7}, {%8,%9}, {%0,%1,%2,%3};"
               : "+f"(c[0]), "+f"(c[1]), "+f"(c[2]), "+f"(c[3]) : "r"(a0), "r"(a1), "r"(a2), "r"(a3), "r"(b0), "r"(b1));
}
__device__ __forceinline__ void mma1688(float (&c)[4], uint32_t a0, uint32_t a1, uint32_t b0) {
  asm("mma.sync.aligned.m16n8k8.row.col.f32.bf16.bf16.f32 {%0,%1,%2,%3}, {%4,%5}, {%6}, {%0,%1,%2,%3};"
               : "+f"(c[0]), "+f"(c[1]), "+f"(c[2]), "+f"(c[3]) : "r"(a0), "r"(a1), "r"(b0));
}
__device__ __forceinline__ float ex2(float x) { float r; asm("ex2.approx.ftz.f32 %0, %1;" : "=f"(r) : "f"(x)); return r; }
__device__ __forceinline__ float quad_sum(float v) { v += __shfl_xor_sync(0xffffffffu, v, 1); v += __shfl_xor_sync(0xffffffffu, v, 2); return v; }
__device__ __forceinline__ float quad_max(float v) { v = fmaxf(v, __shfl_xor_sync(0xffffffffu, v, 1)); v = fmaxf(v, __shfl_xor_sync(0xffffffffu, v, 2)); return v; }

__device__ __forceinline__ void wgmma_rs_n64(float (&d)[32], uint32_t a0, uint32_t a1, uint32_t a2, uint32_t a3, uint64_t desc, int scale_d) {
  asm volatile("{\n.reg .pred p;\nsetp.ne.b32 p, %37, 0;\n"
    "wgmma.mma_async.sync.aligned.m64n64k16.f32.bf16.bf16 "
    "{%0, %1, %2, %3, %4, %5, %6, %7, %8, %9, %10, %11, %12, %13, %14, %15, %16, %17, %18, %19, %20, %21, %22, %23, %24, %25, %26, %27, %28, %29, %30, %31}, "
    "{%32, %33, %34, %35}, %36, p, 1, 1, 1;\n}\n"
    : "+f"(d[0]), "+f"(d[1]), "+f"(d[2]), "+f"(d[3]), "+f"(d[4]), "+f"(d[5]), "+f"(d[6]), "+f"(d[7]), "+f"(d[8]), "+f"(d[9]), "+f"(d[10]), "+f"(d[11]), "+f"(d[12]), "+f"(d[13]), "+f"(d[14]), "+f"(d[15]), "+f"(d[16]), "+f"(d[17]), "+f"(d[18]), "+f"(d[19]), "+f"(d[20]), "+f"(d[21]), "+f"(d[22]), "+f"(d[23]), "+f"(d[24]), "+f"(d[25]), "+f"(d[26]), "+f"(d[27]), "+f"(d[28]), "+f"(d[29]), "+f"(d[30]), "+f"(d[31])
    : "r"(a0), "r"(a1), "r"(a2), "r"(a3), "l"(desc), "r"(scale_d));
}

__device__ __forceinline__ void wgmma_rs_n72(float (&d)[36], uint32_t a0, uint32_t a1, uint32_t a2, uint32_t a3, uint64_t desc, int scale_d) {
  asm volatile("{\n.reg .pred p;\nsetp.ne.b32 p, %41, 0;\n"
    "wgmma.mma_async.sync.aligned.m64n72k16.f32.bf16.bf16 "
    "{%0, %1, %2, %3, %4, %5, %6, %7, %8, %9, %10, %11, %12, %13, %14, %15, %16, %17, %18, %19, %20, %21, %22, %23, %24, %25, %26, %27, %28, %29, %30, %31, %32, %33, %34, %35}, "
    "{%36, %37, %38, %39}, %40, p, 1, 1, 1;\n}\n"
    : "+f"(d[0]), "+f"(d[1]), "+f"(d[2]), "+f"(d[3]), "+f"(d[4]), "+f"(d[5]), "+f"(d[6]), "+f"(d[7]), "+f"(d[8]), "+f"(d[9]), "+f"(d[10]), "+f"(d[11]), "+f"(d[12]), "+f"(d[13]), "+f"(d[14]), "+f"(d[15]), "+f"(d[16]), "+f"(d[17]), "+f"(d[18]), "+f"(d[19]), "+f"(d[20]), "+f"(d[21]), "+f"(d[22]), "+f"(d[23]), "+f"(d[24]), "+f"(d[25]), "+f"(d[26]), "+f"(d[27]), "+f"(d[28]), "+f"(d[29]), "+f"(d[30]), "+f"(d[31]), "+f"(d[32]), "+f"(d[33]), "+f"(d[34]), "+f"(d[35])
    : "r"(a0), "r"(a1), "r"(a2), "r"(a3), "l"(desc), "r"(scale_d));
}

__device__ __forceinline__ void wgmma_rs_n128(float (&d)[64], uint32_t a0, uint32_t a1, uint32_t a2, uint32_t a3, uint64_t desc, int scale_d) {
  asm volatile("{\n.reg .pred p;\nsetp.ne.b32 p, %69, 0;\n"
    "wgmma.mma_async.sync.aligned.m64n128k16.f32.bf16.bf16 "
    "{%0, %1, %2, %3, %4, %5, %6, %7, %8, %9, %10, %11, %12, %13, %14, %15, %16, %17, %18, %19, %20, %21, %22, %23, %24, %25, %26, %27, %28, %29, %30, %31, %32, %33, %34, %35, %36, %37, %38, %39, %40, %41, %42, %43, %44, %45, %46, %47, %48, %49, %50, %51, %52, %53, %54, %55, %56, %57, %58, %59, %60, %61, %62, %63}, "
    "{%64, %65, %66, %67}, %68, p, 1, 1, 1;\n}\n"
    : "+f"(d[0]), "+f"(d[1]), "+f"(d[2]), "+f"(d[3]), "+f"(d[4]), "+f"(d[5]), "+f"(d[6]), "+f"(d[7]), "+f"(d[8]), "+f"(d[9]), "+f"(d[10]), "+f"(d[11]), "+f"(d[12]), "+f"(d[13]), "+f"(d[14]), "+f"(d[15]), "+f"(d[16]), "+f"(d[17]), "+f"(d[18]), "+f"(d[19]), "+f"(d[20]), "+f"(d[21]), "+f"(d[22]), "+f"(d[23]), "+f"(d[24]), "+f"(d[25]), "+f"(d[26]), "+f"(d[27]), "+f"(d[28]), "+f"(d[29]), "+f"(d[30]), "+f"(d[31]), "+f"(d[32]), "+f"(d[33]), "+f"(d[34]), "+f"(d[35]), "+f"(d[36]), "+f"(d[37]), "+f"(d[38]), "+f"(d[39]), "+f"(d[40]), "+f"(d[41]), "+f"(d[42]), "+f"(d[43]), "+f"(d[44]), "+f"(d[45]), "+f"(d[46]), "+f"(d[47]), "+f"(d[48]), "+f"(d[49]), "+f"(d[50]), "+f"(d[51]), "+f"(d[52]), "+f"(d[53]), "+f"(d[54]), "+f"(d[55]), "+f"(d[56]), "+f"(d[57]), "+f"(d[58]), "+f"(d[59]), "+f"(d[60]), "+f"(d[61]), "+f"(d[62]), "+f"(d[63])
    : "r"(a0), "r"(a1), "r"(a2), "r"(a3), "l"(desc), "r"(scale_d));
}

__device__ __forceinline__ void wgmma_rs_n144(float (&d)[72], uint32_t a0, uint32_t a1, uint32_t a2, uint32_t a3, uint64_t desc, int scale_d) {
  asm volatile("{\n.reg .pred p;\nsetp.ne.b32 p, %77, 0;\n"
    "wgmma.mma_async.sync.aligned.m64n144k16.f32.bf16.bf16 "
    "{%0, %1, %2, %3, %4, %5, %6, %7, %8, %9, %10, %11, %12, %13, %14, %15, %16, %17, %18, %19, %20, %21, %22, %23, %24, %25, %26, %27, %28, %29, %30, %31, %32, %33, %34, %35, %36, %37, %38, %39, %40, %41, %42, %43, %44, %45, %46, %47, %48, %49, %50, %51, %52, %53, %54, %55, %56, %57, %58, %59, %60, %61, %62, %63, %64, %65, %66, %67, %68, %69, %70, %71}, "
    "{%72, %73, %74, %75}, %76, p, 1, 1, 1;\n}\n"
    : "+f"(d[0]), "+f"(d[1]), "+f"(d[2]), "+f"(d[3]), "+f"(d[4]), "+f"(d[5]), "+f"(d[6]), "+f"(d[7]), "+f"(d[8]), "+f"(d[9]), "+f"(d[10]), "+f"(d[11]), "+f"(d[12]), "+f"(d[13]), "+f"(d[14]), "+f"(d[15]), "+f"(d[16]), "+f"(d[17]), "+f"(d[18]), "+f"(d[19]), "+f"(d[20]), "+f"(d[21]), "+f"(d[22]), "+f"(d[23]), "+f"(d[24]), "+f"(d[25]), "+f"(d[26]), "+f"(d[27]), "+f"(d[28]), "+f"(d[29]), "+f"(d[30]), "+f"(d[31]), "+f"(d[32]), "+f"(d[33]), "+f"(d[34]), "+f"(d[35]), "+f"(d[36]), "+f"(d[37]), "+f"(d[38]), "+f"(d[39]), "+f"(d[40]), "+f"(d[41]), "+f"(d[42]), "+f"(d[43]), "+f"(d[44]), "+f"(d[45]), "+f"(d[46]), "+f"(d[47]), "+f"(d[48]), "+f"(d[49]), "+f"(d[50]), "+f"(d[51]), "+f"(d[52]), "+f"(d[53]), "+f"(d[54]), "+f"(d[55]), "+f"(d[56]), "+f"(d[57]), "+f"(d[58]), "+f"(d[59]), "+f"(d[60]), "+f"(d[61]), "+f"(d[62]), "+f"(d[63]), "+f"(d[64]), "+f"(d[65]), "+f"(d[66]), "+f"(d[67]), "+f"(d[68]), "+f"(d[69]), "+f"(d[70]), "+f"(d[71])
    : "r"(a0), "r"(a1), "r"(a2), "r"(a3), "l"(desc), "r"(scale_d));
}

template <int N> struct WG;
template <> struct WG<64>  { static __device__ __forceinline__ void f(float (&d)[32], const uint32_t* a, uint64_t ds, int s) { wgmma_rs_n64(d, a[0], a[1], a[2], a[3], ds, s); } };
template <> struct WG<72>  { static __device__ __forceinline__ void f(float (&d)[36], const uint32_t* a, uint64_t ds, int s) { wgmma_rs_n72(d, a[0], a[1], a[2], a[3], ds, s); } };
template <> struct WG<128> { static __device__ __forceinline__ void f(float (&d)[64], const uint32_t* a, uint64_t ds, int s) { wgmma_rs_n128(d, a[0], a[1], a[2], a[3], ds, s); } };
template <> struct WG<144> { static __device__ __forceinline__ void f(float (&d)[72], const uint32_t* a, uint64_t ds, int s) { wgmma_rs_n144(d, a[0], a[1], a[2], a[3], ds, s); } };

constexpr uint64_t DESC_SW128 = ((uint64_t)(8192 >> 4) << 16) | ((uint64_t)(1024 >> 4) << 32) | (1ull << 62);
constexpr uint64_t DESC_KV = ((uint64_t)(128 >> 4) << 16) | ((uint64_t)(768 >> 4) << 32);
constexpr uint64_t DESC_Q = ((uint64_t)(128 >> 4) << 16) | ((uint64_t)(1536 >> 4) << 32);

template <int V> struct IntC { static constexpr int value = V; };
enum { PS_KV, PS_Q, PS_WO, PS_FF };
template <int PS> __host__ __device__ constexpr int pass_slot(int i) {
  return PS == PS_KV ? (i < 3 ? 9 + i : i - 3) : PS == PS_WO ? 6 + i : i;
}

__device__ __forceinline__ void load_frag(uint32_t (&a)[144], int i, const uint8_t* sb, uint32_t uo, uint32_t t) {
  if (i < 32) ld16(&a[4 * i], sb, uo + t * 16, i * 2048);
  else { ld8(&a[4 * i], sb, uo + t * 8, i * 2048); ld8(&a[4 * i + 2], sb, uo + t * 8, i * 2048 + 1024); }
}
__device__ __forceinline__ void store_own(const uint32_t (&y)[18], uint8_t* sb, uint32_t uo, int j, uint32_t t) {
  t += j * 128;
#pragma unroll
  for (int i = 0; i < 4; i++) st16(sb, uo + t * 16, i * 16384, nz(y[4 * i]), y[4 * i + 1], y[4 * i + 2], y[4 * i + 3]);
  st8(sb, uo + t * 8, 65536, nz(y[16]), y[17]);
}
__device__ __forceinline__ void load_own(uint32_t* y, const uint8_t* sb, uint32_t uo, int j) {
  const uint32_t t = tid_() + j * 128;
#pragma unroll
  for (int i = 0; i < 4; i++) ld16(&y[4 * i], sb, uo + t * 16, i * 16384);
  ld8(&y[16], sb, uo + t * 8, 65536);
}

template <int N, int PS, int KPS, int KSTEP, int CHK, bool SUB, bool HREL = false>
__device__ __forceinline__ void mma_pass(float (&acc)[N / 2], uint32_t (&a)[144], uint64_t desc, uint32_t par, const Rel& rel, int bar_id,
                                         const uint8_t* sb = nullptr, uint32_t uo = 0, uint32_t flag = 0, uint32_t m0 = 0, uint32_t m1 = 0, uint32_t park = 0) {
  constexpr int NS = 36 / KPS;
  auto check = [&](int s) {
    while (true) {
      uint32_t m = a[4 * s * KPS];
#pragma unroll
      for (int i = s * KPS; i < (s + 1) * KPS; i++) m = min(m, i < 32 ? a[4 * i] : min(a[4 * i], a[4 * i + 2]));
      if (!__any_sync(0xffffffffu, (m | flag) == 0)) break;
      const uint32_t t = tid_();
#pragma unroll
      for (int i = s * KPS; i < (s + 1) * KPS; i++) load_frag(a, i, sb, uo, t);
    }
  };
#pragma unroll
  for (int s = 0; s < NS; s++) {
    const int sl = pass_slot<PS>(s);
    if (CHK) {
      check(s);
      if (s + CHK < NS && !flag) {
        const uint32_t t = tid_();
#pragma unroll
        for (int i = (s + CHK) * KPS; i < (s + CHK + 1) * KPS; i++) load_frag(a, i, sb, uo, t);
      }
    }
    if (SUB) {
#pragma unroll
      for (int i = s * KPS * 4; i < (s + 1) * KPS * 4; i += 2) { a[i] = bf2_sub(a[i], m0); a[i + 1] = bf2_sub(a[i + 1], m1); }
    }
    if (PS == PS_KV && s == 0) sts128(park + tid_() * 16, a[0], a[1], a[2], a[3]);
    mbar_wait(bar_full(sl), sl < 9 ? par : par ^ 1);
    wg_fence();
#pragma unroll
    for (int kk = 0; kk < KPS; kk++)
      WG<N>::f(acc, &a[(s * KPS + kk) * 4], desc + ((slot_addr(sl) + kk * KSTEP) >> 4), (s | kk) ? 1 : 0);
    wg_commit();
    if (s == (PS == PS_KV ? KV_LEAD : NS - 1) && bar_id >= 0) bar_arrive(bar_id, 256);
    if (s > 0) {
      wg_wait<1>();
      if (!(PS == PS_WO && s > 3)) rel(pass_slot<PS>(s - 1));
    }
    if (HREL && s == 3 && flag) {
#pragma unroll
      for (int i = 0; i < 12; i++) ld16(&a[4 * i], sb, uo, (i >> 2) * TILE + (i & 3) * 2048);
    }
  }
  wg_wait<0>();
  if (PS != PS_WO) rel(pass_slot<PS>(NS - 1));
}

template <int NF> __device__ __forceinline__ void load_frags(uint32_t (&a)[144], const uint8_t* sb, uint32_t uo, uint32_t t) {
#pragma unroll
  for (int i = 0; i < NF; i++) load_frag(a, i, sb, uo, t);
}
__device__ __forceinline__ void ln_scalars(float s1, float s2, uint32_t& m, float& var, uint32_t zero) {
  const float mean = s1 * (1.f / DM);
  var = s2 * (1.f / DM) - mean * mean;
  m = pack_bf16(mean, mean) ^ (__float_as_uint(var) & zero);
}
__device__ __forceinline__ float ln_rstd(float var, float after, uint32_t zero) {
  var = __uint_as_float(__float_as_uint(var) ^ (__float_as_uint(after) & zero));
  float sd, r;
  asm("sqrt.approx.ftz.f32 %0, %1;" : "=f"(sd) : "f"(bf_round(bf_round(fmaxf(var, 0.f)) + 1e-5f)));
  asm("rcp.approx.ftz.f32 %0, %1;" : "=f"(r) : "f"(bf_round(sd)));
  return r;
}
template <int NF> __device__ __forceinline__ void gather_ln(uint32_t (&a)[144], const uint8_t* sb, uint32_t uo, uint32_t sto,
                                          uint32_t& m0, uint32_t& m1, float& r0, float& r1, uint32_t zero) {
  uint32_t u[32];
  const uint32_t t = tid_(), so = sto + (t >> 5) * 1024 + (t & 28) * 4;
#pragma unroll
  for (int i = 0; i < 8; i++) ld16(&u[4 * i], sb, so, OFF_ST + i * 128);
  load_frags<NF>(a, sb, uo, t);
  while (true) {
    uint32_t m = u[0];
#pragma unroll
    for (int i = 1; i < 8; i++) m = min(m, u[4 * i]);
    if (!__any_sync(0xffffffffu, m == 0)) break;
#pragma unroll
    for (int i = 0; i < 8; i++) ld16(&u[4 * i], sb, so, OFF_ST + i * 128);
  }
  float v[4];
#pragma unroll
  for (int k = 0; k < 4; k++)
    v[k] = ((__uint_as_float(u[k]) + __uint_as_float(u[4 + k])) + (__uint_as_float(u[8 + k]) + __uint_as_float(u[12 + k]))) +
           ((__uint_as_float(u[16 + k]) + __uint_as_float(u[20 + k])) + (__uint_as_float(u[24 + k]) + __uint_as_float(u[28 + k])));
  ln_scalars(v[1], v[0], m0, r0, zero); ln_scalars(v[3], v[2], m1, r1, zero);
}
struct Stats {
  float s[4] = {0, 0, 0, 0}, d0[4] = {0, 0, 0, 0}, d1[4] = {0, 0, 0, 0};
  __device__ __forceinline__ void add16(const uint32_t* f) {
    mma16816(s, f[0], f[1], f[2], f[3], 0x3f803f80u, 0x3f803f80u);
    mma16816(d0, f[0], f[1], f[2], f[3], f[0], f[2]);
    mma16816(d1, f[0], f[1], f[2], f[3], f[1], f[3]);
  }
  __device__ __forceinline__ float sq0(int g) const { return (g & 1) ? d0[1] : d0[0]; }
  __device__ __forceinline__ float sq1(int g) const { return (g & 1) ? d1[3] : d1[2]; }
};
struct RowStats {
  float s[4] = {0, 0, 0, 0}, u[4] = {0, 0, 0, 0};
  template <int N> __device__ __forceinline__ void add(const uint32_t* y) {
#pragma unroll
    for (int i = 0; i < N; i++) {
      const float lo = bf_lo(y[i]), hi = bf_hi(y[i]);
      const int r = (i & 1) * 2;
      s[r] = fmaf(lo, lo, s[r]); u[r] = fmaf(hi, hi, u[r]); s[r + 1] += lo; u[r + 1] += hi;
    }
  }
  __device__ __forceinline__ uint32_t fold() {
    uint32_t x = 0;
#pragma unroll
    for (int i = 0; i < 4; i++) { s[i] += u[i]; u[i] = 0; x |= __float_as_uint(s[i]); }
    return x;
  }
  __device__ __forceinline__ void store(uint8_t* sb, uint32_t sto, uint32_t t) {
    fold();
#pragma unroll
    for (int i = 0; i < 4; i++) s[i] += __shfl_xor_sync(0xffffffffu, s[i], 1);
#pragma unroll
    for (int i = 0; i < 4; i++) s[i] += __shfl_xor_sync(0xffffffffu, s[i], 2);
    if ((t & 3) == 0) st16(sb, sto + (t >> 5) * 1024 + (t & 28) * 4, OFF_ST, __float_as_uint(s[0]) | 1u, __float_as_uint(s[1]), __float_as_uint(s[2]), __float_as_uint(s[3]));
  }
};
__device__ __forceinline__ void reduce4(const uint32_t* f, uint32_t* y) {
#pragma unroll
  for (int i = 0; i < 4; i++) {
    float lo = bf_lo(f[i]), hi = bf_hi(f[i]);
#pragma unroll
    for (int s = 1; s < 8; s++) { lo += bf_lo(f[4 * s + i]); hi += bf_hi(f[4 * s + i]); }
    y[i] = pack_bf16(lo, hi);
  }
}

#define TS(i) do {} while (0)
#define TSP(i) do {} while (0)
#define TSH(i) do {} while (0)

__host__ __device__ constexpr int role_j(int c) {
  return MAP == 0 ? (MC ? (c >> 1) & 7 : c & 7) : MAP == 1 ? c >> 4 : MAP == 2 ? ((c >> 6) << 2) | ((c >> 1) & 3)
       : MAP == 3 ? ((c >> 5) << 1) | ((c >> 2) & 1) : ((c >> 3) & 3) * 2 + ((c >> 2) & 1);
}
__host__ __device__ constexpr int role_rb(int c) {
  return MAP == 0 ? (MC ? (c >> 4) * 2 + (c & 1) : c >> 3) : MAP == 1 ? c & 15 : MAP == 2 ? ((c >> 3) & 7) * 2 + (c & 1)
       : MAP == 3 ? ((c >> 3) & 3) * 4 + (c & 3) : (c >> 5) * 4 + (c & 3);
}

__device__ __forceinline__ uint32_t row_off(int rb, int wg, uint32_t t) { return (rb * 128 + wg + ((t >> 5) * 16 + (t & 15)) * 2) * (2 * DM); }

__device__ __forceinline__ const __nv_bfloat16* wo_src(const __nv_bfloat16* wo, int k, int u, int j) {
  const int ko = k < 512 ? ((k >> 4) & 7) * 72 + (k >> 7) * 16 + (k & 15) : ((k >> 3) & 7) * 72 + 64 + (k & 7);
  return wo + ko * 576 + (u < 8 ? (u >> 1) * 128 + j * 16 + (u & 1) * 8 : 512 + j * 8);
}

struct Params {
  const __nv_bfloat16 *x, *wqkv, *wo, *wg, *wu, *wd;
  __nv_bfloat16* out;
  uint8_t* scr;
  uint8_t* times;
  unsigned zero;
};

__device__ __forceinline__ void tma_prefetch(const CUtensorMap* m, int c0, int c1) {
  asm volatile("cp.async.bulk.prefetch.tensor.2d.L2.global [%0, {%1, %2}];" ::"l"(m), "r"(c0), "r"(c1) : "memory");
}
__device__ __forceinline__ void fill_packed(int sl, uint32_t par, const uint8_t* src, uint32_t rank, uint32_t own) {
  mbar_wait(bar_empty(sl), par);
  mbar_expect_tx(bar_full(sl), PSLOT);
  if (MC) bulk_load_mc(own + slot_addr(sl) + rank * (PSLOT / 2), src + rank * (PSLOT / 2), PSLOT / 2, own + bar_full(sl));
  else bulk_load(slot_addr(sl), src, PSLOT, bar_full(sl));
}

__global__ void __launch_bounds__(384, 1)
fused_kernel(const __grid_constant__ CUtensorMap map_x, const __grid_constant__ CUtensorMap map_wg,
             const __grid_constant__ CUtensorMap map_wu, const __grid_constant__ CUtensorMap map_wd, const Params P) {
  const int wg = __shfl_sync(0xffffffffu, threadIdx.x >> 7, 0);
  const int cta = blockIdx.x, rank = MC ? cta & 1 : 0, j = role_j(cta), rb = role_rb(cta);
  const uint32_t own = win();
  unsigned* const flags = (unsigned*)(P.scr + OFF_FLAGS);
  if (__shfl_sync(0xffffffffu, threadIdx.x >> 5, 0) == 11) {
    if (threadIdx.x == 352) {
#pragma unroll
      for (int i = 0; i < 14; i++) { mbar_init(bar_full(i), 1); mbar_init(bar_empty(i), MC && i < 12 ? 4 : 2); }
      mbar_init(bar_full(14), 1); mbar_init(bar_empty(14), 1);
      asm volatile("fence.mbarrier_init.release.cluster;" ::: "memory");
      if (smem_u32(smem_raw) != own + SB) asm volatile("trap;");
    }
    __syncwarp();
    bar_arrive(0, 384);
    if (MC) asm volatile("barrier.cluster.arrive.relaxed.aligned;" ::: "memory");
    if (threadIdx.x == 352) {
#pragma unroll 1
      for (int c = 0; c < 9; c++) {
        mbar_expect_tx(bar_full(c), SLOT);
        tma_3d(own + slot_addr(c), &map_x, c * 64, rb * 64, 0, own + bar_full(c));
      }
    }
  } else {
    const bool on = threadIdx.x < 324;
    const int k = rb * 36 + (on ? threadIdx.x / 36 : 0) * 4 + (threadIdx.x & 3), u = (threadIdx.x % 36) >> 2;
    const uint4* s = (const uint4*)(P.wqkv + k * 1728 + j * 72 + u * 8);
    const uint4 vk = ldg_line(s + 72), vv = ldg_line(s + 144);
    const unsigned ep0 = *(volatile unsigned*)&flags[(72 + cta) * 8];
    if (MC) asm volatile("barrier.cluster.arrive.relaxed.aligned;" ::: "memory");
    bar_sync(0, 384);
    uint8_t* d = P.scr + OFF_WPACK + j * 24 * PSLOT;
    if (on) {
      const uint32_t dkv = (k / 48) * PSLOT + u * 768 + (k % 48) * 16;
      st16(d, dkv, 0, vk.x, vk.y, vk.z, vk.w);
      st16(d, dkv, 9 * 768, vv.x, vv.y, vv.z, vv.w);
    }
    asm volatile("fence.proxy.async.global;" ::: "memory");
    bar_arrive(NB_PUB + 3, 384);
    if (threadIdx.x == 351) sts32(SM_EPOCH, ep0);
    if (wg == 2) bar_sync(NB_PUB + 1, 96);
  }
  __syncwarp();
  if (MC) asm volatile("barrier.cluster.wait.acquire.aligned;" ::: "memory");

  if (wg == 2) {
    asm volatile("setmaxnreg.dec.sync.aligned.u32 24;");
    const int pw = __shfl_sync(0xffffffffu, (threadIdx.x >> 5) & 3, 0), lane = threadIdx.x & 31;
    auto tile_col = [](int t, int j) { return t < 9 ? j * 576 + t * 64 : t == 9 ? 512 : (t - 10) * 128; };
    auto prefetch_tile = [&](int t) {
#pragma unroll 1
      for (int b = rb; b < 18; b += 16) {
        const int h = b & 1, k = b >> 1;
        if (t < 9) tma_prefetch(h ? &map_wu : &map_wg, tile_col(t, j), k * 64);
        else if (t != 9 || !h) tma_prefetch(&map_wd, tile_col(t, j) + h * 64, j * 576 + k * 64);
      }
    };
    if (pw == 0) {
      if (lane == 0) {
        flag_wait(&flags[j * 8], (lds32(SM_EPOCH) + 1) * 16);
        TSP(7);
        asm volatile("fence.proxy.async.global;" ::: "memory");
        const uint8_t* wp = P.scr + OFF_WPACK + j * 24 * PSLOT;
#pragma unroll 1
        for (int s = 0; s < 3; s++) fill_packed(9 + s, 1, wp + s * PSLOT, rank, own);
#pragma unroll 1
        for (int L = 0; L < 2; L++) {
#pragma unroll 1
          for (int s = 0; s < 21; s++) {
            if (s == 9 && L == 0) { flag_wait(&flags[(56 + j) * 8], (lds32(SM_EPOCH) + 1) * 16); asm volatile("fence.proxy.async.global;" ::: "memory"); }
            fill_packed(s < 9 ? s : s - 9, s >= 9 && s < 18, wp + (s + 3) * PSLOT, rank, own);
          }
#pragma unroll 1
          for (int t = 0; t < 14; t++) {
            const int p = t - 9;
            const CUtensorMap* ma = p < 0 ? &map_wg : &map_wd;
            const CUtensorMap* mb = p < 0 ? &map_wu : &map_wd;
            const int ca = tile_col(t, j), cb = p < 0 ? ca : ca + 64, r0 = p < 0 ? 0 : j * 576;
            if (L * 14 + t + PF_AHEAD < 28) prefetch_tile((t + PF_AHEAD) % 14);
#pragma unroll 1
            for (int k = 0; k < 9; k++) {
              mbar_wait(bar_empty(k), t & 1);
              mbar_expect_tx(bar_full(k), p == 0 ? 8192 : SLOT);
              const int r = r0 + (p < 0 || k == 8 ? k : k < 3 ? k + 5 : k - 3) * 64;
              if (MC) {
                if (p != 0) tma_2d_mc(own + slot_addr(k) + rank * 8192, rank ? mb : ma, rank ? cb : ca, r, own + bar_full(k));
                else if ((k & 1) == rank) tma_2d_mc(own + slot_addr(k), ma, ca, r, own + bar_full(k));
              } else {
                tma_2d(slot_addr(k), ma, ca, r, bar_full(k));
                if (p != 0) tma_2d(slot_addr(k) + 8192, mb, cb, r, bar_full(k));
              }
            }
            if (p == 1 && L == 0) {
              l2_prefetch(wp + rb * (24 * PSLOT / 16), 24 * PSLOT / 16);
#pragma unroll 1
              for (int s = 0; s < 3; s++) fill_packed(9 + s, 1, wp + s * PSLOT, rank, own);
            }
          }
        }
        flags[(72 + cta) * 8] = lds32(SM_EPOCH) + 1;
      }
    } else if (pw < 3) {
      const int hw = pw - 1;
      const uint32_t ep = __shfl_sync(0xffffffffu, lds32(SM_EPOCH), 0);
      uint8_t* const sb = P.scr + (rb * 2 + hw) * STRM;
      const uint32_t xs = slot_addr(12) + hw * SLOT, fb = bar_full(12) + hw * 8;
      uint32_t hph = 0;
#pragma unroll 1
      for (int L = 0; L < 2; L++) {
        const uint32_t tag = ep * 2 + L + 1;
        bar_sync(NB_FREE + hw, 160);
        if (rb > 0) hint_wait(sb + OFF_HINT + 512 + j * 128, tag);
        uint32_t bad;
        do {
          if (rb > 0) {
            if (lane == 0) {
              mbar_expect_tx(bar_full(14) + hw * 128, 3072);
              bulk_load(own + ytail(hw * 2), sb + OFF_HALO + (L * 8 + j) * 3072, 1536, own + bar_full(14) + hw * 128);
              bulk_load(own + ytail(hw * 2 + 1), sb + OFF_HALO + (L * 8 + j) * 3072 + 1536, 1536, own + bar_full(14) + hw * 128);
            }
            mbar_wait(bar_full(14) + hw * 128, hph);
            hph ^= 1;
          }
          bad = 0;
#pragma unroll 1
          for (int c = 0; c < 3; c++) {
            uint32_t u[4] = {tag, 0, 0, 0}, v[4] = {tag, 0, 0, 0};
            if (rb > 0) { lds128(u, ytail(hw * 2) + c * 512 + lane * 16); lds128(v, ytail(hw * 2 + 1) + c * 512 + lane * 16); }
            bad |= (u[0] ^ tag) | (v[0] ^ tag);
#pragma unroll
            for (int i = 0; i < 3; i++) { sts32(xs + KSTG + (c * 3 + i) * 128 + lane * 4, u[i + 1]); sts32(xs + (c * 3 + i) * 128 + lane * 4, v[i + 1]); }
          }
        } while (__any_sync(0xffffffffu, bad != 0));
        bar_arrive(NB_HALO + hw, 160);
#pragma unroll 1
        for (int p = 0; p < 4; p++) {
          if (L == 0 && p == 3) flag_wait(flags + (40 + rb) * 8, (ep + 1) * 8);
          bar_sync(NB_FREE + hw, 160);
          TSH(L * 12 + p * 3);
          hint_wait(sb + OFF_HINT + (lane & 3) * 128, (ep * 15 + L * 8 + p + 3) * 8);
          TSH(L * 12 + p * 3 + 1);
          if (lane == 0) {
            mbar_expect_tx(fb, p ? PBUF : PBUF / 2);
            bulk_load(own + xs, sb + OFF_P + j * PSRC + (p ? (p == 2) * PBUF : 2 * PBUF), p ? PBUF : PBUF / 2, own + fb);
          }
          TSH(L * 12 + p * 3 + 2);
        }
      }
    } else {
      auto clear = [&](int t) {
        const uint32_t so = rb * 2 * STRM + (threadIdx.x & 31) * 16;
#pragma unroll 1
        for (int i = 0; i < 18; i++) {
          st16(P.scr, so + t * TILE + j * 9216 + i * 512, 0, 0, 0, 0, 0);
          st16(P.scr, so + t * TILE + j * 9216 + i * 512, STRM, 0, 0, 0, 0);
          __nanosleep(0);
        }
        if (t != 1) {
          st16(P.scr, so + (t ? t - 1 : 0) * 4096 + j * 512, OFF_ST, 0, 0, 0, 0);
          st16(P.scr, so + (t ? t - 1 : 0) * 4096 + j * 512, OFF_ST + STRM, 0, 0, 0, 0);
        }
      };
      bar_sync(NB_PUB + 3, 384);
      if (lane == 0) flag_signal(&flags[j * 8]);
      TSP(5);
      bar_sync(NB_PUB + 2, 288);
      if (lane == 0) flag_signal(&flags[(56 + j) * 8]);
      TSP(4);
      if (lane == 0) {
#pragma unroll 1
        for (int t = 0; t < PF_AHEAD; t++) prefetch_tile(t);
      }
      __syncwarp();
#pragma unroll 1
      for (int L = 0; L < 2; L++) {
        timed_wait(bar_empty(13), L);
#pragma unroll 1
        for (int t = L ^ 1; t < 4 - 2 * L; t++) clear(t);
        __syncwarp();
        if (lane == 0 && L == 0) flag_signal(flags + (40 + rb) * 8);
      }
      timed_wait(bar_empty(12), 0);
      if (MC) asm volatile("barrier.cluster.arrive.relaxed.aligned;\nbarrier.cluster.wait.aligned;" ::: "memory");
    }
  } else {
    asm volatile("setmaxnreg.inc.sync.aligned.u32 240;");
    const int w = __shfl_sync(0xffffffffu, (threadIdx.x >> 5) & 3, 0);
    const bool leader = (threadIdx.x & 127) == 0;
    const Rel rel{MC ? (threadIdx.x & 95) == 0 : leader, MC ? cta_window(w & 1) : 0};
    uint8_t* const sb = P.scr + (rb * 2 + wg) * STRM;
    uint8_t* const hint = sb + OFF_HINT + w * 128;
    auto hint_target = [](int e) { return (lds32(SM_EPOCH) * 15 + e + 1) * 8; };
    TS(0);
    uint32_t a[144];
#pragma unroll 1
    for (int L = 0; L < 2; L++) {
      uint32_t m0, m1; float r0, r1;
      if (L == 0) {
        Stats st;
        const int lane = tid_() & 31, g = lane >> 2;
        const int row = w * 16 + (lane & 15);
        const uint32_t ra = SB + wg * 8192 + row * 128;
        const uint32_t pt = tid_(), pu = (pt % 36) >> 2, pk = rb * 36 + (pt < 108 ? pt / 36 : 0) * 4 + (pt & 3);
        uint4 pv[3];
#pragma unroll
        for (int i = 0; i < 3; i++) pv[i] = ldg_line(wg ? wo_src(P.wo, pk + i * 12, pu, j) : P.wqkv + (pk + i * 12) * 1728 + j * 72 + pu * 8);
#pragma unroll
        for (int c = 0; c < 9; c++) {
          mbar_wait(bar_full(c), 0);
          if (c == 0) TS(60); if (c == 8) TS(62);
#pragma unroll
          for (int kk = 0; kk < 4; kk++) ldsm4(&a[c * 16 + kk * 4], ra + (((kk * 2 + (lane >> 4)) ^ (row & 7)) << 4) + c * SLOT);
          if (c == 8) {
            uint32_t y[18], z[4];
#pragma unroll
            for (int i = 0; i < 4; i++) ldsm4(&y[4 * i], ra + ((((j & 3) * 2 + (lane >> 4)) ^ (row & 7)) << 4) + (2 * i + (j >> 2)) * SLOT);
            ldsm4(z, ra + ((j ^ (row & 7)) << 4) + 8 * SLOT);
            y[16] = z[0]; y[17] = z[1];
            bar_sync(NB_WG + wg, 128);
#pragma unroll
            for (int i = 0; i < 9; i++) rel(i);
            if (pt < 108) {
#pragma unroll
              for (int i = 0; i < 3; i++) {
                const uint32_t k = pk + i * 12;
                st16(P.scr, (j * 24 + wg * 6 + k / 96) * PSLOT + pu * 1536 + (k % 96) * 16, OFF_WPACK + 12 * PSLOT, pv[i].x, pv[i].y, pv[i].z, pv[i].w);
              }
            }
            asm volatile("fence.proxy.async.global;" ::: "memory");
            bar_arrive(NB_PUB + 2, 288);
            store_own(y, sb, OFF_X2, j, tid_());
          }
#pragma unroll
          for (int kk = 0; kk < 4; kk++) st.add16(&a[c * 16 + kk * 4]);
        }
        const int dl = (lane & ~3) | (g >> 1);
        ln_scalars(st.s[0], __shfl_sync(0xffffffffu, st.sq0(g), dl), m0, r0, P.zero);
        ln_scalars(st.s[2], __shfl_sync(0xffffffffu, st.sq1(g), dl), m1, r1, P.zero);
      } else {
#pragma unroll
        for (int i = 12 * D_KV; i < 144; i++) a[i] = 0;
        hint_wait(hint, hint_target(7));
        TS(61);
        gather_ln<3 * D_KV>(a, sb, OFF_X2, 8192, m0, m1, r0, r1, P.zero);
      }
      TS(1 + L * 20);
      uint32_t kf[18], qf[18];
      {
        float acc[72];
        if (wg == 1) bar_sync(NB_ORD1, 256);
        mma_pass<144, PS_KV, 3, 256, D_KV, true>(acc, a, DESC_KV, 1, rel, wg == 0 ? NB_ORD1 : -1, sb, OFF_X2, L ^ 1, m0, m1, ytail(wg * 2));
        r0 = ln_rstd(r0, acc[0], P.zero); r1 = ln_rstd(r1, acc[0], P.zero);
        uint32_t vf[18];
#pragma unroll
        for (int c = 0; c < 9; c++) {
          kf[2 * c] = pack_bf16(acc[4 * c] * r0, acc[4 * c + 1] * r0);
          kf[2 * c + 1] = pack_bf16(acc[4 * c + 2] * r1, acc[4 * c + 3] * r1);
          vf[c] = pack_bf16(acc[36 + 4 * c] * r0, acc[36 + 4 * c + 1] * r0);
          vf[9 + c] = pack_bf16(acc[36 + 4 * c + 2] * r1, acc[36 + 4 * c + 3] * r1);
        }
        TS(2 + L * 20);
        const uint32_t l16 = (tid_() & 31) * 16, xs = slot_addr(12) + wg * SLOT + w * 1152;
#pragma unroll
        for (int i = 0; i < 4; i++) stsm4(xs + w * 1152 + 1152 + i * 512 + l16, vf[4 * i], vf[4 * i + 1], vf[4 * i + 2], vf[4 * i + 3]);
        sts32(xs + w * 1152 + 1152 + 2048 + l16 / 4, vf[16]); sts32(xs + w * 1152 + 1152 + 2176 + l16 / 4, vf[17]);
        if (w < 3) {
          stsm4(xs + KSTG + 1152 + l16, kf[1], kf[3], kf[5], kf[7]);
          stsm4(xs + KSTG + 1152 + 512 + l16, kf[9], kf[11], kf[13], kf[15]);
          sts32(xs + KSTG + 1152 + 1024 + l16 / 4, kf[17]);
        } else if (rb < 15) {
          const uint32_t tag = lds32(SM_EPOCH) * 2 + L + 1;
          const uint32_t ho = l16 + (L * 8 + j) * 3072;
#pragma unroll
          for (int c = 0; c < 3; c++) {
            st16(sb, ho, 2 * STRM + OFF_HALO + c * 512, tag, kf[6 * c + 1], kf[6 * c + 3], kf[6 * c + 5]);
            st16(sb, ho, 2 * STRM + OFF_HALO + 1536 + c * 512, tag, vf[9 + 3 * c], vf[10 + 3 * c], vf[11 + 3 * c]);
          }
          hint_post(sb + 2 * STRM + OFF_HINT + 512 + j * 128);
        }
      }
      lds128(a, ytail(wg * 2) + tid_() * 16);
      bar_arrive(NB_FREE + wg, 160);
      {
        float acc[36];
        if (wg == 1) bar_sync(NB_ORD1, 256);
        mma_pass<72, PS_Q, 6, 256, 0, false>(acc, a, DESC_Q, 0, rel, -1);
#pragma unroll
        for (int c = 0; c < 9; c++) {
          qf[2 * c] = pack_bf16(acc[4 * c] * r0, acc[4 * c + 1] * r0);
          qf[2 * c + 1] = pack_bf16(acc[4 * c + 2] * r1, acc[4 * c + 3] * r1);
        }
      }
      TS(3 + L * 20);
      uint32_t xr[18];
      {
        uint32_t kh[12], vt[28];
        const int tid = tid_(), g = (tid >> 2) & 7, q = tid & 3;
        bar_sync(NB_HALO + wg, 160);
        {
          const uint32_t xs = slot_addr(12) + wg * SLOT + w * 1152 + (tid & 31) * 16;
#pragma unroll
          for (int i = 0; i < 3; i++) ldsm4(&kh[4 * i], xs + KSTG + i * 512);
#pragma unroll
          for (int i = 0; i < 7; i++) ldsm4t(&vt[4 * i], xs + w * 1152 + i * 512);
        }
        TS(14 + L * 20);
        const bool nohalo = (rb == 0 && w == 0);
        const bool le0 = 2 * q <= g, le1 = 2 * q + 1 <= g;
        const uint32_t M = (le0 ? 0xffffu : 0u) | (le1 ? 0xffff0000u : 0u);
        const float sc = 0.23570226039551584f * 1.4426950408889634f;
        float l[16], t[8];
#pragma unroll
        for (int h = 0; h < 4; h++) {
          const uint32_t qa0 = q >= h ? qf[4 * h] : 0u, qa1 = q >= h ? qf[4 * h + 1] : 0u;
          const uint32_t qc0 = q <= h ? qf[4 * h + 4] : 0u, qc1 = q <= h ? qf[4 * h + 5] : 0u;
          float sm[4] = {0, 0, 0, 0}, s0[4] = {0, 0, 0, 0}, s1[4] = {0, 0, 0, 0};
          mma16816(s0, qa0, qa1, qf[4 * h + 2], qf[4 * h + 3], kf[4 * h], kf[4 * h + 2]);
          mma16816(s1, qa0, qa1, qf[4 * h + 2], qf[4 * h + 3], kf[4 * h + 1], kf[4 * h + 3]);
          mma16816(sm, qa0, qa1, qf[4 * h + 2], qf[4 * h + 3], kh[2 * h], kh[2 * h + 1]);
          mma1688(s0, qc0, qc1, kf[4 * h + 4]);
          mma1688(s1, qc0, qc1, kf[4 * h + 5]);
          mma1688(sm, qc0, qc1, kh[2 * h + 2]);
          if (nohalo) sm[0] = sm[1] = -1e9f / 0.23570226039551584f;
          l[4 * h] = le0 ? s0[0] : sm[0]; l[4 * h + 1] = le1 ? s0[1] : sm[1];
          l[4 * h + 2] = le0 ? s1[2] : s0[2]; l[4 * h + 3] = le1 ? s1[3] : s0[3];
        }
#pragma unroll
        for (int i = 0; i < 8; i++) t[i] = fmaxf(l[2 * i], l[2 * i + 1]);
#pragma unroll
        for (int i = 0; i < 8; i++) t[i] = fmaxf(t[i], __shfl_xor_sync(0xffffffffu, t[i], 1));
#pragma unroll
        for (int i = 0; i < 8; i++) t[i] = fmaxf(t[i], __shfl_xor_sync(0xffffffffu, t[i], 2)) * sc;
#pragma unroll
        for (int i = 0; i < 8; i++) { l[2 * i] = ex2(fmaf(l[2 * i], sc, -t[i])); l[2 * i + 1] = ex2(fmaf(l[2 * i + 1], sc, -t[i])); t[i] = l[2 * i] + l[2 * i + 1]; }
#pragma unroll
        for (int i = 0; i < 8; i++) t[i] += __shfl_xor_sync(0xffffffffu, t[i], 1);
#pragma unroll
        for (int i = 0; i < 8; i++) t[i] += __shfl_xor_sync(0xffffffffu, t[i], 2);
        uint32_t pf[16];
#pragma unroll
        for (int i = 0; i < 8; i++) {
          float r; asm("rcp.approx.ftz.f32 %0, %1;" : "=f"(r) : "f"(t[i]));
          const uint32_t p = pack_bf16(l[2 * i] * r, l[2 * i + 1] * r);
          pf[2 * i] = p & ~M; pf[2 * i + 1] = p & M;
        }
#pragma unroll
        for (int c = 0; c < 9; c++) {
          const int h = c == 8 ? 3 : c >> 1;
          float o[4] = {0, 0, 0, 0};
          mma16816(o, pf[4 * h], 0u, pf[4 * h + 1], pf[4 * h + 2], vt[c], vt[9 + c]);
          mma1688(o, 0u, pf[4 * h + 3], vt[18 + c]);
          if (c == 2 || c == 4 || c == 6) {
            float e[4] = {0, 0, 0, 0};
            mma16816(e, pf[4 * h - 4], 0u, pf[4 * h - 3], pf[4 * h - 2], vt[c], vt[9 + c]);
            mma1688(e, 0u, pf[4 * h - 1], vt[18 + c]);
            if (q < h) { o[0] = e[0]; o[1] = e[1]; o[2] = e[2]; o[3] = e[3]; }
          }
          qf[2 * c] = pack_bf16(o[0], o[1]); qf[2 * c + 1] = pack_bf16(o[2], o[3]);
        }
        store_own(qf, sb, OFF_O, j, tid);
        hint_post(hint);
        bar_arrive(NB_ORD1 - wg, 256);
        load_own(xr, sb, OFF_X2, j);
      }
      TS(4 + L * 20);
      {
        hint_wait(hint, hint_target(L * 8));
        TS(5 + L * 20);
        load_frags<6 * D_WO>(a, sb, OFF_O, tid_());
        float acc[36];
        if (wg == 0) bar_sync(NB_ORD0, 256);
        mma_pass<72, PS_WO, 6, 256, D_WO, false>(acc, a, DESC_Q, 0, rel, -1, sb, OFF_O);
        TS(6 + L * 20);
#pragma unroll
        for (int c = 0; c < 9; c++) {
          xr[2 * c] = bf2_add(xr[2 * c], pack_bf16(acc[4 * c], acc[4 * c + 1]));
          xr[2 * c + 1] = bf2_add(xr[2 * c + 1], pack_bf16(acc[4 * c + 2], acc[4 * c + 3]));
        }
        store_own(xr, sb, L * 3 * TILE, j, tid_());
        RowStats rs;
        rs.add<18>(xr);
        rs.store(sb, L * 4096 + j * 128, tid_());
        hint_post(hint);
      }
      TS(16 + L * 20);
      hint_wait(hint, hint_target(L * 8 + 1));
      TS(15 + L * 20);
      gather_ln<4 * D_T0>(a, sb, L * 3 * TILE, L * 4096, m0, m1, r0, r1, P.zero);
      TS(7 + L * 20);
      const uint32_t hb = (L ^ 1) * TILE + j * 9216;
      {
        float ka0, kb0, kc0, ka1, kb1, kc1;
        float acc[64];
        uint32_t hf[16];
        auto geglu = [&](auto chains, uint32_t hsm) {
          constexpr int CH = decltype(chains)::value;
          float r[32];
#pragma unroll
          for (int e = 0; e < 32; e++) {
            float x = acc[e];
            if (e >= CH) x = __uint_as_float(__float_as_uint(x) ^ (__float_as_uint(r[e - CH]) & P.zero));
            if (CH != 2 && e < 20) {
              const uint32_t ad = (e < 8 ? slot_addr(12) + e * 2048 + wg * 8192 : slot_addr(7 + (e >> 2)) + (e & 3) * 2048) + hsm;
              lds128(&a[48 + 4 * e], e >= CH ? ad ^ (__float_as_uint(r[e - CH]) & P.zero) : ad);
            }
            const bool hi = e & 2;
            float t = x * fmaf(x * x, hi ? kb1 : kb0, hi ? ka1 : ka0);
            asm("tanh.approx.f32 %0, %0;" : "+f"(t));
            const float u = x * acc[32 + e] * (hi ? kc1 : kc0);
            r[e] = fmaf(u, t, u);
            if (e & 1) hf[e >> 1] = pack_bf16(r[e - 1], r[e]);
          }
        };
        if (wg == 1) bar_sync(NB_ORD1, 256);
        mma_pass<128, PS_FF, 4, 2048, D_T0, true>(acc, a, DESC_SW128, 1, rel, NB_ORD1 - wg, sb, L * 3 * TILE, 0, m0, m1);
        TS(8 + L * 20);
        r0 = ln_rstd(r0, acc[0], P.zero); r1 = ln_rstd(r1, acc[0], P.zero);
        ka0 = 0.7978845608028654f * r0; kb0 = 0.035677408136300125f * r0 * r0 * r0; kc0 = 0.5f * r0 * r0;
        ka1 = 0.7978845608028654f * r1; kb1 = 0.035677408136300125f * r1 * r1 * r1; kc1 = 0.5f * r1 * r1;
#pragma unroll 1
        for (int t = 0; t < 8; t++) {
          geglu(IntC<2>(), 0);
          const uint32_t t16 = tid_() * 16;
          if (t < 5) {
            const uint32_t d = (t < 2 ? slot_addr(12) + wg * SLOT + t * 8192 : slot_addr(7) + t * SLOT + wg * 8192) + t16;
#pragma unroll
            for (int i = 0; i < 4; i++)
              sts128(d + i * 2048, hf[4 * i], hf[4 * i + 1], hf[4 * i + 2], hf[4 * i + 3]);
            if (t == 4) asm volatile("fence.proxy.async.shared::cta;" ::: "memory");
          } else {
#pragma unroll
            for (int i = 0; i < 4; i++) st16(sb, hb + (t - 5) * TILE + t16, i * 2048, hf[4 * i], hf[4 * i + 1], hf[4 * i + 2], hf[4 * i + 3]);
          }
          bar_sync(NB_ORD0 + wg, 256);
          mma_pass<128, PS_FF, 4, 2048, 0, false, true>(acc, a, DESC_SW128, t & 1, rel, NB_ORD1 - wg, sb, hb + t16, t == 7);
        }
        TS(9 + L * 20);
        const uint32_t hsm = wg * 8192 + tid_() * 16;
        geglu(IntC<CH_LAST>(), hsm);
#pragma unroll
        for (int i = 0; i < 16; i++) a[128 + i] = hf[i];
      }
      TS(10 + L * 20);
      {
        const uint32_t xs = slot_addr(12) + wg * SLOT;
        {
          bar_sync(NB_ORD0 + wg + ((a[142] | a[143]) & P.zero), 256);
          TS(64 + L * 32);
          rel(9); rel(10); rel(11);
          float acc[32];
          mma_pass<64, PS_FF, 4, 2048, 0, false>(acc, a, DESC_SW128, 0, rel, NB_ORD1 - wg);
          TS(65 + L * 32);
          const uint32_t t8 = tid_() * 8;
#pragma unroll
          for (int i = 0; i < 8; i++) {
            const uint32_t u = pack_bf16(acc[4 * i], acc[4 * i + 1]), v = pack_bf16(acc[4 * i + 2], acc[4 * i + 3]);
            send8(sb, j * 1024 + t8, OFF_P + 2 * PBUF + i * PSRC, xs + PBUF + t8 * 2, i, j, (u & ~1u) | (L ^ 1), v);
          }
          hint_post(hint);
          if (tid_() == 0) mbar_arrive(bar_empty(13));
          bar_arrive(NB_FREE + wg, 160);
          TS(68 + L * 32);
        }
        float acc[64];
        auto verify = [&](int p, uint32_t t16) {
          mbar_wait(bar_full(12) + wg * 8, (p & 1) ^ 1);
          TS(66 + L * 32 + p * 5);
          const uint32_t flip = p == 1 ? L - 1 : p < 4 ? ~0u : 0u;
          const uint32_t sh = p == 1;
          uint32_t m = 0;
#pragma unroll
          for (int s = 0; s < 7; s++) m |= lds32(xs + ((s * 2048 + t16) >> sh)) ^ flip;
          if (__any_sync(0xffffffffu, m & 1)) {
#pragma unroll 1
            for (int s = 0; s < 7; s++) {
              const uint32_t o = (s * 2048 + t16) >> sh;
              uint32_t v[4] = {0, 0, 0, 0};
              do {
                if (sh) ld8(v, sb, j * PSRC + o, OFF_P + 2 * PBUF);
                else ld16(v, sb, j * PSRC + (p & 1) * PBUF + o, OFF_P);
              } while (__any_sync(0xffffffffu, (v[0] ^ flip) & 1));
              sts64(xs + o, v[0], v[1]);
              if (!sh) sts64(xs + o + 8, v[2], v[3]);
            }
            asm volatile("fence.proxy.async.shared::cta;" ::: "memory");
          }
        };
        auto send = [&](int p, uint32_t t16) {
#pragma unroll
          for (int i = 0; i < 8; i++) {
            const uint32_t u0 = pack_bf16(acc[8 * i], acc[8 * i + 1]), u1 = pack_bf16(acc[8 * i + 2], acc[8 * i + 3]);
            const uint32_t u2 = pack_bf16(acc[8 * i + 4], acc[8 * i + 5]), u3 = pack_bf16(acc[8 * i + 6], acc[8 * i + 7]);
            send16(sb, j * 2048 + ((p & 1) ^ 1) * PBUF + t16, OFF_P + i * PSRC, xs + PBUF + t16, i, j, (u0 & ~1u) | (p < 3), u1, u2, u3);
          }
          hint_post(hint);
          TS(68 + L * 32 + p * 5);
        };
        uint32_t y[18];
#pragma unroll 1
        for (int p = 1; p < 5; p++) {
          bar_sync(NB_ORD0 + wg, 256);
          TS(64 + L * 32 + p * 5);
          mma_pass<128, PS_FF, 4, 2048, 0, false>(acc, a, DESC_SW128, p & 1, rel, (p == 4 && wg == 1) ? -1 : NB_ORD1 - wg);
          TS(65 + L * 32 + p * 5);
          const uint32_t t16 = tid_() * 16;
          uint32_t in[32];
          if (p == 4) load_own(&a[64], sb, L * 3 * TILE, j);
          lds128(&in[28], xs + PBUF + t16);
          verify(p, t16);
          send(p, t16);
          if (p == 1) {
#pragma unroll
            for (int s = 0; s < 7; s++) {
              lds64(in[4 * s], in[4 * s + 1], xs + s * 1024 + t16 / 2);
              in[4 * s + 2] = in[4 * s + 3] = 0;
            }
          } else {
#pragma unroll
            for (int s = 0; s < 7; s++) lds128(&in[4 * s], xs + s * 2048 + t16);
          }
          if (p < 4) bar_arrive(NB_FREE + wg, 160);
          reduce4(in, y + 8);
          if (p == 1) sts64(ytail(wg * 2 + (t16 >> 10)) + 2048 + (t16 & 1023) / 2, y[8], y[9]);
          else if (p < 4) sts128(ytail(wg * 2 + p - 2) + t16, y[8], y[9], y[10], y[11]);
          TS(67 + L * 32 + p * 5);
        }
        TS(11 + L * 20);
        const uint32_t t = tid_();
#pragma unroll
        for (int i = 0; i < 2; i++) lds128(&y[4 * i], ytail(wg * 2 + i) + t * 16);
        lds64(y[16], y[17], ytail(wg * 2 + (t >> 6)) + 2048 + (t & 63) * 8);
        lds128(&a[60], xs + PBUF + t * 16);
        const uint32_t tgt = hint_target(L * 8 + 6);
#pragma unroll
        for (int i = 0; i < 18; i++) xr[i] = a[64 + i];
        auto emit = [&](uint32_t mask) {
#pragma unroll
          for (int i = 0; i < 18; i++) if (mask >> (i >> 2) & 1) xr[i] = bf2_add(xr[i], y[i]);
          if (L == 0) {
#pragma unroll
            for (int i = 0; i < 4; i++) if (mask >> i & 1) st16(sb, (t + j * 128) * 16, OFF_X2 + i * 16384, nz(xr[4 * i]), xr[4 * i + 1], xr[4 * i + 2], xr[4 * i + 3]);
            if (mask & 16) st8(sb, (t + j * 128) * 8, OFF_X2 + 65536, nz(xr[16]), xr[17]);
          } else {
#pragma unroll
            for (int i = 0; i < 4; i++) if (mask >> i & 1) stsm4(xs + i * 2048 + t * 16, xr[4 * i], xr[4 * i + 1], xr[4 * i + 2], xr[4 * i + 3]);
            if (mask & 16) stsm4(xs + 8192 + t * 16, xr[16], xr[17], 0, 0);
            __syncwarp();
            uint8_t* op = (uint8_t*)P.out + row_off(rb, wg, t);
#pragma unroll
            for (int i = 0; i < 5; i++) if (mask >> i & 1) {
              uint32_t r[4];
              lds128(r, xs + i * 2048 + t * 16);
              if (i < 4) *(uint4*)(op + i * 256 + j * 32 + (t & 16)) = make_uint4(r[0], r[1], r[2], r[3]);
              else if (!(t & 16)) *(uint4*)(op + 1024 + j * 16) = make_uint4(r[0], r[1], r[2], r[3]);
            }
          }
        };
        __syncwarp();
        emit(23);
        RowStats rs;
        rs.add<12>(xr); rs.add<2>(xr + 16);
        hint_wait(hint, tgt + (rs.fold() & P.zero));
        TS(17 + L * 20);
        {
          uint32_t m;
          do {
            m = 0;
#pragma unroll
            for (int s = 0; s < 7; s++) { ld16(&a[32 + 4 * s], sb, j * PSRC + t * 16, OFF_P + PBUF + s * 2048); m |= a[32 + 4 * s]; }
          } while (__any_sync(0xffffffffu, m & 1));
          TS(12 + L * 20);
          reduce4(a + 32, y + 12);
        }
        TS(18 + L * 20);
        emit(8);
        if (L == 0) {
          rs.add<4>(xr + 12);
          rs.store(sb, 8192 + j * 128, t);
          hint_post(hint);
        }
      }
      TS(13 + L * 20);
    }
    bar_sync(NB_WG + wg, 128);
    if (tid_() == 0) mbar_arrive(bar_empty(12));
  }
}

typedef CUresult (*EncodeFn)(CUtensorMap*, CUtensorMapDataType, cuuint32_t, void*, const cuuint64_t*, const cuuint64_t*, const cuuint32_t*,
                             const cuuint32_t*, CUtensorMapInterleave, CUtensorMapSwizzle, CUtensorMapL2promotion, CUtensorMapFloatOOBfill);

void encode(EncodeFn fn, CUtensorMap* m, const void* p, int rank, const cuuint64_t* dims, const cuuint64_t* str, const cuuint32_t* box) {
  const cuuint32_t es[3] = {1, 1, 1};
  fn(m, CU_TENSOR_MAP_DATA_TYPE_BFLOAT16, rank, const_cast<void*>(p), dims, str, box, es, CU_TENSOR_MAP_INTERLEAVE_NONE,
     CU_TENSOR_MAP_SWIZZLE_128B, CU_TENSOR_MAP_L2_PROMOTION_L2_256B, CU_TENSOR_MAP_FLOAT_OOB_FILL_NONE);
}

}

extern "C" void kernel_launch(void* const* d_in, const int* in_sizes, int n_in, void* d_out, int out_size) {
  (void)in_sizes; (void)n_in; (void)out_size;
  Params P;
  P.x = (const __nv_bfloat16*)d_in[0]; P.wqkv = (const __nv_bfloat16*)d_in[1]; P.wo = (const __nv_bfloat16*)d_in[2];
  P.wg = (const __nv_bfloat16*)d_in[4]; P.wu = (const __nv_bfloat16*)d_in[5]; P.wd = (const __nv_bfloat16*)d_in[6];
  P.out = (__nv_bfloat16*)d_out; P.zero = 0;
  cudaGetSymbolAddress((void**)&P.scr, g_scr);
  void* fnp = nullptr; cudaDriverEntryPointQueryResult qr;
  cudaGetDriverEntryPoint("cuTensorMapEncodeTiled", &fnp, cudaEnableDefault, &qr);
  EncodeFn fn = (EncodeFn)fnp;
  CUtensorMap mx, mg, mu, md;
  { const cuuint64_t dims[3] = {DM, SEQ / 2, 2}, str[2] = {DM * 4, DM * 2}; const cuuint32_t box[3] = {64, 64, 2}; encode(fn, &mx, P.x, 3, dims, str, box); }
  { const cuuint64_t dims[2] = {DFF, DM}, str[1] = {DFF * 2}; const cuuint32_t box[2] = {64, 64}; encode(fn, &mg, P.wg, 2, dims, str, box); encode(fn, &mu, P.wu, 2, dims, str, box); }
  { const cuuint64_t dims[2] = {DM, DFF}, str[1] = {DM * 2}; const cuuint32_t box[2] = {64, 64}; encode(fn, &md, P.wd, 2, dims, str, box); }
  cudaFuncSetAttribute(fused_kernel, cudaFuncAttributeMaxDynamicSharedMemorySize, SMEM_BYTES);
  fused_kernel<<<128, 384, SMEM_BYTES, cudaStreamPerThread>>>(mx, mg, mu, md, P);
}
```

```cpp
#include <cuda_runtime.h>
#include <cuda_bf16.h>
#include <cuda.h>
#include <stdint.h>

#define KV_LEAD 5
#define D_KV 6
#define D_WO 3
#define D_T0 5
#define PF_AHEAD 3
#define CH_LAST 4
#define MC 0
#define MAP 3
#define N_WO 18
#define TH 1
#define THD 0
#define DBG_PS 2
#define TIMING 0

namespace {

constexpr int SEQ = 2048, DM = 576, DFF = 4608;
constexpr uint32_t SB = 1024;
constexpr uint32_t SLOT = 16384;
constexpr uint32_t PSLOT = 13824;
constexpr uint32_t BARS = SB + 14 * SLOT;
constexpr int SMEM_BYTES = 14 * SLOT + 256 + 2560;
__host__ __device__ constexpr uint32_t slot_addr(int s) { return SB + s * SLOT; }
__host__ __device__ constexpr uint32_t bar_full(int s) { return BARS + 8 * s; }
__host__ __device__ constexpr uint32_t bar_empty(int s) { return BARS + 128 + 8 * s; }
enum { NB_ORD0 = 1, NB_ORD1 = 2, NB_WG = 3  , NB_HALO = 5  , NB_FREE = 7  , NB_PUB = 9   };
constexpr uint32_t SM_EPOCH = BARS + 120;
__host__ __device__ constexpr uint32_t ytail(uint32_t k) { return k < 3 ? slot_addr(9) + PSLOT + k * SLOT : BARS + 256; }
constexpr uint32_t KSTG = 9 * 1152;

constexpr uint32_t TILE = 36 * 2048;
constexpr uint32_t OFF_X1 = 0  , OFF_O = TILE, OFF_X2 = 2 * TILE, OFF_ST = 4 * TILE  ;
constexpr uint32_t PBUF = 7 * 2048, PSRC = 2 * PBUF + PBUF / 2;
constexpr uint32_t OFF_P = OFF_ST + 3 * 4096, OFF_HALO = OFF_P + 8 * PSRC  , OFF_HINT = OFF_HALO + 2 * 8 * 3072  ,
                   STRM = OFF_HINT + 12 * 128;
constexpr uint32_t OFF_WPACK = 32 * STRM, OFF_FLAGS = OFF_WPACK + 8 * 24 * PSLOT;
__device__ __align__(1024) uint8_t g_scr[OFF_FLAGS + (8 + 64 + 128) * 32];

__device__ __forceinline__ uint32_t smem_u32(const void* p) { return (uint32_t)__cvta_generic_to_shared(p); }
extern __shared__ __align__(1024) uint8_t smem_raw[];
__device__ __forceinline__ uint32_t win() { return MC ? (blockIdx.x & 1) << 24 : 0; }
#define SA(A, W) ".reg .u32 sa;\nadd.u32 sa, " A ", " W ";\n"
__device__ __forceinline__ void mbar_init(uint32_t bar, uint32_t cnt) { asm volatile("{\n" SA("%0", "%2") "mbarrier.init.shared::cta.b64 [sa], %1;\n}" ::"r"(bar), "r"(cnt), "r"(win())); }
__device__ __forceinline__ void mbar_expect_tx(uint32_t bar, uint32_t bytes) { asm volatile("{\n" SA("%0", "%2") "mbarrier.arrive.expect_tx.shared::cta.b64 _, [sa], %1;\n}" ::"r"(bar), "r"(bytes), "r"(win()) : "memory"); }
__device__ __forceinline__ void mbar_arrive(uint32_t bar) { asm volatile("{\n" SA("%0", "%1") "mbarrier.arrive.shared::cta.b64 _, [sa];\n}" ::"r"(bar), "r"(win()) : "memory"); }
__device__ __forceinline__ uint32_t lds32(uint32_t a) { uint32_t v; asm volatile("{\n" SA("%1", "%2") "ld.shared.u32 %0, [sa];\n}" : "=r"(v) : "r"(a), "r"(win()) : "memory"); return v; }
__device__ __forceinline__ void lds64(uint32_t& x, uint32_t& y, uint32_t a) { asm volatile("{\n" SA("%2", "%3") "ld.shared.v2.u32 {%0,%1}, [sa];\n}" : "=r"(x), "=r"(y) : "r"(a), "r"(win()) : "memory"); }
__device__ __forceinline__ void lds128(uint32_t* v, uint32_t a) {
  asm volatile("{\n" SA("%4", "%5") "ld.shared.v4.u32 {%0,%1,%2,%3}, [sa];\n}" : "=r"(v[0]), "=r"(v[1]), "=r"(v[2]), "=r"(v[3]) : "r"(a), "r"(win()) : "memory");
}
__device__ __forceinline__ void stsm4(uint32_t a, uint32_t x, uint32_t y, uint32_t z, uint32_t w) {
  asm volatile("{\n" SA("%0", "%5") "stmatrix.sync.aligned.m8n8.x4.shared.b16 [sa], {%1,%2,%3,%4};\n}" ::"r"(a), "r"(x), "r"(y), "r"(z), "r"(w), "r"(win()) : "memory");
}
__device__ __forceinline__ void ldsm4(uint32_t* v, uint32_t a) {
  asm volatile("{\n" SA("%4", "%5") "ldmatrix.sync.aligned.m8n8.x4.shared.b16 {%0,%1,%2,%3}, [sa];\n}" : "=r"(v[0]), "=r"(v[1]), "=r"(v[2]), "=r"(v[3]) : "r"(a), "r"(win()) : "memory");
}
__device__ __forceinline__ void ldsm4t(uint32_t* v, uint32_t a) {
  asm volatile("{\n" SA("%4", "%5") "ldmatrix.sync.aligned.m8n8.x4.trans.shared.b16 {%0,%1,%2,%3}, [sa];\n}" : "=r"(v[0]), "=r"(v[1]), "=r"(v[2]), "=r"(v[3]) : "r"(a), "r"(win()) : "memory");
}
__device__ __forceinline__ void sts32(uint32_t a, uint32_t x) { asm volatile("{\n" SA("%0", "%2") "st.shared.u32 [sa], %1;\n}" ::"r"(a), "r"(x), "r"(win()) : "memory"); }
__device__ __forceinline__ void sts64(uint32_t a, uint32_t x, uint32_t y) { asm volatile("{\n" SA("%0", "%3") "st.shared.v2.u32 [sa], {%1,%2};\n}" ::"r"(a), "r"(x), "r"(y), "r"(win()) : "memory"); }
__device__ __forceinline__ void sts128(uint32_t a, uint32_t x, uint32_t y, uint32_t z, uint32_t w) {
  asm volatile("{\n" SA("%0", "%5") "st.shared.v4.u32 [sa], {%1,%2,%3,%4};\n}" ::"r"(a), "r"(x), "r"(y), "r"(z), "r"(w), "r"(win()) : "memory");
}
__device__ __forceinline__ void mbar_wait(uint32_t bar, uint32_t parity) {
  asm volatile("{\n.reg .pred p;\n" SA("%0", "%2") "LAB_WAIT:\nmbarrier.try_wait.parity.shared::cta.b64 p, [sa], %1;\n@!p bra LAB_WAIT;\n}" ::"r"(bar), "r"(parity), "r"(win()) : "memory");
}
__device__ __forceinline__ void timed_wait(uint32_t bar, uint32_t par) {
  asm volatile("{\n.reg .pred p;\n.reg .u64 t0, t1;\nmov.u64 t0, %%globaltimer;\nLAB_WD:\n"
               "mbarrier.try_wait.parity.shared::cta.b64 p, [%0], %1, 100000;\n@p bra LAB_OK;\n"
               "mov.u64 t1, %%globaltimer;\nsub.u64 t1, t1, t0;\nsetp.lt.u64 p, t1, 2000000000;\n@p bra LAB_WD;\ntrap;\nLAB_OK:\n}" ::"r"(bar + win()), "r"(par) : "memory");
}
__device__ __forceinline__ void flag_wait(const unsigned* flag, unsigned target) {
  asm volatile("{\n.reg .pred p;\n.reg .u32 v;\nLAB_WAIT:\nld.acquire.gpu.global.u32 v, [%0];\nsub.u32 v, v, %1;\n"
               "setp.lt.s32 p, v, 0;\n@p nanosleep.u32 100;\n@p bra LAB_WAIT;\n}" ::"l"(flag), "r"(target) : "memory");
}
__device__ __forceinline__ void hint_post(uint8_t* p) {
  __syncwarp();
  asm volatile("{\n.reg .pred p;\nelect.sync _|p, 0xffffffff;\n@p red.relaxed.gpu.global.add.u32 [%0], 1;\n}" ::"l"(p) : "memory");
}
__device__ __forceinline__ void hint_wait(const uint8_t* p, uint32_t target) {
  asm volatile("{\n.reg .pred p;\n.reg .u32 v;\nLAB_WAIT:\nld.relaxed.gpu.global.u32 v, [%0];\nsub.u32 v, v, %1;\n"
               "setp.lt.s32 p, v, 0;\nvote.sync.any.pred p, p, 0xffffffff;\n@p bra LAB_WAIT;\n}" ::"l"(p), "r"(target) : "memory");
}
__device__ __forceinline__ void flag_signal(unsigned* flag) { asm volatile("red.release.gpu.global.add.u32 [%0], 1;" ::"l"(flag) : "memory"); }
struct Rel {
  bool on; uint32_t base;
  __device__ __forceinline__ void operator()(int s) const {
    if (on) {
      if (MC) asm volatile("{\n" SA("%0", "%1") "mbarrier.arrive.shared::cluster.b64 _, [sa];\n}" ::"r"(bar_empty(s)), "r"(base) : "memory");
      else mbar_arrive(bar_empty(s));
    }
  }
};
__device__ __forceinline__ uint32_t cta_window(uint32_t rank) { uint32_t a; asm("mapa.shared::cluster.u32 %0, %1, %2;" : "=r"(a) : "r"(0), "r"(rank)); return a; }
__device__ __forceinline__ void tma_2d_mc(uint32_t dst, const CUtensorMap* m, int c0, int c1, uint32_t bar) {
  asm volatile("cp.async.bulk.tensor.2d.shared::cluster.global.mbarrier::complete_tx::bytes.multicast::cluster [%0], [%1, {%3, %4}], [%2], %5;"
               ::"r"(dst), "l"(m), "r"(bar), "r"(c0), "r"(c1), "h"((uint16_t)3) : "memory");
}
__device__ __forceinline__ void bulk_load_mc(uint32_t dst, const void* src, uint32_t bytes, uint32_t bar) {
  asm volatile("cp.async.bulk.shared::cluster.global.mbarrier::complete_tx::bytes.multicast::cluster [%0], [%1], %2, [%3], %4;"
               ::"r"(dst), "l"(src), "r"(bytes), "r"(bar), "h"((uint16_t)3) : "memory");
}
__device__ __forceinline__ void tma_2d(uint32_t dst, const CUtensorMap* m, int c0, int c1, uint32_t bar) {
  asm volatile("cp.async.bulk.tensor.2d.shared::cluster.global.mbarrier::complete_tx::bytes [%0], [%1, {%3, %4}], [%2];"
               ::"r"(dst), "l"(m), "r"(bar), "r"(c0), "r"(c1) : "memory");
}
__device__ __forceinline__ void tma_3d(uint32_t dst, const CUtensorMap* m, int c0, int c1, int c2, uint32_t bar) {
  asm volatile("cp.async.bulk.tensor.3d.shared::cluster.global.mbarrier::complete_tx::bytes [%0], [%1, {%3, %4, %5}], [%2];"
               ::"r"(dst), "l"(m), "r"(bar), "r"(c0), "r"(c1), "r"(c2) : "memory");
}
__device__ __forceinline__ void bulk_load(uint32_t dst, const void* src, uint32_t bytes, uint32_t bar) {
  asm volatile("cp.async.bulk.shared::cluster.global.mbarrier::complete_tx::bytes [%0], [%1], %2, [%3];" ::"r"(dst), "l"(src), "r"(bytes), "r"(bar) : "memory");
}
__device__ __forceinline__ void l2_prefetch(const void* src, uint32_t bytes) { asm volatile("cp.async.bulk.prefetch.L2.global [%0], %1;" ::"l"(src), "r"(bytes) : "memory"); }
__device__ __forceinline__ void wg_fence() { asm volatile("wgmma.fence.sync.aligned;" ::: "memory"); }
__device__ __forceinline__ void wg_commit() { asm volatile("wgmma.commit_group.sync.aligned;" ::: "memory"); }
template <int N> __device__ __forceinline__ void wg_wait() { asm volatile("wgmma.wait_group.sync.aligned %0;" ::"n"(N) : "memory"); }
__device__ __forceinline__ void bar_sync(int id, int n) { asm volatile("bar.sync %0, %1;" ::"r"(id), "r"(n) : "memory"); }
__device__ __forceinline__ void bar_arrive(int id, int n) { asm volatile("bar.arrive %0, %1;" ::"r"(id), "r"(n) : "memory"); }
__device__ __forceinline__ uint32_t pack_bf16(float lo, float hi) { uint32_t r; asm("cvt.rn.bf16x2.f32 %0, %1, %2;" : "=r"(r) : "f"(hi), "f"(lo)); return r; }
__device__ __forceinline__ float bf_lo(uint32_t w) { return __uint_as_float(w << 16); }
__device__ __forceinline__ float bf_hi(uint32_t w) { return __uint_as_float(w & 0xffff0000u); }
__device__ __forceinline__ float bf_round(float x) { return bf_lo(pack_bf16(x, 0.f)); }
__device__ __forceinline__ uint32_t bf2_sub(uint32_t a, uint32_t b) { uint32_t r; asm("sub.rn.bf16x2 %0, %1, %2;" : "=r"(r) : "r"(a), "r"(b)); return r; }
__device__ __forceinline__ uint32_t bf2_add(uint32_t a, uint32_t b) { uint32_t r; asm("add.rn.bf16x2 %0, %1, %2;" : "=r"(r) : "r"(a), "r"(b)); return r; }
#define GADDR(B, O, I) "cvt.u64.u32 ad, " O ";\nadd.u64 ad, ad, " B ";\nadd.u64 ad, ad, " I ";\n"
__device__ __forceinline__ void ld16(uint32_t* v, const uint8_t* ub, uint32_t off, uint32_t imm) {
  asm volatile("{\n.reg .b128 z;\n.reg .b64 x, y, ad;\n" GADDR("%4", "%5", "%6") "ld.relaxed.gpu.global.b128 z, [ad];\n"
               "mov.b128 {x, y}, z;\nmov.b64 {%0,%1}, x;\nmov.b64 {%2,%3}, y;\n}"
               : "=r"(v[0]), "=r"(v[1]), "=r"(v[2]), "=r"(v[3]) : "l"(ub), "r"(off), "l"((uint64_t)imm) : "memory");
}
__device__ __forceinline__ void ld8(uint32_t* v, const uint8_t* ub, uint32_t off, uint32_t imm) {
  asm volatile("{\n.reg .b64 x, ad;\n" GADDR("%2", "%3", "%4") "ld.relaxed.gpu.global.b64 x, [ad];\nmov.b64 {%0,%1}, x;\n}"
               : "=r"(v[0]), "=r"(v[1]) : "l"(ub), "r"(off), "l"((uint64_t)imm) : "memory");
}
__device__ __forceinline__ void st16(uint8_t* ub, uint32_t off, uint32_t imm, uint32_t a, uint32_t b, uint32_t c, uint32_t d) {
  asm volatile("{\n.reg .b128 z;\n.reg .b64 x, y, ad;\n" GADDR("%0", "%1", "%2") "mov.b64 x, {%3,%4};\nmov.b64 y, {%5,%6};\nmov.b128 z, {x, y};\n"
               "st.relaxed.gpu.global.b128 [ad], z;\n}" ::"l"(ub), "r"(off), "l"((uint64_t)imm), "r"(a), "r"(b), "r"(c), "r"(d) : "memory");
}
__device__ __forceinline__ void st8(uint8_t* ub, uint32_t off, uint32_t imm, uint32_t a, uint32_t b) {
  asm volatile("{\n.reg .b64 x, ad;\n" GADDR("%0", "%1", "%2") "mov.b64 x, {%3,%4};\nst.relaxed.gpu.global.b64 [ad], x;\n}"
               ::"l"(ub), "r"(off), "l"((uint64_t)imm), "r"(a), "r"(b) : "memory");
}
__device__ __forceinline__ void send16(uint8_t* ub, uint32_t off, uint32_t imm, uint32_t sm, int i, int j, uint32_t a, uint32_t b, uint32_t c, uint32_t d) {
  asm volatile("{\n.reg .pred p, q, e;\n.reg .b128 z;\n.reg .b64 x, y, ad;\n" SA("%3", "%10") GADDR("%0", "%1", "%2")
               "setp.lt.s32 p, %4, %5;\nsetp.gt.s32 q, %4, %5;\nsetp.eq.s32 e, %4, %5;\nmov.b64 x, {%6,%7};\nmov.b64 y, {%8,%9};\nmov.b128 z, {x, y};\n"
               "@p st.relaxed.gpu.global.b128 [ad+-2048], z;\n@q st.relaxed.gpu.global.b128 [ad], z;\n@e st.shared.v4.u32 [sa], {%6,%7,%8,%9};\n}"
               ::"l"(ub), "r"(off), "l"((uint64_t)imm), "r"(sm), "r"(i), "r"(j), "r"(a), "r"(b), "r"(c), "r"(d), "r"(win()) : "memory");
}
__device__ __forceinline__ void send8(uint8_t* ub, uint32_t off, uint32_t imm, uint32_t sm, int i, int j, uint32_t a, uint32_t b) {
  asm volatile("{\n.reg .pred p, q, e;\n.reg .b64 x, ad;\n" SA("%3", "%8") GADDR("%0", "%1", "%2")
               "setp.lt.s32 p, %4, %5;\nsetp.gt.s32 q, %4, %5;\nsetp.eq.s32 e, %4, %5;\nmov.b64 x, {%6,%7};\n"
               "@p st.relaxed.gpu.global.b64 [ad+-1024], x;\n@q st.relaxed.gpu.global.b64 [ad], x;\n@e st.shared.v2.u32 [sa], {%6,%7};\n}"
               ::"l"(ub), "r"(off), "l"((uint64_t)imm), "r"(sm), "r"(i), "r"(j), "r"(a), "r"(b), "r"(win()) : "memory");
}
__device__ __forceinline__ uint4 ldg_line(const void* p) {
  uint4 v; asm volatile("ld.global.nc.L2::128B.v4.u32 {%0,%1,%2,%3}, [%4];" : "=r"(v.x), "=r"(v.y), "=r"(v.z), "=r"(v.w) : "l"(p)); return v;
}
__device__ __forceinline__ void stg4(void* ub, uint32_t off, uint32_t imm, uint32_t v) {
  asm volatile("{\n.reg .b64 ad;\n" GADDR("%0", "%1", "%2") "st.global.u32 [ad], %3;\n}" ::"l"(ub), "r"(off), "l"((uint64_t)imm), "r"(v) : "memory");
}
__device__ __forceinline__ uint32_t tid_() { uint32_t t; asm volatile("mov.u32 %0, %%tid.x;" : "=r"(t)); return t & 127; }
__device__ __forceinline__ uint32_t nz(uint32_t w) { return max(w, 1u); }
__device__ __forceinline__ void mma16816(float (&c)[4], uint32_t a0, uint32_t a1, uint32_t a2, uint32_t a3, uint32_t b0, uint32_t b1) {
  asm("mma.sync.aligned.m16n8k16.row.col.f32.bf16.bf16.f32 {%0,%1,%2,%3}, {%4,%5,%6,%7}, {%8,%9}, {%0,%1,%2,%3};"
               : "+f"(c[0]), "+f"(c[1]), "+f"(c[2]), "+f"(c[3]) : "r"(a0), "r"(a1), "r"(a2), "r"(a3), "r"(b0), "r"(b1));
}
__device__ __forceinline__ void mma1688(float (&c)[4], uint32_t a0, uint32_t a1, uint32_t b0) {
  asm("mma.sync.aligned.m16n8k8.row.col.f32.bf16.bf16.f32 {%0,%1,%2,%3}, {%4,%5}, {%6}, {%0,%1,%2,%3};"
               : "+f"(c[0]), "+f"(c[1]), "+f"(c[2]), "+f"(c[3]) : "r"(a0), "r"(a1), "r"(b0));
}
__device__ __forceinline__ float ex2(float x) { float r; asm("ex2.approx.ftz.f32 %0, %1;" : "=f"(r) : "f"(x)); return r; }
__device__ __forceinline__ float quad_sum(float v) { v += __shfl_xor_sync(0xffffffffu, v, 1); v += __shfl_xor_sync(0xffffffffu, v, 2); return v; }
__device__ __forceinline__ float quad_max(float v) { v = fmaxf(v, __shfl_xor_sync(0xffffffffu, v, 1)); v = fmaxf(v, __shfl_xor_sync(0xffffffffu, v, 2)); return v; }

__device__ __forceinline__ void wgmma_rs_n64(float (&d)[32], uint32_t a0, uint32_t a1, uint32_t a2, uint32_t a3, uint64_t desc, int scale_d) {
  asm volatile("{\n.reg .pred p;\nsetp.ne.b32 p, %37, 0;\n"
    "wgmma.mma_async.sync.aligned.m64n64k16.f32.bf16.bf16 "
    "{%0, %1, %2, %3, %4, %5, %6, %7, %8, %9, %10, %11, %12, %13, %14, %15, %16, %17, %18, %19, %20, %21, %22, %23, %24, %25, %26, %27, %28, %29, %30, %31}, "
    "{%32, %33, %34, %35}, %36, p, 1, 1, 1;\n}\n"
    : "+f"(d[0]), "+f"(d[1]), "+f"(d[2]), "+f"(d[3]), "+f"(d[4]), "+f"(d[5]), "+f"(d[6]), "+f"(d[7]), "+f"(d[8]), "+f"(d[9]), "+f"(d[10]), "+f"(d[11]), "+f"(d[12]), "+f"(d[13]), "+f"(d[14]), "+f"(d[15]), "+f"(d[16]), "+f"(d[17]), "+f"(d[18]), "+f"(d[19]), "+f"(d[20]), "+f"(d[21]), "+f"(d[22]), "+f"(d[23]), "+f"(d[24]), "+f"(d[25]), "+f"(d[26]), "+f"(d[27]), "+f"(d[28]), "+f"(d[29]), "+f"(d[30]), "+f"(d[31])
    : "r"(a0), "r"(a1), "r"(a2), "r"(a3), "l"(desc), "r"(scale_d));
}

__device__ __forceinline__ void wgmma_rs_n72(float (&d)[36], uint32_t a0, uint32_t a1, uint32_t a2, uint32_t a3, uint64_t desc, int scale_d) {
  asm volatile("{\n.reg .pred p;\nsetp.ne.b32 p, %41, 0;\n"
    "wgmma.mma_async.sync.aligned.m64n72k16.f32.bf16.bf16 "
    "{%0, %1, %2, %3, %4, %5, %6, %7, %8, %9, %10, %11, %12, %13, %14, %15, %16, %17, %18, %19, %20, %21, %22, %23, %24, %25, %26, %27, %28, %29, %30, %31, %32, %33, %34, %35}, "
    "{%36, %37, %38, %39}, %40, p, 1, 1, 1;\n}\n"
    : "+f"(d[0]), "+f"(d[1]), "+f"(d[2]), "+f"(d[3]), "+f"(d[4]), "+f"(d[5]), "+f"(d[6]), "+f"(d[7]), "+f"(d[8]), "+f"(d[9]), "+f"(d[10]), "+f"(d[11]), "+f"(d[12]), "+f"(d[13]), "+f"(d[14]), "+f"(d[15]), "+f"(d[16]), "+f"(d[17]), "+f"(d[18]), "+f"(d[19]), "+f"(d[20]), "+f"(d[21]), "+f"(d[22]), "+f"(d[23]), "+f"(d[24]), "+f"(d[25]), "+f"(d[26]), "+f"(d[27]), "+f"(d[28]), "+f"(d[29]), "+f"(d[30]), "+f"(d[31]), "+f"(d[32]), "+f"(d[33]), "+f"(d[34]), "+f"(d[35])
    : "r"(a0), "r"(a1), "r"(a2), "r"(a3), "l"(desc), "r"(scale_d));
}

__device__ __forceinline__ void wgmma_rs_n128(float (&d)[64], uint32_t a0, uint32_t a1, uint32_t a2, uint32_t a3, uint64_t desc, int scale_d) {
  asm volatile("{\n.reg .pred p;\nsetp.ne.b32 p, %69, 0;\n"
    "wgmma.mma_async.sync.aligned.m64n128k16.f32.bf16.bf16 "
    "{%0, %1, %2, %3, %4, %5, %6, %7, %8, %9, %10, %11, %12, %13, %14, %15, %16, %17, %18, %19, %20, %21, %22, %23, %24, %25, %26, %27, %28, %29, %30, %31, %32, %33, %34, %35, %36, %37, %38, %39, %40, %41, %42, %43, %44, %45, %46, %47, %48, %49, %50, %51, %52, %53, %54, %55, %56, %57, %58, %59, %60, %61, %62, %63}, "
    "{%64, %65, %66, %67}, %68, p, 1, 1, 1;\n}\n"
    : "+f"(d[0]), "+f"(d[1]), "+f"(d[2]), "+f"(d[3]), "+f"(d[4]), "+f"(d[5]), "+f"(d[6]), "+f"(d[7]), "+f"(d[8]), "+f"(d[9]), "+f"(d[10]), "+f"(d[11]), "+f"(d[12]), "+f"(d[13]), "+f"(d[14]), "+f"(d[15]), "+f"(d[16]), "+f"(d[17]), "+f"(d[18]), "+f"(d[19]), "+f"(d[20]), "+f"(d[21]), "+f"(d[22]), "+f"(d[23]), "+f"(d[24]), "+f"(d[25]), "+f"(d[26]), "+f"(d[27]), "+f"(d[28]), "+f"(d[29]), "+f"(d[30]), "+f"(d[31]), "+f"(d[32]), "+f"(d[33]), "+f"(d[34]), "+f"(d[35]), "+f"(d[36]), "+f"(d[37]), "+f"(d[38]), "+f"(d[39]), "+f"(d[40]), "+f"(d[41]), "+f"(d[42]), "+f"(d[43]), "+f"(d[44]), "+f"(d[45]), "+f"(d[46]), "+f"(d[47]), "+f"(d[48]), "+f"(d[49]), "+f"(d[50]), "+f"(d[51]), "+f"(d[52]), "+f"(d[53]), "+f"(d[54]), "+f"(d[55]), "+f"(d[56]), "+f"(d[57]), "+f"(d[58]), "+f"(d[59]), "+f"(d[60]), "+f"(d[61]), "+f"(d[62]), "+f"(d[63])
    : "r"(a0), "r"(a1), "r"(a2), "r"(a3), "l"(desc), "r"(scale_d));
}

__device__ __forceinline__ void wgmma_rs_n144(float (&d)[72], uint32_t a0, uint32_t a1, uint32_t a2, uint32_t a3, uint64_t desc, int scale_d) {
  asm volatile("{\n.reg .pred p;\nsetp.ne.b32 p, %77, 0;\n"
    "wgmma.mma_async.sync.aligned.m64n144k16.f32.bf16.bf16 "
    "{%0, %1, %2, %3, %4, %5, %6, %7, %8, %9, %10, %11, %12, %13, %14, %15, %16, %17, %18, %19, %20, %21, %22, %23, %24, %25, %26, %27, %28, %29, %30, %31, %32, %33, %34, %35, %36, %37, %38, %39, %40, %41, %42, %43, %44, %45, %46, %47, %48, %49, %50, %51, %52, %53, %54, %55, %56, %57, %58, %59, %60, %61, %62, %63, %64, %65, %66, %67, %68, %69, %70, %71}, "
    "{%72, %73, %74, %75}, %76, p, 1, 1, 1;\n}\n"
    : "+f"(d[0]), "+f"(d[1]), "+f"(d[2]), "+f"(d[3]), "+f"(d[4]), "+f"(d[5]), "+f"(d[6]), "+f"(d[7]), "+f"(d[8]), "+f"(d[9]), "+f"(d[10]), "+f"(d[11]), "+f"(d[12]), "+f"(d[13]), "+f"(d[14]), "+f"(d[15]), "+f"(d[16]), "+f"(d[17]), "+f"(d[18]), "+f"(d[19]), "+f"(d[20]), "+f"(d[21]), "+f"(d[22]), "+f"(d[23]), "+f"(d[24]), "+f"(d[25]), "+f"(d[26]), "+f"(d[27]), "+f"(d[28]), "+f"(d[29]), "+f"(d[30]), "+f"(d[31]), "+f"(d[32]), "+f"(d[33]), "+f"(d[34]), "+f"(d[35]), "+f"(d[36]), "+f"(d[37]), "+f"(d[38]), "+f"(d[39]), "+f"(d[40]), "+f"(d[41]), "+f"(d[42]), "+f"(d[43]), "+f"(d[44]), "+f"(d[45]), "+f"(d[46]), "+f"(d[47]), "+f"(d[48]), "+f"(d[49]), "+f"(d[50]), "+f"(d[51]), "+f"(d[52]), "+f"(d[53]), "+f"(d[54]), "+f"(d[55]), "+f"(d[56]), "+f"(d[57]), "+f"(d[58]), "+f"(d[59]), "+f"(d[60]), "+f"(d[61]), "+f"(d[62]), "+f"(d[63]), "+f"(d[64]), "+f"(d[65]), "+f"(d[66]), "+f"(d[67]), "+f"(d[68]), "+f"(d[69]), "+f"(d[70]), "+f"(d[71])
    : "r"(a0), "r"(a1), "r"(a2), "r"(a3), "l"(desc), "r"(scale_d));
}

template <int N> struct WG;
template <> struct WG<64>  { static __device__ __forceinline__ void f(float (&d)[32], const uint32_t* a, uint64_t ds, int s) { wgmma_rs_n64(d, a[0], a[1], a[2], a[3], ds, s); } };
template <> struct WG<72>  { static __device__ __forceinline__ void f(float (&d)[36], const uint32_t* a, uint64_t ds, int s) { wgmma_rs_n72(d, a[0], a[1], a[2], a[3], ds, s); } };
template <> struct WG<128> { static __device__ __forceinline__ void f(float (&d)[64], const uint32_t* a, uint64_t ds, int s) { wgmma_rs_n128(d, a[0], a[1], a[2], a[3], ds, s); } };
template <> struct WG<144> { static __device__ __forceinline__ void f(float (&d)[72], const uint32_t* a, uint64_t ds, int s) { wgmma_rs_n144(d, a[0], a[1], a[2], a[3], ds, s); } };

constexpr uint64_t DESC_SW128 = ((uint64_t)(8192 >> 4) << 16) | ((uint64_t)(1024 >> 4) << 32) | (1ull << 62);
constexpr uint64_t DESC_KV = ((uint64_t)(128 >> 4) << 16) | ((uint64_t)(768 >> 4) << 32);
constexpr uint64_t DESC_Q = ((uint64_t)(128 >> 4) << 16) | ((uint64_t)(1536 >> 4) << 32);

template <int V> struct IntC { static constexpr int value = V; };
enum { PS_KV, PS_Q, PS_WO, PS_FF };
template <int PS> __host__ __device__ constexpr int pass_slot(int i) {
  return PS == PS_KV ? (i < 3 ? 9 + i : i - 3) : PS == PS_WO ? 6 + i : i;
}

__device__ __forceinline__ void load_frag(uint32_t (&a)[144], int i, const uint8_t* sb, uint32_t uo, uint32_t t) {
  if (i < 32) ld16(&a[4 * i], sb, uo + t * 16, i * 2048);
  else { ld8(&a[4 * i], sb, uo + t * 8, i * 2048); ld8(&a[4 * i + 2], sb, uo + t * 8, i * 2048 + 1024); }
}
__device__ __forceinline__ void store_own(const uint32_t (&y)[18], uint8_t* sb, uint32_t uo, int j, uint32_t t) {
  t += j * 128;
#pragma unroll
  for (int i = 0; i < 4; i++) st16(sb, uo + t * 16, i * 16384, nz(y[4 * i]), y[4 * i + 1], y[4 * i + 2], y[4 * i + 3]);
  st8(sb, uo + t * 8, 65536, nz(y[16]), y[17]);
}
__device__ __forceinline__ void load_own(uint32_t* y, const uint8_t* sb, uint32_t uo, int j) {
  const uint32_t t = tid_() + j * 128;
#pragma unroll
  for (int i = 0; i < 4; i++) ld16(&y[4 * i], sb, uo + t * 16, i * 16384);
  ld8(&y[16], sb, uo + t * 8, 65536);
}

struct NoTail { __device__ __forceinline__ void operator()() const {} };
template <int N, int PS, int KPS, int KSTEP, int CHK, bool SUB, bool HREL = false, class Tail = NoTail>
__device__ __forceinline__ void mma_pass(float (&acc)[N / 2], uint32_t (&a)[144], uint64_t desc, uint32_t par, const Rel& rel, int bar_id,
                                         const uint8_t* sb = nullptr, uint32_t uo = 0, uint32_t flag = 0, uint32_t m0 = 0, uint32_t m1 = 0, uint32_t park = 0, Tail tail = Tail()) {
  constexpr int NS = 36 / KPS;
  auto check = [&](int lo, int hi, uint32_t m0_) {
    while (true) {
      uint32_t m = m0_;
#pragma unroll
      for (int i = hi - 1; i >= lo; i--) m = min(m, i < 32 ? a[4 * i] : min(a[4 * i], a[4 * i + 2]));
      if (!__any_sync(0xffffffffu, (m | flag) == 0)) break;
      const uint32_t t = tid_();
#pragma unroll
      for (int i = lo; i < hi; i++) load_frag(a, i, sb, uo, t);
    }
  };
#pragma unroll
  for (int s = 0; s < NS; s++) {
    const int sl = pass_slot<PS>(s);
    if (CHK && s == 0 && !SUB) check(0, CHK * KPS, ~0u);
    if (CHK && s == CHK) check(CHK * KPS, 36, lds32(SM_EPOCH) | 1);
    if (SUB) {
#pragma unroll
      for (int i = s * KPS * 4; i < (s + 1) * KPS * 4; i += 2) { a[i] = bf2_sub(a[i], m0); a[i + 1] = bf2_sub(a[i + 1], m1); }
    }
    if (PS == PS_KV && s == 0) sts128(park + tid_() * 16, a[0], a[1], a[2], a[3]);
    mbar_wait(bar_full(sl), sl < 9 ? par : par ^ 1);
    wg_fence();
#pragma unroll
    for (int kk = 0; kk < KPS; kk++)
      WG<N>::f(acc, &a[(s * KPS + kk) * 4], desc + ((slot_addr(sl) + kk * KSTEP) >> 4), (s | kk) ? 1 : 0);
    wg_commit();
    if (s == (PS == PS_KV ? KV_LEAD : NS - 1) && bar_id >= 0) bar_arrive(bar_id, 256);
    if (s > 0) {
      wg_wait<1>();
      if (!(PS == PS_WO && s > 3)) rel(pass_slot<PS>(s - 1));
    }
    if (HREL && s == 3 && flag) {
#pragma unroll
      for (int i = 0; i < 12; i++) ld16(&a[4 * i], sb, uo, (i >> 2) * TILE + (i & 3) * 2048);
    }
  }
  tail();
  wg_wait<0>();
  if (PS != PS_WO) rel(pass_slot<PS>(NS - 1));
}

template <int NF, int N0 = 0> __device__ __forceinline__ void load_frags(uint32_t (&a)[144], const uint8_t* sb, uint32_t uo, uint32_t t) {
#pragma unroll
  for (int i = N0; i < NF; i++) load_frag(a, i, sb, uo, t);
}
__device__ __forceinline__ void ln_scalars(float s1, float s2, uint32_t& m, float& var, uint32_t zero) {
  const float mean = s1 * (1.f / DM);
  var = s2 * (1.f / DM) - mean * mean;
  m = pack_bf16(mean, mean) ^ (__float_as_uint(var) & zero);
}
__device__ __forceinline__ float ln_rstd(float var, float after, uint32_t zero) {
  var = __uint_as_float(__float_as_uint(var) ^ (__float_as_uint(after) & zero));
  float sd, r;
  asm("sqrt.approx.ftz.f32 %0, %1;" : "=f"(sd) : "f"(bf_round(bf_round(fmaxf(var, 0.f)) + 1e-5f)));
  asm("rcp.approx.ftz.f32 %0, %1;" : "=f"(r) : "f"(bf_round(sd)));
  return r;
}
template <int NF> __device__ __forceinline__ void gather_ln(uint32_t (&a)[144], const uint8_t* sb, uint32_t uo, uint32_t sto,
                                          uint32_t& m0, uint32_t& m1, float& r0, float& r1, uint32_t zero) {
  uint32_t u[32];
  const uint32_t t = tid_(), so = sto + (t >> 5) * 1024 + (t & 28) * 4;
#pragma unroll
  for (int i = 0; i < 8; i++) ld16(&u[4 * i], sb, so, OFF_ST + i * 128);
  load_frags<36>(a, sb, uo, t);
  while (true) {
    uint32_t m = a[4 * NF - 4];
#pragma unroll
    for (int i = NF - 2; i >= 0; i--) m = min(m, a[4 * i]);
#pragma unroll
    for (int i = 0; i < 8; i++) m = min(m, u[4 * i]);
    if (!__any_sync(0xffffffffu, m == 0)) break;
#pragma unroll
    for (int i = 0; i < 8; i++) ld16(&u[4 * i], sb, so, OFF_ST + i * 128);
    load_frags<NF>(a, sb, uo, t);
  }
  float v[4];
#pragma unroll
  for (int k = 0; k < 4; k++)
    v[k] = ((__uint_as_float(u[k]) + __uint_as_float(u[4 + k])) + (__uint_as_float(u[8 + k]) + __uint_as_float(u[12 + k]))) +
           ((__uint_as_float(u[16 + k]) + __uint_as_float(u[20 + k])) + (__uint_as_float(u[24 + k]) + __uint_as_float(u[28 + k])));
  ln_scalars(v[1], v[0], m0, r0, zero); ln_scalars(v[3], v[2], m1, r1, zero);
}
struct Stats {
  float s[4] = {0, 0, 0, 0}, d0[4] = {0, 0, 0, 0}, d1[4] = {0, 0, 0, 0};
  __device__ __forceinline__ void add16(const uint32_t* f) {
    mma16816(s, f[0], f[1], f[2], f[3], 0x3f803f80u, 0x3f803f80u);
    mma16816(d0, f[0], f[1], f[2], f[3], f[0], f[2]);
    mma16816(d1, f[0], f[1], f[2], f[3], f[1], f[3]);
  }
  __device__ __forceinline__ float sq0(int g) const { return (g & 1) ? d0[1] : d0[0]; }
  __device__ __forceinline__ float sq1(int g) const { return (g & 1) ? d1[3] : d1[2]; }
};
struct RowStats {
  float s[4] = {0, 0, 0, 0}, u[4] = {0, 0, 0, 0};
  template <int N> __device__ __forceinline__ void add(const uint32_t* y) {
#pragma unroll
    for (int i = 0; i < N; i++) {
      const float lo = bf_lo(y[i]), hi = bf_hi(y[i]);
      const int r = (i & 1) * 2;
      s[r] = fmaf(lo, lo, s[r]); u[r] = fmaf(hi, hi, u[r]); s[r + 1] += lo; u[r + 1] += hi;
    }
  }
  __device__ __forceinline__ uint32_t fold() {
    uint32_t x = 0;
#pragma unroll
    for (int i = 0; i < 4; i++) { s[i] += u[i]; u[i] = 0; x |= __float_as_uint(s[i]); }
    return x;
  }
  __device__ __forceinline__ void store(uint8_t* sb, uint32_t sto, uint32_t t) {
    fold();
#pragma unroll
    for (int i = 0; i < 4; i++) s[i] += __shfl_xor_sync(0xffffffffu, s[i], 1);
#pragma unroll
    for (int i = 0; i < 4; i++) s[i] += __shfl_xor_sync(0xffffffffu, s[i], 2);
    if ((t & 3) == 0) st16(sb, sto + (t >> 5) * 1024 + (t & 28) * 4, OFF_ST, __float_as_uint(s[0]) | 1u, __float_as_uint(s[1]), __float_as_uint(s[2]), __float_as_uint(s[3]));
  }
};
__device__ __forceinline__ void reduce4(const uint32_t* f, uint32_t* y) {
#pragma unroll
  for (int i = 0; i < 4; i++) {
    float lo = bf_lo(f[i]), hi = bf_hi(f[i]);
#pragma unroll
    for (int s = 1; s < 8; s++) { lo += bf_lo(f[4 * s + i]); hi += bf_hi(f[4 * s + i]); }
    y[i] = pack_bf16(lo, hi);
  }
}

#define TS(i) do {} while (0)
#define TSP(i) do {} while (0)
#define TSH(i) do {} while (0)

__host__ __device__ constexpr int role_j(int c) {
  return MAP == 0 ? (MC ? (c >> 1) & 7 : c & 7) : MAP == 1 ? c >> 4 : MAP == 2 ? ((c >> 6) << 2) | ((c >> 1) & 3)
       : MAP == 3 ? ((c >> 5) << 1) | ((c >> 2) & 1) : ((c >> 3) & 3) * 2 + ((c >> 2) & 1);
}
__host__ __device__ constexpr int role_rb(int c) {
  return MAP == 0 ? (MC ? (c >> 4) * 2 + (c & 1) : c >> 3) : MAP == 1 ? c & 15 : MAP == 2 ? ((c >> 3) & 7) * 2 + (c & 1)
       : MAP == 3 ? ((c >> 3) & 3) * 4 + (c & 3) : (c >> 5) * 4 + (c & 3);
}

__device__ __forceinline__ uint32_t row_off(int rb, int wg, uint32_t t) { return (rb * 128 + wg + ((t >> 5) * 16 + (t & 15)) * 2) * (2 * DM); }

__device__ __forceinline__ const __nv_bfloat16* wo_src(const __nv_bfloat16* wo, int k, int u, int j) {
  const int ko = k < 512 ? ((k >> 4) & 7) * 72 + (k >> 7) * 16 + (k & 15) : ((k >> 3) & 7) * 72 + 64 + (k & 7);
  return wo + ko * 576 + (u < 8 ? (u >> 1) * 128 + j * 16 + (u & 1) * 8 : 512 + j * 8);
}

struct Params {
  const __nv_bfloat16 *x, *wqkv, *wo, *wg, *wu, *wd;
  __nv_bfloat16* out;
  uint8_t* scr;
  uint8_t* times;
  unsigned zero;
};

__device__ __forceinline__ void tma_prefetch(const CUtensorMap* m, int c0, int c1) {
  asm volatile("cp.async.bulk.prefetch.tensor.2d.L2.global [%0, {%1, %2}];" ::"l"(m), "r"(c0), "r"(c1) : "memory");
}
__device__ __forceinline__ void fill_packed(int sl, uint32_t par, const uint8_t* src, uint32_t rank, uint32_t own) {
  mbar_wait(bar_empty(sl), par);
  mbar_expect_tx(bar_full(sl), PSLOT);
  if (MC) bulk_load_mc(own + slot_addr(sl) + rank * (PSLOT / 2), src + rank * (PSLOT / 2), PSLOT / 2, own + bar_full(sl));
  else bulk_load(slot_addr(sl), src, PSLOT, bar_full(sl));
}

__global__ void __launch_bounds__(384, 1)
fused_kernel(const __grid_constant__ CUtensorMap map_x, const __grid_constant__ CUtensorMap map_wg,
             const __grid_constant__ CUtensorMap map_wu, const __grid_constant__ CUtensorMap map_wd, const Params P) {
  const int wg = __shfl_sync(0xffffffffu, threadIdx.x >> 7, 0);
  const int cta = blockIdx.x, rank = MC ? cta & 1 : 0, j = role_j(cta), rb = role_rb(cta);
  const uint32_t own = win();
  unsigned* const flags = (unsigned*)(P.scr + OFF_FLAGS);
  if (__shfl_sync(0xffffffffu, threadIdx.x >> 5, 0) == 11) {
    if (threadIdx.x == 352) {
#pragma unroll
      for (int i = 0; i < 14; i++) { mbar_init(bar_full(i), 1); mbar_init(bar_empty(i), MC && i < 12 ? 4 : 2); }
      mbar_init(bar_full(14), 1); mbar_init(bar_empty(14), 1);
      asm volatile("fence.mbarrier_init.release.cluster;" ::: "memory");
      if (smem_u32(smem_raw) != own + SB) asm volatile("trap;");
    }
    __syncwarp();
    bar_arrive(0, 384);
    if (MC) asm volatile("barrier.cluster.arrive.relaxed.aligned;" ::: "memory");
    if (threadIdx.x == 352) {
#pragma unroll 1
      for (int c = 0; c < 9; c++) {
        mbar_expect_tx(bar_full(c), SLOT);
        tma_3d(own + slot_addr(c), &map_x, c * 64, rb * 64, 0, own + bar_full(c));
      }
    }
  } else {
    const bool on = threadIdx.x < 324;
    const int k = rb * 36 + (on ? threadIdx.x / 36 : 0) * 4 + (threadIdx.x & 3), u = (threadIdx.x % 36) >> 2;
    const uint4* s = (const uint4*)(P.wqkv + k * 1728 + j * 72 + u * 8);
    const uint4 vk = ldg_line(s + 72), vv = ldg_line(s + 144);
    const unsigned ep0 = *(volatile unsigned*)&flags[(72 + cta) * 8];
    if (MC) asm volatile("barrier.cluster.arrive.relaxed.aligned;" ::: "memory");
    bar_sync(0, 384);
    uint8_t* d = P.scr + OFF_WPACK + j * 24 * PSLOT;
    if (on) {
      const uint32_t dkv = (k / 48) * PSLOT + u * 768 + (k % 48) * 16;
      st16(d, dkv, 0, vk.x, vk.y, vk.z, vk.w);
      st16(d, dkv, 9 * 768, vv.x, vv.y, vv.z, vv.w);
    }
    asm volatile("fence.proxy.async.global;" ::: "memory");
    bar_arrive(NB_PUB + 3, 384);
    if (threadIdx.x == 351) sts32(SM_EPOCH, ep0);
    if (wg == 2) bar_sync(NB_PUB + 1, 96);
  }
  __syncwarp();
  if (MC) asm volatile("barrier.cluster.wait.acquire.aligned;" ::: "memory");

  if (wg == 2) {
    asm volatile("setmaxnreg.dec.sync.aligned.u32 24;");
    const int pw = __shfl_sync(0xffffffffu, (threadIdx.x >> 5) & 3, 0), lane = threadIdx.x & 31;
    auto tile_col = [](int t, int j) { return t < 9 ? j * 576 + t * 64 : t == 9 ? 512 : (t - 10) * 128; };
    auto prefetch_tile = [&](int t) {
#pragma unroll 1
      for (int b = rb; b < 18; b += 16) {
        const int h = b & 1, k = b >> 1;
        if (t < 9) tma_prefetch(h ? &map_wu : &map_wg, tile_col(t, j), k * 64);
        else if (t != 9 || !h) tma_prefetch(&map_wd, tile_col(t, j) + h * 64, j * 576 + k * 64);
      }
    };
    if (pw == 0) {
      if (lane == 0) {
        flag_wait(&flags[j * 8], (lds32(SM_EPOCH) + 1) * 16);
        TSP(7);
        asm volatile("fence.proxy.async.global;" ::: "memory");
        const uint8_t* wp = P.scr + OFF_WPACK + j * 24 * PSLOT;
#pragma unroll 1
        for (int s = 0; s < 3; s++) fill_packed(9 + s, 1, wp + s * PSLOT, rank, own);
#pragma unroll 1
        for (int L = 0; L < 2; L++) {
#pragma unroll 1
          for (int s = 0; s < 21; s++) {
            if (s == 9 && L == 0) { flag_wait(&flags[(56 + j) * 8], (lds32(SM_EPOCH) + 1) * 16); asm volatile("fence.proxy.async.global;" ::: "memory"); }
            fill_packed(s < 9 ? s : s - 9, s >= 9 && s < 18, wp + (s + 3) * PSLOT, rank, own);
          }
#pragma unroll 1
          for (int t = 0; t < 14; t++) {
            const int p = t - 9;
            const CUtensorMap* ma = p < 0 ? &map_wg : &map_wd;
            const CUtensorMap* mb = p < 0 ? &map_wu : &map_wd;
            const int ca = tile_col(t, j), cb = p < 0 ? ca : ca + 64, r0 = p < 0 ? 0 : j * 576;
            if (L * 14 + t + PF_AHEAD < 28) prefetch_tile((t + PF_AHEAD) % 14);
#pragma unroll 1
            for (int k = 0; k < 9; k++) {
              if (TH && t == 0 && k >= TH && k < 6) { mbar_wait(bar_full(k - TH), 1); for (int i = 0; i < THD; i++) __nanosleep(0); }
              mbar_wait(bar_empty(k), t & 1);
              mbar_expect_tx(bar_full(k), p == 0 ? 8192 : SLOT);
              const int r = r0 + (p < 0 || k == 8 ? k : k < 3 ? k + 5 : k - 3) * 64;
              if (MC) {
                if (p != 0) tma_2d_mc(own + slot_addr(k) + rank * 8192, rank ? mb : ma, rank ? cb : ca, r, own + bar_full(k));
                else if ((k & 1) == rank) tma_2d_mc(own + slot_addr(k), ma, ca, r, own + bar_full(k));
              } else {
                tma_2d(slot_addr(k), ma, ca, r, bar_full(k));
                if (p != 0) tma_2d(slot_addr(k) + 8192, mb, cb, r, bar_full(k));
              }
            }
            if (p == 1 && L == 0) {
              l2_prefetch(wp + rb * (24 * PSLOT / 16), 24 * PSLOT / 16);
#pragma unroll 1
              for (int s = 0; s < 3; s++) fill_packed(9 + s, 1, wp + s * PSLOT, rank, own);
            }
          }
        }
        flags[(72 + cta) * 8] = lds32(SM_EPOCH) + 1;
      }
    } else if (pw < 3) {
      const int hw = pw - 1;
      const uint32_t ep = __shfl_sync(0xffffffffu, lds32(SM_EPOCH), 0);
      uint8_t* const sb = P.scr + (rb * 2 + hw) * STRM;
      const uint32_t xs = slot_addr(12) + hw * SLOT, fb = bar_full(12) + hw * 8;
      uint32_t hph = 0;
#pragma unroll 1
      for (int L = 0; L < 2; L++) {
        const uint32_t tag = ep * 2 + L + 1;
        bar_sync(NB_FREE + hw, 160);
        if (rb > 0) hint_wait(sb + OFF_HINT + 512 + j * 128, tag);
        uint32_t bad;
        do {
          if (rb > 0) {
            if (lane == 0) {
              mbar_expect_tx(bar_full(14) + hw * 128, 3072);
              bulk_load(own + ytail(hw * 2), sb + OFF_HALO + (L * 8 + j) * 3072, 1536, own + bar_full(14) + hw * 128);
              bulk_load(own + ytail(hw * 2 + 1), sb + OFF_HALO + (L * 8 + j) * 3072 + 1536, 1536, own + bar_full(14) + hw * 128);
            }
            mbar_wait(bar_full(14) + hw * 128, hph);
            hph ^= 1;
          }
          bad = 0;
#pragma unroll 1
          for (int c = 0; c < 3; c++) {
            uint32_t u[4] = {tag, 0, 0, 0}, v[4] = {tag, 0, 0, 0};
            if (rb > 0) { lds128(u, ytail(hw * 2) + c * 512 + lane * 16); lds128(v, ytail(hw * 2 + 1) + c * 512 + lane * 16); }
            bad |= (u[0] ^ tag) | (v[0] ^ tag);
#pragma unroll
            for (int i = 0; i < 3; i++) { sts32(xs + KSTG + (c * 3 + i) * 128 + lane * 4, u[i + 1]); sts32(xs + (c * 3 + i) * 128 + lane * 4, v[i + 1]); }
          }
        } while (__any_sync(0xffffffffu, bad != 0));
        bar_arrive(NB_HALO + hw, 160);
#pragma unroll 1
        for (int p = 0; p < 4; p++) {
          if (L == 0 && p == 3) flag_wait(flags + (40 + rb) * 8, (ep + 1) * 8);
          bar_sync(NB_FREE + hw, 160);
          TSH(L * 12 + p * 3);
          hint_wait(sb + OFF_HINT + (lane & 3) * 128, (ep * 15 + L * 8 + p + 3) * 8);
          TSH(L * 12 + p * 3 + 1);
          if (lane == 0) {
            mbar_expect_tx(fb, p ? PBUF : PBUF / 2);
            bulk_load(own + xs, sb + OFF_P + j * PSRC + (p ? (p == 2) * PBUF : 2 * PBUF), p ? PBUF : PBUF / 2, own + fb);
          }
          TSH(L * 12 + p * 3 + 2);
        }
      }
    } else {
      auto clear = [&](int t) {
        const uint32_t so = rb * 2 * STRM + (threadIdx.x & 31) * 16;
#pragma unroll 1
        for (int i = 0; i < 18; i++) {
          st16(P.scr, so + t * TILE + j * 9216 + i * 512, 0, 0, 0, 0, 0);
          st16(P.scr, so + t * TILE + j * 9216 + i * 512, STRM, 0, 0, 0, 0);
          __nanosleep(0);
        }
        if (t != 1) {
          st16(P.scr, so + (t ? t - 1 : 0) * 4096 + j * 512, OFF_ST, 0, 0, 0, 0);
          st16(P.scr, so + (t ? t - 1 : 0) * 4096 + j * 512, OFF_ST + STRM, 0, 0, 0, 0);
        }
      };
      bar_sync(NB_PUB + 3, 384);
      if (lane == 0) flag_signal(&flags[j * 8]);
      TSP(5);
      bar_sync(NB_PUB + 2, 288);
      if (lane == 0) flag_signal(&flags[(56 + j) * 8]);
      TSP(4);
      if (lane == 0) {
#pragma unroll 1
        for (int t = 0; t < PF_AHEAD; t++) prefetch_tile(t);
      }
      __syncwarp();
#pragma unroll 1
      for (int L = 0; L < 2; L++) {
        timed_wait(bar_empty(13), L);
#pragma unroll 1
        for (int t = L ^ 1; t < 4 - 2 * L; t++) clear(t);
        __syncwarp();
        if (lane == 0 && L == 0) flag_signal(flags + (40 + rb) * 8);
      }
      timed_wait(bar_empty(12), 0);
      if (MC) asm volatile("barrier.cluster.arrive.relaxed.aligned;\nbarrier.cluster.wait.aligned;" ::: "memory");
    }
  } else {
    asm volatile("setmaxnreg.inc.sync.aligned.u32 240;");
    const int w = __shfl_sync(0xffffffffu, (threadIdx.x >> 5) & 3, 0);
    const bool leader = (threadIdx.x & 127) == 0;
    const Rel rel{MC ? (threadIdx.x & 95) == 0 : leader, MC ? cta_window(w & 1) : 0};
    uint8_t* const sb = P.scr + (rb * 2 + wg) * STRM;
    uint8_t* const hint = sb + OFF_HINT + w * 128;
    auto hint_target = [](int e) { return (lds32(SM_EPOCH) * 15 + e + 1) * 8; };
    TS(0);
    uint32_t a[144];
#pragma unroll 1
    for (int L = 0; L < 2; L++) {
      uint32_t m0, m1; float r0, r1;
      if (L == 0) {
        Stats st;
        const int lane = tid_() & 31, g = lane >> 2;
        const int row = w * 16 + (lane & 15);
        const uint32_t ra = SB + wg * 8192 + row * 128;
        const uint32_t pt = tid_(), pu = (pt % 36) >> 2, pk = rb * 36 + (pt < 108 ? pt / 36 : 0) * 4 + (pt & 3);
        uint4 pv[3];
#pragma unroll
        for (int i = 0; i < 3; i++) pv[i] = ldg_line(wg ? wo_src(P.wo, pk + i * 12, pu, j) : P.wqkv + (pk + i * 12) * 1728 + j * 72 + pu * 8);
#pragma unroll
        for (int c = 0; c < 9; c++) {
          mbar_wait(bar_full(c), 0);
          if (c == 0) TS(60); if (c == 8) TS(62);
#pragma unroll
          for (int kk = 0; kk < 4; kk++) ldsm4(&a[c * 16 + kk * 4], ra + (((kk * 2 + (lane >> 4)) ^ (row & 7)) << 4) + c * SLOT);
          if (c == 8) {
            uint32_t y[18], z[4];
#pragma unroll
            for (int i = 0; i < 4; i++) ldsm4(&y[4 * i], ra + ((((j & 3) * 2 + (lane >> 4)) ^ (row & 7)) << 4) + (2 * i + (j >> 2)) * SLOT);
            ldsm4(z, ra + ((j ^ (row & 7)) << 4) + 8 * SLOT);
            y[16] = z[0]; y[17] = z[1];
            bar_sync(NB_WG + wg, 128);
#pragma unroll
            for (int i = 0; i < 9; i++) rel(i);
            if (pt < 108) {
#pragma unroll
              for (int i = 0; i < 3; i++) {
                const uint32_t k = pk + i * 12;
                st16(P.scr, (j * 24 + wg * 6 + k / 96) * PSLOT + pu * 1536 + (k % 96) * 16, OFF_WPACK + 12 * PSLOT, pv[i].x, pv[i].y, pv[i].z, pv[i].w);
              }
            }
            asm volatile("fence.proxy.async.global;" ::: "memory");
            bar_arrive(NB_PUB + 2, 288);
            store_own(y, sb, OFF_X2, j, tid_());
          }
#pragma unroll
          for (int kk = 0; kk < 4; kk++) st.add16(&a[c * 16 + kk * 4]);
        }
        const int dl = (lane & ~3) | (g >> 1);
        ln_scalars(st.s[0], __shfl_sync(0xffffffffu, st.sq0(g), dl), m0, r0, P.zero);
        ln_scalars(st.s[2], __shfl_sync(0xffffffffu, st.sq1(g), dl), m1, r1, P.zero);
      } else {
        hint_wait(hint, hint_target(7));
        TS(61);
        gather_ln<3 * D_KV>(a, sb, OFF_X2, 8192, m0, m1, r0, r1, P.zero);
      }
      TS(1 + L * 20);
      uint32_t kf[18], qf[18];
      {
        float acc[72];
        if (wg == 1) bar_sync(NB_ORD1, 256);
        mma_pass<144, PS_KV, 3, 256, D_KV, true>(acc, a, DESC_KV, 1, rel, wg == 0 ? NB_ORD1 : -1, sb, OFF_X2, L ^ 1, m0, m1, ytail(wg * 2));
        r0 = ln_rstd(r0, acc[0], P.zero); r1 = ln_rstd(r1, acc[0], P.zero);
        uint32_t vf[18];
#pragma unroll
        for (int c = 0; c < 9; c++) {
          kf[2 * c] = pack_bf16(acc[4 * c] * r0, acc[4 * c + 1] * r0);
          kf[2 * c + 1] = pack_bf16(acc[4 * c + 2] * r1, acc[4 * c + 3] * r1);
          vf[c] = pack_bf16(acc[36 + 4 * c] * r0, acc[36 + 4 * c + 1] * r0);
          vf[9 + c] = pack_bf16(acc[36 + 4 * c + 2] * r1, acc[36 + 4 * c + 3] * r1);
        }
        TS(2 + L * 20);
        const uint32_t l16 = (tid_() & 31) * 16, xs = slot_addr(12) + wg * SLOT + w * 1152;
#pragma unroll
        for (int i = 0; i < 4; i++) stsm4(xs + w * 1152 + 1152 + i * 512 + l16, vf[4 * i], vf[4 * i + 1], vf[4 * i + 2], vf[4 * i + 3]);
        sts32(xs + w * 1152 + 1152 + 2048 + l16 / 4, vf[16]); sts32(xs + w * 1152 + 1152 + 2176 + l16 / 4, vf[17]);
        if (w < 3) {
          stsm4(xs + KSTG + 1152 + l16, kf[1], kf[3], kf[5], kf[7]);
          stsm4(xs + KSTG + 1152 + 512 + l16, kf[9], kf[11], kf[13], kf[15]);
          sts32(xs + KSTG + 1152 + 1024 + l16 / 4, kf[17]);
        } else if (rb < 15) {
          const uint32_t tag = lds32(SM_EPOCH) * 2 + L + 1;
          const uint32_t ho = l16 + (L * 8 + j) * 3072;
#pragma unroll
          for (int c = 0; c < 3; c++) {
            st16(sb, ho, 2 * STRM + OFF_HALO + c * 512, tag, kf[6 * c + 1], kf[6 * c + 3], kf[6 * c + 5]);
            st16(sb, ho, 2 * STRM + OFF_HALO + 1536 + c * 512, tag, vf[9 + 3 * c], vf[10 + 3 * c], vf[11 + 3 * c]);
          }
          hint_post(sb + 2 * STRM + OFF_HINT + 512 + j * 128);
        }
      }
      lds128(a, ytail(wg * 2) + tid_() * 16);
      bar_arrive(NB_FREE + wg, 160);
      {
        float acc[36];
        if (wg == 1) bar_sync(NB_ORD1, 256);
        mma_pass<72, PS_Q, 6, 256, 0, false>(acc, a, DESC_Q, 0, rel, -1);
#pragma unroll
        for (int c = 0; c < 9; c++) {
          qf[2 * c] = pack_bf16(acc[4 * c] * r0, acc[4 * c + 1] * r0);
          qf[2 * c + 1] = pack_bf16(acc[4 * c + 2] * r1, acc[4 * c + 3] * r1);
        }
      }
      TS(3 + L * 20);
      uint32_t xr[18];
      {
        uint32_t kh[12], vt[28];
        const int tid = tid_(), g = (tid >> 2) & 7, q = tid & 3;
        bar_sync(NB_HALO + wg, 160);
        {
          const uint32_t xs = slot_addr(12) + wg * SLOT + w * 1152 + (tid & 31) * 16;
#pragma unroll
          for (int i = 0; i < 3; i++) ldsm4(&kh[4 * i], xs + KSTG + i * 512);
#pragma unroll
          for (int i = 0; i < 7; i++) ldsm4t(&vt[4 * i], xs + w * 1152 + i * 512);
        }
        TS(14 + L * 20);
        const bool nohalo = (rb == 0 && w == 0);
        const bool le0 = 2 * q <= g, le1 = 2 * q + 1 <= g;
        const uint32_t M = (le0 ? 0xffffu : 0u) | (le1 ? 0xffff0000u : 0u);
        const float sc = 0.23570226039551584f * 1.4426950408889634f;
        float l[16], t[8];
#pragma unroll
        for (int h = 0; h < 4; h++) {
          const uint32_t qa0 = q >= h ? qf[4 * h] : 0u, qa1 = q >= h ? qf[4 * h + 1] : 0u;
          const uint32_t qc0 = q <= h ? qf[4 * h + 4] : 0u, qc1 = q <= h ? qf[4 * h + 5] : 0u;
          float sm[4] = {0, 0, 0, 0}, s0[4] = {0, 0, 0, 0}, s1[4] = {0, 0, 0, 0};
          mma16816(s0, qa0, qa1, qf[4 * h + 2], qf[4 * h + 3], kf[4 * h], kf[4 * h + 2]);
          mma16816(s1, qa0, qa1, qf[4 * h + 2], qf[4 * h + 3], kf[4 * h + 1], kf[4 * h + 3]);
          mma16816(sm, qa0, qa1, qf[4 * h + 2], qf[4 * h + 3], kh[2 * h], kh[2 * h + 1]);
          mma1688(s0, qc0, qc1, kf[4 * h + 4]);
          mma1688(s1, qc0, qc1, kf[4 * h + 5]);
          mma1688(sm, qc0, qc1, kh[2 * h + 2]);
          if (nohalo) sm[0] = sm[1] = -1e9f / 0.23570226039551584f;
          l[4 * h] = le0 ? s0[0] : sm[0]; l[4 * h + 1] = le1 ? s0[1] : sm[1];
          l[4 * h + 2] = le0 ? s1[2] : s0[2]; l[4 * h + 3] = le1 ? s1[3] : s0[3];
        }
#pragma unroll
        for (int i = 0; i < 8; i++) t[i] = fmaxf(l[2 * i], l[2 * i + 1]);
#pragma unroll
        for (int i = 0; i < 8; i++) t[i] = fmaxf(t[i], __shfl_xor_sync(0xffffffffu, t[i], 1));
#pragma unroll
        for (int i = 0; i < 8; i++) t[i] = fmaxf(t[i], __shfl_xor_sync(0xffffffffu, t[i], 2)) * sc;
#pragma unroll
        for (int i = 0; i < 8; i++) { l[2 * i] = ex2(fmaf(l[2 * i], sc, -t[i])); l[2 * i + 1] = ex2(fmaf(l[2 * i + 1], sc, -t[i])); t[i] = l[2 * i] + l[2 * i + 1]; }
#pragma unroll
        for (int i = 0; i < 8; i++) t[i] += __shfl_xor_sync(0xffffffffu, t[i], 1);
#pragma unroll
        for (int i = 0; i < 8; i++) t[i] += __shfl_xor_sync(0xffffffffu, t[i], 2);
        uint32_t pf[16];
#pragma unroll
        for (int i = 0; i < 8; i++) {
          float r; asm("rcp.approx.ftz.f32 %0, %1;" : "=f"(r) : "f"(t[i]));
          const uint32_t p = pack_bf16(l[2 * i] * r, l[2 * i + 1] * r);
          pf[2 * i] = p & ~M; pf[2 * i + 1] = p & M;
        }
#pragma unroll
        for (int c = 0; c < 9; c++) {
          const int h = c == 8 ? 3 : c >> 1;
          float o[4] = {0, 0, 0, 0};
          mma16816(o, pf[4 * h], 0u, pf[4 * h + 1], pf[4 * h + 2], vt[c], vt[9 + c]);
          mma1688(o, 0u, pf[4 * h + 3], vt[18 + c]);
          if (c == 2 || c == 4 || c == 6) {
            float e[4] = {0, 0, 0, 0};
            mma16816(e, pf[4 * h - 4], 0u, pf[4 * h - 3], pf[4 * h - 2], vt[c], vt[9 + c]);
            mma1688(e, 0u, pf[4 * h - 1], vt[18 + c]);
            if (q < h) { o[0] = e[0]; o[1] = e[1]; o[2] = e[2]; o[3] = e[3]; }
          }
          qf[2 * c] = pack_bf16(o[0], o[1]); qf[2 * c + 1] = pack_bf16(o[2], o[3]);
        }
        store_own(qf, sb, OFF_O, j, tid);
        hint_post(hint);
        bar_arrive(NB_ORD1 - wg, 256);
        load_own(xr, sb, OFF_X2, j);
      }
      TS(4 + L * 20);
      {
        hint_wait(hint, hint_target(L * 8));
        TS(5 + L * 20);
        load_frags<N_WO>(a, sb, OFF_O, tid_());
        float acc[36];
        if (wg == 0) bar_sync(NB_ORD0, 256);
        load_frags<36, N_WO>(a, sb, OFF_O, tid_());
        TS(19 + L * 20);
        mma_pass<72, PS_WO, 6, 256, D_WO, false>(acc, a, DESC_Q, 0, rel, -1, sb, OFF_O);
        TS(6 + L * 20);
#pragma unroll
        for (int c = 0; c < 9; c++) {
          xr[2 * c] = bf2_add(xr[2 * c], pack_bf16(acc[4 * c], acc[4 * c + 1]));
          xr[2 * c + 1] = bf2_add(xr[2 * c + 1], pack_bf16(acc[4 * c + 2], acc[4 * c + 3]));
        }
        store_own(xr, sb, L * 3 * TILE, j, tid_());
        RowStats rs;
        rs.add<18>(xr);
        rs.store(sb, L * 4096 + j * 128, tid_());
        hint_post(hint);
      }
      TS(16 + L * 20);
      hint_wait(hint, hint_target(L * 8 + 1));
      TS(15 + L * 20);
      gather_ln<4 * D_T0>(a, sb, L * 3 * TILE, L * 4096, m0, m1, r0, r1, P.zero);
      TS(7 + L * 20);
      const uint32_t hb = (L ^ 1) * TILE + j * 9216;
      {
        float ka0, kb0, kc0, ka1, kb1, kc1;
        float acc[64];
        uint32_t hf[16];
        auto geglu = [&](auto chains, uint32_t hsm) {
          constexpr int CH = decltype(chains)::value;
          float r[32];
#pragma unroll
          for (int e = 0; e < 32; e++) {
            float x = acc[e];
            if (e >= CH) x = __uint_as_float(__float_as_uint(x) ^ (__float_as_uint(r[e - CH]) & P.zero));
            if (CH != 2 && e < 20) {
              const uint32_t ad = (e < 8 ? slot_addr(12) + e * 2048 + wg * 8192 : slot_addr(7 + (e >> 2)) + (e & 3) * 2048) + hsm;
              lds128(&a[48 + 4 * e], e >= CH ? ad ^ (__float_as_uint(r[e - CH]) & P.zero) : ad);
            }
            const bool hi = e & 2;
            float t = x * fmaf(x * x, hi ? kb1 : kb0, hi ? ka1 : ka0);
            asm("tanh.approx.f32 %0, %0;" : "+f"(t));
            const float u = x * acc[32 + e] * (hi ? kc1 : kc0);
            r[e] = fmaf(u, t, u);
            if (e & 1) hf[e >> 1] = pack_bf16(r[e - 1], r[e]);
          }
        };
        if (wg == 1) bar_sync(NB_ORD1, 256);
        mma_pass<128, PS_FF, 4, 2048, D_T0, true>(acc, a, DESC_SW128, 1, rel, NB_ORD1 - wg, sb, L * 3 * TILE, 0, m0, m1);
        TS(8 + L * 20);
        r0 = ln_rstd(r0, acc[0], P.zero); r1 = ln_rstd(r1, acc[0], P.zero);
        ka0 = 0.7978845608028654f * r0; kb0 = 0.035677408136300125f * r0 * r0 * r0; kc0 = 0.5f * r0 * r0;
        ka1 = 0.7978845608028654f * r1; kb1 = 0.035677408136300125f * r1 * r1 * r1; kc1 = 0.5f * r1 * r1;
#pragma unroll 1
        for (int t = 0; t < 8; t++) {
          geglu(IntC<2>(), 0);
          const uint32_t t16 = tid_() * 16;
          if (t < 5) {
            const uint32_t d = (t < 2 ? slot_addr(12) + wg * SLOT + t * 8192 : slot_addr(7) + t * SLOT + wg * 8192) + t16;
#pragma unroll
            for (int i = 0; i < 4; i++)
              sts128(d + i * 2048, hf[4 * i], hf[4 * i + 1], hf[4 * i + 2], hf[4 * i + 3]);
            if (t == 4) asm volatile("fence.proxy.async.shared::cta;" ::: "memory");
          } else {
#pragma unroll
            for (int i = 0; i < 4; i++) st16(sb, hb + (t - 5) * TILE + t16, i * 2048, hf[4 * i], hf[4 * i + 1], hf[4 * i + 2], hf[4 * i + 3]);
          }
          bar_sync(NB_ORD0 + wg, 256);
          mma_pass<128, PS_FF, 4, 2048, 0, false, true>(acc, a, DESC_SW128, t & 1, rel, NB_ORD1 - wg, sb, hb + t16, t == 7);
        }
        TS(9 + L * 20);
        const uint32_t hsm = wg * 8192 + tid_() * 16;
        geglu(IntC<CH_LAST>(), hsm);
#pragma unroll
        for (int i = 0; i < 16; i++) a[128 + i] = hf[i];
      }
      TS(10 + L * 20);
      {
        const uint32_t xs = slot_addr(12) + wg * SLOT;
        {
          bar_sync(NB_ORD0 + wg + ((a[142] | a[143]) & P.zero), 256);
          TS(64 + L * 32);
          rel(9); rel(10); rel(11);
          float acc[32];
          mma_pass<64, PS_FF, 4, 2048, 0, false>(acc, a, DESC_SW128, 0, rel, NB_ORD1 - wg);
          TS(65 + L * 32);
          const uint32_t t8 = tid_() * 8;
#pragma unroll
          for (int i = 0; i < 8; i++) {
            const uint32_t u = pack_bf16(acc[4 * i], acc[4 * i + 1]), v = pack_bf16(acc[4 * i + 2], acc[4 * i + 3]);
            send8(sb, j * 1024 + t8, OFF_P + 2 * PBUF + i * PSRC, xs + PBUF + t8 * 2, i, j, (u & ~1u) | (L ^ 1), v);
          }
          hint_post(hint);
          if (tid_() == 0) mbar_arrive(bar_empty(13));
          bar_arrive(NB_FREE + wg, 160);
          TS(68 + L * 32);
        }
        float acc[64];
        auto verify = [&](int p, uint32_t t16) {
          mbar_wait(bar_full(12) + wg * 8, (p & 1) ^ 1);
          TS(66 + L * 32 + p * 5);
          const uint32_t flip = p == 1 ? L - 1 : p < 4 ? ~0u : 0u;
          const uint32_t sh = p == 1;
          uint32_t m = 0;
#pragma unroll
          for (int s = 0; s < 7; s++) m |= lds32(xs + ((s * 2048 + t16) >> sh)) ^ flip;
          if (__any_sync(0xffffffffu, m & 1)) {
#pragma unroll 1
            for (int s = 0; s < 7; s++) {
              const uint32_t o = (s * 2048 + t16) >> sh;
              uint32_t v[4] = {0, 0, 0, 0};
              do {
                if (sh) ld8(v, sb, j * PSRC + o, OFF_P + 2 * PBUF);
                else ld16(v, sb, j * PSRC + (p & 1) * PBUF + o, OFF_P);
              } while (__any_sync(0xffffffffu, (v[0] ^ flip) & 1));
              sts64(xs + o, v[0], v[1]);
              if (!sh) sts64(xs + o + 8, v[2], v[3]);
            }
            asm volatile("fence.proxy.async.shared::cta;" ::: "memory");
          }
        };
        auto send = [&](int p, uint32_t t16) {
#pragma unroll
          for (int i = 0; i < 8; i++) {
            const uint32_t u0 = pack_bf16(acc[8 * i], acc[8 * i + 1]), u1 = pack_bf16(acc[8 * i + 2], acc[8 * i + 3]);
            const uint32_t u2 = pack_bf16(acc[8 * i + 4], acc[8 * i + 5]), u3 = pack_bf16(acc[8 * i + 6], acc[8 * i + 7]);
            send16(sb, j * 2048 + ((p & 1) ^ 1) * PBUF + t16, OFF_P + i * PSRC, xs + PBUF + t16, i, j, (u0 & ~1u) | (p < 3), u1, u2, u3);
          }
          hint_post(hint);
          TS(68 + L * 32 + p * 5);
        };
        uint32_t y[18];
#pragma unroll 1
        for (int p = 1; p < 5; p++) {
          bar_sync(NB_ORD0 + wg, 256);
          TS(64 + L * 32 + p * 5);
          uint32_t in[32], t16;
          mma_pass<128, PS_FF, 4, 2048, 0, false, false>(acc, a, DESC_SW128, p & 1, rel, (p == 4 && wg == 1) ? -1 : NB_ORD1 - wg, nullptr, 0, 0, 0, 0, 0, [&]() {
            t16 = tid_() * 16;
            if (p == 4) load_own(&a[64], sb, L * 3 * TILE, j);
            lds128(&in[28], xs + PBUF + t16);
            verify(p, t16);
          });
          TS(65 + L * 32 + p * 5);
          send(p, t16);
          if (p == 1) {
#pragma unroll
            for (int s = 0; s < 7; s++) {
              lds64(in[4 * s], in[4 * s + 1], xs + s * 1024 + t16 / 2);
              in[4 * s + 2] = in[4 * s + 3] = 0;
            }
          } else {
#pragma unroll
            for (int s = 0; s < 7; s++) lds128(&in[4 * s], xs + s * 2048 + t16);
          }
          if (p < 4) bar_arrive(NB_FREE + wg, 160);
          reduce4(in, y + 8);
          if (p == 1) sts64(ytail(wg * 2 + (t16 >> 10)) + 2048 + (t16 & 1023) / 2, y[8], y[9]);
          else if (p < 4) sts128(ytail(wg * 2 + p - 2) + t16, y[8], y[9], y[10], y[11]);
          TS(67 + L * 32 + p * 5);
        }
        TS(11 + L * 20);
        const uint32_t t = tid_();
#pragma unroll
        for (int i = 0; i < 2; i++) lds128(&y[4 * i], ytail(wg * 2 + i) + t * 16);
        lds64(y[16], y[17], ytail(wg * 2 + (t >> 6)) + 2048 + (t & 63) * 8);
        lds128(&a[60], xs + PBUF + t * 16);
        const uint32_t tgt = hint_target(L * 8 + 6);
#pragma unroll
        for (int i = 0; i < 18; i++) xr[i] = a[64 + i];
        auto emit = [&](uint32_t mask) {
#pragma unroll
          for (int i = 0; i < 18; i++) if (mask >> (i >> 2) & 1) xr[i] = bf2_add(xr[i], y[i]);
          if (L == 0) {
#pragma unroll
            for (int i = 0; i < 4; i++) if (mask >> i & 1) st16(sb, (t + j * 128) * 16, OFF_X2 + i * 16384, nz(xr[4 * i]), xr[4 * i + 1], xr[4 * i + 2], xr[4 * i + 3]);
            if (mask & 16) st8(sb, (t + j * 128) * 8, OFF_X2 + 65536, nz(xr[16]), xr[17]);
          } else {
#pragma unroll
            for (int i = 0; i < 4; i++) if (mask >> i & 1) stsm4(xs + i * 2048 + t * 16, xr[4 * i], xr[4 * i + 1], xr[4 * i + 2], xr[4 * i + 3]);
            if (mask & 16) stsm4(xs + 8192 + t * 16, xr[16], xr[17], 0, 0);
            __syncwarp();
            uint8_t* op = (uint8_t*)P.out + row_off(rb, wg, t);
#pragma unroll
            for (int i = 0; i < 5; i++) if (mask >> i & 1) {
              uint32_t r[4];
              lds128(r, xs + i * 2048 + t * 16);
              if (i < 4) *(uint4*)(op + i * 256 + j * 32 + (t & 16)) = make_uint4(r[0], r[1], r[2], r[3]);
              else if (!(t & 16)) *(uint4*)(op + 1024 + j * 16) = make_uint4(r[0], r[1], r[2], r[3]);
            }
          }
        };
        hint_wait(hint, tgt);
        TS(17 + L * 20);
#pragma unroll
        for (int s = 0; s < 7; s++) ld16(&a[32 + 4 * s], sb, j * PSRC + t * 16, OFF_P + PBUF + s * 2048);
        emit(23);
        RowStats rs;
        rs.add<12>(xr); rs.add<2>(xr + 16);
        {
          uint32_t m = rs.fold() & P.zero;
          while (true) {
#pragma unroll
            for (int s = 0; s < 7; s++) m |= a[32 + 4 * s];
            if (!__any_sync(0xffffffffu, m & 1)) break;
            m = 0;
#pragma unroll
            for (int s = 0; s < 7; s++) ld16(&a[32 + 4 * s], sb, j * PSRC + t * 16, OFF_P + PBUF + s * 2048);
          }
          TS(12 + L * 20);
          reduce4(a + 32, y + 12);
        }
        TS(18 + L * 20);
        emit(8);
        if (L == 0) {
          rs.add<4>(xr + 12);
          rs.store(sb, 8192 + j * 128, t);
          hint_post(hint);
        }
      }
      TS(13 + L * 20);
    }
    bar_sync(NB_WG + wg, 128);
    if (tid_() == 0) mbar_arrive(bar_empty(12));
  }
}

typedef CUresult (*EncodeFn)(CUtensorMap*, CUtensorMapDataType, cuuint32_t, void*, const cuuint64_t*, const cuuint64_t*, const cuuint32_t*,
                             const cuuint32_t*, CUtensorMapInterleave, CUtensorMapSwizzle, CUtensorMapL2promotion, CUtensorMapFloatOOBfill);

void encode(EncodeFn fn, CUtensorMap* m, const void* p, int rank, const cuuint64_t* dims, const cuuint64_t* str, const cuuint32_t* box) {
  const cuuint32_t es[3] = {1, 1, 1};
  fn(m, CU_TENSOR_MAP_DATA_TYPE_BFLOAT16, rank, const_cast<void*>(p), dims, str, box, es, CU_TENSOR_MAP_INTERLEAVE_NONE,
     CU_TENSOR_MAP_SWIZZLE_128B, CU_TENSOR_MAP_L2_PROMOTION_L2_256B, CU_TENSOR_MAP_FLOAT_OOB_FILL_NONE);
}

}

extern "C" void kernel_launch(void* const* d_in, const int* in_sizes, int n_in, void* d_out, int out_size) {
  (void)in_sizes; (void)n_in; (void)out_size;
  Params P;
  P.x = (const __nv_bfloat16*)d_in[0]; P.wqkv = (const __nv_bfloat16*)d_in[1]; P.wo = (const __nv_bfloat16*)d_in[2];
  P.wg = (const __nv_bfloat16*)d_in[4]; P.wu = (const __nv_bfloat16*)d_in[5]; P.wd = (const __nv_bfloat16*)d_in[6];
  P.out = (__nv_bfloat16*)d_out; P.zero = 0;
  cudaGetSymbolAddress((void**)&P.scr, g_scr);
  void* fnp = nullptr; cudaDriverEntryPointQueryResult qr;
  cudaGetDriverEntryPoint("cuTensorMapEncodeTiled", &fnp, cudaEnableDefault, &qr);
  EncodeFn fn = (EncodeFn)fnp;
  CUtensorMap mx, mg, mu, md;
  { const cuuint64_t dims[3] = {DM, SEQ / 2, 2}, str[2] = {DM * 4, DM * 2}; const cuuint32_t box[3] = {64, 64, 2}; encode(fn, &mx, P.x, 3, dims, str, box); }
  { const cuuint64_t dims[2] = {DFF, DM}, str[1] = {DFF * 2}; const cuuint32_t box[2] = {64, 64}; encode(fn, &mg, P.wg, 2, dims, str, box); encode(fn, &mu, P.wu, 2, dims, str, box); }
  { const cuuint64_t dims[2] = {DM, DFF}, str[1] = {DM * 2}; const cuuint32_t box[2] = {64, 64}; encode(fn, &md, P.wd, 2, dims, str, box); }
  cudaFuncSetAttribute(fused_kernel, cudaFuncAttributeMaxDynamicSharedMemorySize, SMEM_BYTES);
  fused_kernel<<<128, 384, SMEM_BYTES, cudaStreamPerThread>>>(mx, mg, mu, md, P);
}
```

```cpp
#include <cuda_runtime.h>
#include <cuda_bf16.h>
#include <cuda.h>
#include <stdint.h>

#define KV_LEAD 5
#define D_KV 6
#define D_WO 3
#define D_T0 5
#define PF_AHEAD 3
#define CH_LAST 2
#define MC 0
#define MAP 3
#define N_WO 18
#define TH 1
#define THD 0
#define DBG_PS 2
#define TIMING 0

namespace {

constexpr int SEQ = 2048, DM = 576, DFF = 4608;
constexpr uint32_t SB = 1024;
constexpr uint32_t SLOT = 16384;
constexpr uint32_t PSLOT = 13824;
constexpr uint32_t BARS = SB + 14 * SLOT;
constexpr int SMEM_BYTES = 14 * SLOT + 256 + 2560;
__host__ __device__ constexpr uint32_t slot_addr(int s) { return SB + s * SLOT; }
__host__ __device__ constexpr uint32_t bar_full(int s) { return BARS + 8 * s; }
__host__ __device__ constexpr uint32_t bar_empty(int s) { return BARS + 128 + 8 * s; }
enum { NB_ORD0 = 1, NB_ORD1 = 2, NB_WG = 3  , NB_HALO = 5  , NB_FREE = 7  , NB_PUB = 9   };
constexpr uint32_t SM_EPOCH = BARS + 120;
__host__ __device__ constexpr uint32_t ytail(uint32_t k) { return k < 3 ? slot_addr(9) + PSLOT + k * SLOT : BARS + 256; }
constexpr uint32_t KSTG = 9 * 1152;

constexpr uint32_t TILE = 36 * 2048;
constexpr uint32_t OFF_X1 = 0  , OFF_O = TILE, OFF_X2 = 2 * TILE, OFF_ST = 4 * TILE  ;
constexpr uint32_t PSRC = 2 * 16384 + 7 * 1024;
constexpr uint32_t OFF_P = OFF_ST + 3 * 4096, OFF_HALO = OFF_P + 8 * PSRC  , OFF_HINT = OFF_HALO + 2 * 8 * 3072  ,
                   STRM = OFF_HINT + 12 * 128;
constexpr uint32_t OFF_WPACK = 32 * STRM, OFF_FLAGS = OFF_WPACK + 8 * 24 * PSLOT;
__device__ __align__(1024) uint8_t g_scr[OFF_FLAGS + (8 + 64 + 128) * 32];

__device__ __forceinline__ uint32_t smem_u32(const void* p) { return (uint32_t)__cvta_generic_to_shared(p); }
extern __shared__ __align__(1024) uint8_t smem_raw[];
__device__ __forceinline__ uint32_t win() { return MC ? (blockIdx.x & 1) << 24 : 0; }
#define SA(A, W) ".reg .u32 sa;\nadd.u32 sa, " A ", " W ";\n"
__device__ __forceinline__ void mbar_init(uint32_t bar, uint32_t cnt) { asm volatile("{\n" SA("%0", "%2") "mbarrier.init.shared::cta.b64 [sa], %1;\n}" ::"r"(bar), "r"(cnt), "r"(win())); }
__device__ __forceinline__ void mbar_expect_tx(uint32_t bar, uint32_t bytes) { asm volatile("{\n" SA("%0", "%2") "mbarrier.arrive.expect_tx.shared::cta.b64 _, [sa], %1;\n}" ::"r"(bar), "r"(bytes), "r"(win()) : "memory"); }
__device__ __forceinline__ void mbar_arrive(uint32_t bar) { asm volatile("{\n" SA("%0", "%1") "mbarrier.arrive.shared::cta.b64 _, [sa];\n}" ::"r"(bar), "r"(win()) : "memory"); }
__device__ __forceinline__ uint32_t lds32(uint32_t a) { uint32_t v; asm volatile("{\n" SA("%1", "%2") "ld.shared.u32 %0, [sa];\n}" : "=r"(v) : "r"(a), "r"(win()) : "memory"); return v; }
__device__ __forceinline__ void lds64(uint32_t& x, uint32_t& y, uint32_t a) { asm volatile("{\n" SA("%2", "%3") "ld.shared.v2.u32 {%0,%1}, [sa];\n}" : "=r"(x), "=r"(y) : "r"(a), "r"(win()) : "memory"); }
__device__ __forceinline__ void lds128(uint32_t* v, uint32_t a) {
  asm volatile("{\n" SA("%4", "%5") "ld.shared.v4.u32 {%0,%1,%2,%3}, [sa];\n}" : "=r"(v[0]), "=r"(v[1]), "=r"(v[2]), "=r"(v[3]) : "r"(a), "r"(win()) : "memory");
}
__device__ __forceinline__ void stsm4(uint32_t a, uint32_t x, uint32_t y, uint32_t z, uint32_t w) {
  asm volatile("{\n" SA("%0", "%5") "stmatrix.sync.aligned.m8n8.x4.shared.b16 [sa], {%1,%2,%3,%4};\n}" ::"r"(a), "r"(x), "r"(y), "r"(z), "r"(w), "r"(win()) : "memory");
}
__device__ __forceinline__ void ldsm4(uint32_t* v, uint32_t a) {
  asm volatile("{\n" SA("%4", "%5") "ldmatrix.sync.aligned.m8n8.x4.shared.b16 {%0,%1,%2,%3}, [sa];\n}" : "=r"(v[0]), "=r"(v[1]), "=r"(v[2]), "=r"(v[3]) : "r"(a), "r"(win()) : "memory");
}
__device__ __forceinline__ void ldsm4t(uint32_t* v, uint32_t a) {
  asm volatile("{\n" SA("%4", "%5") "ldmatrix.sync.aligned.m8n8.x4.trans.shared.b16 {%0,%1,%2,%3}, [sa];\n}" : "=r"(v[0]), "=r"(v[1]), "=r"(v[2]), "=r"(v[3]) : "r"(a), "r"(win()) : "memory");
}
__device__ __forceinline__ void sts32(uint32_t a, uint32_t x) { asm volatile("{\n" SA("%0", "%2") "st.shared.u32 [sa], %1;\n}" ::"r"(a), "r"(x), "r"(win()) : "memory"); }
__device__ __forceinline__ void sts64(uint32_t a, uint32_t x, uint32_t y) { asm volatile("{\n" SA("%0", "%3") "st.shared.v2.u32 [sa], {%1,%2};\n}" ::"r"(a), "r"(x), "r"(y), "r"(win()) : "memory"); }
__device__ __forceinline__ void sts128(uint32_t a, uint32_t x, uint32_t y, uint32_t z, uint32_t w) {
  asm volatile("{\n" SA("%0", "%5") "st.shared.v4.u32 [sa], {%1,%2,%3,%4};\n}" ::"r"(a), "r"(x), "r"(y), "r"(z), "r"(w), "r"(win()) : "memory");
}
__device__ __forceinline__ void mbar_wait(uint32_t bar, uint32_t parity) {
  asm volatile("{\n.reg .pred p;\n" SA("%0", "%2") "LAB_WAIT:\nmbarrier.try_wait.parity.shared::cta.b64 p, [sa], %1;\n@!p bra LAB_WAIT;\n}" ::"r"(bar), "r"(parity), "r"(win()) : "memory");
}
__device__ __forceinline__ void timed_wait(uint32_t bar, uint32_t par) {
  asm volatile("{\n.reg .pred p;\n.reg .u64 t0, t1;\nmov.u64 t0, %%globaltimer;\nLAB_WD:\n"
               "mbarrier.try_wait.parity.shared::cta.b64 p, [%0], %1, 100000;\n@p bra LAB_OK;\n"
               "mov.u64 t1, %%globaltimer;\nsub.u64 t1, t1, t0;\nsetp.lt.u64 p, t1, 2000000000;\n@p bra LAB_WD;\ntrap;\nLAB_OK:\n}" ::"r"(bar + win()), "r"(par) : "memory");
}
__device__ __forceinline__ void flag_wait(const unsigned* flag, unsigned target) {
  asm volatile("{\n.reg .pred p;\n.reg .u32 v;\nLAB_WAIT:\nld.acquire.gpu.global.u32 v, [%0];\nsub.u32 v, v, %1;\n"
               "setp.lt.s32 p, v, 0;\n@p nanosleep.u32 100;\n@p bra LAB_WAIT;\n}" ::"l"(flag), "r"(target) : "memory");
}
__device__ __forceinline__ void hint_post(uint8_t* p) {
  __syncwarp();
  asm volatile("{\n.reg .pred p;\nelect.sync _|p, 0xffffffff;\n@p red.relaxed.gpu.global.add.u32 [%0], 1;\n}" ::"l"(p) : "memory");
}
__device__ __forceinline__ void hint_wait(const uint8_t* p, uint32_t target) {
  asm volatile("{\n.reg .pred p;\n.reg .u32 v;\nLAB_WAIT:\nld.relaxed.gpu.global.u32 v, [%0];\nsub.u32 v, v, %1;\n"
               "setp.lt.s32 p, v, 0;\nvote.sync.any.pred p, p, 0xffffffff;\n@p bra LAB_WAIT;\n}" ::"l"(p), "r"(target) : "memory");
}
__device__ __forceinline__ void flag_signal(unsigned* flag) { asm volatile("red.release.gpu.global.add.u32 [%0], 1;" ::"l"(flag) : "memory"); }
struct Rel {
  bool on; uint32_t base;
  __device__ __forceinline__ void operator()(int s) const {
    if (on) {
      if (MC) asm volatile("{\n" SA("%0", "%1") "mbarrier.arrive.shared::cluster.b64 _, [sa];\n}" ::"r"(bar_empty(s)), "r"(base) : "memory");
      else mbar_arrive(bar_empty(s));
    }
  }
};
__device__ __forceinline__ uint32_t cta_window(uint32_t rank) { uint32_t a; asm("mapa.shared::cluster.u32 %0, %1, %2;" : "=r"(a) : "r"(0), "r"(rank)); return a; }
__device__ __forceinline__ void tma_2d_mc(uint32_t dst, const CUtensorMap* m, int c0, int c1, uint32_t bar) {
  asm volatile("cp.async.bulk.tensor.2d.shared::cluster.global.mbarrier::complete_tx::bytes.multicast::cluster [%0], [%1, {%3, %4}], [%2], %5;"
               ::"r"(dst), "l"(m), "r"(bar), "r"(c0), "r"(c1), "h"((uint16_t)3) : "memory");
}
__device__ __forceinline__ void bulk_load_mc(uint32_t dst, const void* src, uint32_t bytes, uint32_t bar) {
  asm volatile("cp.async.bulk.shared::cluster.global.mbarrier::complete_tx::bytes.multicast::cluster [%0], [%1], %2, [%3], %4;"
               ::"r"(dst), "l"(src), "r"(bytes), "r"(bar), "h"((uint16_t)3) : "memory");
}
__device__ __forceinline__ void tma_2d(uint32_t dst, const CUtensorMap* m, int c0, int c1, uint32_t bar) {
  asm volatile("cp.async.bulk.tensor.2d.shared::cluster.global.mbarrier::complete_tx::bytes [%0], [%1, {%3, %4}], [%2];"
               ::"r"(dst), "l"(m), "r"(bar), "r"(c0), "r"(c1) : "memory");
}
__device__ __forceinline__ void tma_3d(uint32_t dst, const CUtensorMap* m, int c0, int c1, int c2, uint32_t bar) {
  asm volatile("cp.async.bulk.tensor.3d.shared::cluster.global.mbarrier::complete_tx::bytes [%0], [%1, {%3, %4, %5}], [%2];"
               ::"r"(dst), "l"(m), "r"(bar), "r"(c0), "r"(c1), "r"(c2) : "memory");
}
__device__ __forceinline__ void bulk_load(uint32_t dst, const void* src, uint32_t bytes, uint32_t bar) {
  asm volatile("cp.async.bulk.shared::cluster.global.mbarrier::complete_tx::bytes [%0], [%1], %2, [%3];" ::"r"(dst), "l"(src), "r"(bytes), "r"(bar) : "memory");
}
__device__ __forceinline__ void l2_prefetch(const void* src, uint32_t bytes) { asm volatile("cp.async.bulk.prefetch.L2.global [%0], %1;" ::"l"(src), "r"(bytes) : "memory"); }
__device__ __forceinline__ void wg_fence() { asm volatile("wgmma.fence.sync.aligned;" ::: "memory"); }
__device__ __forceinline__ void wg_commit() { asm volatile("wgmma.commit_group.sync.aligned;" ::: "memory"); }
template <int N> __device__ __forceinline__ void wg_wait() { asm volatile("wgmma.wait_group.sync.aligned %0;" ::"n"(N) : "memory"); }
__device__ __forceinline__ void bar_sync(int id, int n) { asm volatile("bar.sync %0, %1;" ::"r"(id), "r"(n) : "memory"); }
__device__ __forceinline__ void bar_arrive(int id, int n) { asm volatile("bar.arrive %0, %1;" ::"r"(id), "r"(n) : "memory"); }
__device__ __forceinline__ uint32_t pack_bf16(float lo, float hi) { uint32_t r; asm("cvt.rn.bf16x2.f32 %0, %1, %2;" : "=r"(r) : "f"(hi), "f"(lo)); return r; }
__device__ __forceinline__ float bf_lo(uint32_t w) { return __uint_as_float(w << 16); }
__device__ __forceinline__ float bf_hi(uint32_t w) { return __uint_as_float(w & 0xffff0000u); }
__device__ __forceinline__ float bf_round(float x) { return bf_lo(pack_bf16(x, 0.f)); }
__device__ __forceinline__ uint32_t bf2_sub(uint32_t a, uint32_t b) { uint32_t r; asm("sub.rn.bf16x2 %0, %1, %2;" : "=r"(r) : "r"(a), "r"(b)); return r; }
__device__ __forceinline__ uint32_t bf2_add(uint32_t a, uint32_t b) { uint32_t r; asm("add.rn.bf16x2 %0, %1, %2;" : "=r"(r) : "r"(a), "r"(b)); return r; }
#define GADDR(B, O, I) "cvt.u64.u32 ad, " O ";\nadd.u64 ad, ad, " B ";\nadd.u64 ad, ad, " I ";\n"
__device__ __forceinline__ void ld16(uint32_t* v, const uint8_t* ub, uint32_t off, uint32_t imm) {
  asm volatile("{\n.reg .b128 z;\n.reg .b64 x, y, ad;\n" GADDR("%4", "%5", "%6") "ld.relaxed.gpu.global.b128 z, [ad];\n"
               "mov.b128 {x, y}, z;\nmov.b64 {%0,%1}, x;\nmov.b64 {%2,%3}, y;\n}"
               : "=r"(v[0]), "=r"(v[1]), "=r"(v[2]), "=r"(v[3]) : "l"(ub), "r"(off), "l"((uint64_t)imm) : "memory");
}
__device__ __forceinline__ void ld8(uint32_t* v, const uint8_t* ub, uint32_t off, uint32_t imm) {
  asm volatile("{\n.reg .b64 x, ad;\n" GADDR("%2", "%3", "%4") "ld.relaxed.gpu.global.b64 x, [ad];\nmov.b64 {%0,%1}, x;\n}"
               : "=r"(v[0]), "=r"(v[1]) : "l"(ub), "r"(off), "l"((uint64_t)imm) : "memory");
}
__device__ __forceinline__ void st16(uint8_t* ub, uint32_t off, uint32_t imm, uint32_t a, uint32_t b, uint32_t c, uint32_t d) {
  asm volatile("{\n.reg .b128 z;\n.reg .b64 x, y, ad;\n" GADDR("%0", "%1", "%2") "mov.b64 x, {%3,%4};\nmov.b64 y, {%5,%6};\nmov.b128 z, {x, y};\n"
               "st.relaxed.gpu.global.b128 [ad], z;\n}" ::"l"(ub), "r"(off), "l"((uint64_t)imm), "r"(a), "r"(b), "r"(c), "r"(d) : "memory");
}
__device__ __forceinline__ void st8(uint8_t* ub, uint32_t off, uint32_t imm, uint32_t a, uint32_t b) {
  asm volatile("{\n.reg .b64 x, ad;\n" GADDR("%0", "%1", "%2") "mov.b64 x, {%3,%4};\nst.relaxed.gpu.global.b64 [ad], x;\n}"
               ::"l"(ub), "r"(off), "l"((uint64_t)imm), "r"(a), "r"(b) : "memory");
}
__device__ __forceinline__ void send8(uint8_t* ub, uint32_t off, uint32_t imm, uint32_t sm, int i, int j, uint32_t a, uint32_t b) {
  asm volatile("{\n.reg .pred p, q, e;\n.reg .b64 x, ad;\n" SA("%3", "%8") GADDR("%0", "%1", "%2")
               "setp.lt.s32 p, %4, %5;\nsetp.gt.s32 q, %4, %5;\nsetp.eq.s32 e, %4, %5;\nmov.b64 x, {%6,%7};\n"
               "@p st.relaxed.gpu.global.b64 [ad+-1024], x;\n@q st.relaxed.gpu.global.b64 [ad], x;\n@e st.shared.v2.u32 [sa], {%6,%7};\n}"
               ::"l"(ub), "r"(off), "l"((uint64_t)imm), "r"(sm), "r"(i), "r"(j), "r"(a), "r"(b), "r"(win()) : "memory");
}
__device__ __forceinline__ uint4 ldg_line(const void* p) {
  uint4 v; asm volatile("ld.global.nc.L2::128B.v4.u32 {%0,%1,%2,%3}, [%4];" : "=r"(v.x), "=r"(v.y), "=r"(v.z), "=r"(v.w) : "l"(p)); return v;
}
__device__ __forceinline__ void stg4(void* ub, uint32_t off, uint32_t imm, uint32_t v) {
  asm volatile("{\n.reg .b64 ad;\n" GADDR("%0", "%1", "%2") "st.global.u32 [ad], %3;\n}" ::"l"(ub), "r"(off), "l"((uint64_t)imm), "r"(v) : "memory");
}
__device__ __forceinline__ uint32_t tid_() { uint32_t t; asm volatile("mov.u32 %0, %%tid.x;" : "=r"(t)); return t & 127; }
__device__ __forceinline__ uint32_t nz(uint32_t w) { return max(w, 1u); }
__device__ __forceinline__ void mma16816(float (&c)[4], uint32_t a0, uint32_t a1, uint32_t a2, uint32_t a3, uint32_t b0, uint32_t b1) {
  asm("mma.sync.aligned.m16n8k16.row.col.f32.bf16.bf16.f32 {%0,%1,%2,%3}, {%4,%5,%6,%7}, {%8,%9}, {%0,%1,%2,%3};"
               : "+f"(c[0]), "+f"(c[1]), "+f"(c[2]), "+f"(c[3]) : "r"(a0), "r"(a1), "r"(a2), "r"(a3), "r"(b0), "r"(b1));
}
__device__ __forceinline__ void mma1688(float (&c)[4], uint32_t a0, uint32_t a1, uint32_t b0) {
  asm("mma.sync.aligned.m16n8k8.row.col.f32.bf16.bf16.f32 {%0,%1,%2,%3}, {%4,%5}, {%6}, {%0,%1,%2,%3};"
               : "+f"(c[0]), "+f"(c[1]), "+f"(c[2]), "+f"(c[3]) : "r"(a0), "r"(a1), "r"(b0));
}
__device__ __forceinline__ float ex2(float x) { float r; asm("ex2.approx.ftz.f32 %0, %1;" : "=f"(r) : "f"(x)); return r; }
__device__ __forceinline__ float quad_sum(float v) { v += __shfl_xor_sync(0xffffffffu, v, 1); v += __shfl_xor_sync(0xffffffffu, v, 2); return v; }
__device__ __forceinline__ float quad_max(float v) { v = fmaxf(v, __shfl_xor_sync(0xffffffffu, v, 1)); v = fmaxf(v, __shfl_xor_sync(0xffffffffu, v, 2)); return v; }

__device__ __forceinline__ void wgmma_rs_n64(float (&d)[32], uint32_t a0, uint32_t a1, uint32_t a2, uint32_t a3, uint64_t desc, int scale_d) {
  asm volatile("{\n.reg .pred p;\nsetp.ne.b32 p, %37, 0;\n"
    "wgmma.mma_async.sync.aligned.m64n64k16.f32.bf16.bf16 "
    "{%0, %1, %2, %3, %4, %5, %6, %7, %8, %9, %10, %11, %12, %13, %14, %15, %16, %17, %18, %19, %20, %21, %22, %23, %24, %25, %26, %27, %28, %29, %30, %31}, "
    "{%32, %33, %34, %35}, %36, p, 1, 1, 1;\n}\n"
    : "+f"(d[0]), "+f"(d[1]), "+f"(d[2]), "+f"(d[3]), "+f"(d[4]), "+f"(d[5]), "+f"(d[6]), "+f"(d[7]), "+f"(d[8]), "+f"(d[9]), "+f"(d[10]), "+f"(d[11]), "+f"(d[12]), "+f"(d[13]), "+f"(d[14]), "+f"(d[15]), "+f"(d[16]), "+f"(d[17]), "+f"(d[18]), "+f"(d[19]), "+f"(d[20]), "+f"(d[21]), "+f"(d[22]), "+f"(d[23]), "+f"(d[24]), "+f"(d[25]), "+f"(d[26]), "+f"(d[27]), "+f"(d[28]), "+f"(d[29]), "+f"(d[30]), "+f"(d[31])
    : "r"(a0), "r"(a1), "r"(a2), "r"(a3), "l"(desc), "r"(scale_d));
}

__device__ __forceinline__ void wgmma_rs_n72(float (&d)[36], uint32_t a0, uint32_t a1, uint32_t a2, uint32_t a3, uint64_t desc, int scale_d) {
  asm volatile("{\n.reg .pred p;\nsetp.ne.b32 p, %41, 0;\n"
    "wgmma.mma_async.sync.aligned.m64n72k16.f32.bf16.bf16 "
    "{%0, %1, %2, %3, %4, %5, %6, %7, %8, %9, %10, %11, %12, %13, %14, %15, %16, %17, %18, %19, %20, %21, %22, %23, %24, %25, %26, %27, %28, %29, %30, %31, %32, %33, %34, %35}, "
    "{%36, %37, %38, %39}, %40, p, 1, 1, 1;\n}\n"
    : "+f"(d[0]), "+f"(d[1]), "+f"(d[2]), "+f"(d[3]), "+f"(d[4]), "+f"(d[5]), "+f"(d[6]), "+f"(d[7]), "+f"(d[8]), "+f"(d[9]), "+f"(d[10]), "+f"(d[11]), "+f"(d[12]), "+f"(d[13]), "+f"(d[14]), "+f"(d[15]), "+f"(d[16]), "+f"(d[17]), "+f"(d[18]), "+f"(d[19]), "+f"(d[20]), "+f"(d[21]), "+f"(d[22]), "+f"(d[23]), "+f"(d[24]), "+f"(d[25]), "+f"(d[26]), "+f"(d[27]), "+f"(d[28]), "+f"(d[29]), "+f"(d[30]), "+f"(d[31]), "+f"(d[32]), "+f"(d[33]), "+f"(d[34]), "+f"(d[35])
    : "r"(a0), "r"(a1), "r"(a2), "r"(a3), "l"(desc), "r"(scale_d));
}

__device__ __forceinline__ void wgmma_rs_n128(float (&d)[64], uint32_t a0, uint32_t a1, uint32_t a2, uint32_t a3, uint64_t desc, int scale_d) {
  asm volatile("{\n.reg .pred p;\nsetp.ne.b32 p, %69, 0;\n"
    "wgmma.mma_async.sync.aligned.m64n128k16.f32.bf16.bf16 "
    "{%0, %1, %2, %3, %4, %5, %6, %7, %8, %9, %10, %11, %12, %13, %14, %15, %16, %17, %18, %19, %20, %21, %22, %23, %24, %25, %26, %27, %28, %29, %30, %31, %32, %33, %34, %35, %36, %37, %38, %39, %40, %41, %42, %43, %44, %45, %46, %47, %48, %49, %50, %51, %52, %53, %54, %55, %56, %57, %58, %59, %60, %61, %62, %63}, "
    "{%64, %65, %66, %67}, %68, p, 1, 1, 1;\n}\n"
    : "+f"(d[0]), "+f"(d[1]), "+f"(d[2]), "+f"(d[3]), "+f"(d[4]), "+f"(d[5]), "+f"(d[6]), "+f"(d[7]), "+f"(d[8]), "+f"(d[9]), "+f"(d[10]), "+f"(d[11]), "+f"(d[12]), "+f"(d[13]), "+f"(d[14]), "+f"(d[15]), "+f"(d[16]), "+f"(d[17]), "+f"(d[18]), "+f"(d[19]), "+f"(d[20]), "+f"(d[21]), "+f"(d[22]), "+f"(d[23]), "+f"(d[24]), "+f"(d[25]), "+f"(d[26]), "+f"(d[27]), "+f"(d[28]), "+f"(d[29]), "+f"(d[30]), "+f"(d[31]), "+f"(d[32]), "+f"(d[33]), "+f"(d[34]), "+f"(d[35]), "+f"(d[36]), "+f"(d[37]), "+f"(d[38]), "+f"(d[39]), "+f"(d[40]), "+f"(d[41]), "+f"(d[42]), "+f"(d[43]), "+f"(d[44]), "+f"(d[45]), "+f"(d[46]), "+f"(d[47]), "+f"(d[48]), "+f"(d[49]), "+f"(d[50]), "+f"(d[51]), "+f"(d[52]), "+f"(d[53]), "+f"(d[54]), "+f"(d[55]), "+f"(d[56]), "+f"(d[57]), "+f"(d[58]), "+f"(d[59]), "+f"(d[60]), "+f"(d[61]), "+f"(d[62]), "+f"(d[63])
    : "r"(a0), "r"(a1), "r"(a2), "r"(a3), "l"(desc), "r"(scale_d));
}

__device__ __forceinline__ void wgmma_rs_n144(float (&d)[72], uint32_t a0, uint32_t a1, uint32_t a2, uint32_t a3, uint64_t desc, int scale_d) {
  asm volatile("{\n.reg .pred p;\nsetp.ne.b32 p, %77, 0;\n"
    "wgmma.mma_async.sync.aligned.m64n144k16.f32.bf16.bf16 "
    "{%0, %1, %2, %3, %4, %5, %6, %7, %8, %9, %10, %11, %12, %13, %14, %15, %16, %17, %18, %19, %20, %21, %22, %23, %24, %25, %26, %27, %28, %29, %30, %31, %32, %33, %34, %35, %36, %37, %38, %39, %40, %41, %42, %43, %44, %45, %46, %47, %48, %49, %50, %51, %52, %53, %54, %55, %56, %57, %58, %59, %60, %61, %62, %63, %64, %65, %66, %67, %68, %69, %70, %71}, "
    "{%72, %73, %74, %75}, %76, p, 1, 1, 1;\n}\n"
    : "+f"(d[0]), "+f"(d[1]), "+f"(d[2]), "+f"(d[3]), "+f"(d[4]), "+f"(d[5]), "+f"(d[6]), "+f"(d[7]), "+f"(d[8]), "+f"(d[9]), "+f"(d[10]), "+f"(d[11]), "+f"(d[12]), "+f"(d[13]), "+f"(d[14]), "+f"(d[15]), "+f"(d[16]), "+f"(d[17]), "+f"(d[18]), "+f"(d[19]), "+f"(d[20]), "+f"(d[21]), "+f"(d[22]), "+f"(d[23]), "+f"(d[24]), "+f"(d[25]), "+f"(d[26]), "+f"(d[27]), "+f"(d[28]), "+f"(d[29]), "+f"(d[30]), "+f"(d[31]), "+f"(d[32]), "+f"(d[33]), "+f"(d[34]), "+f"(d[35]), "+f"(d[36]), "+f"(d[37]), "+f"(d[38]), "+f"(d[39]), "+f"(d[40]), "+f"(d[41]), "+f"(d[42]), "+f"(d[43]), "+f"(d[44]), "+f"(d[45]), "+f"(d[46]), "+f"(d[47]), "+f"(d[48]), "+f"(d[49]), "+f"(d[50]), "+f"(d[51]), "+f"(d[52]), "+f"(d[53]), "+f"(d[54]), "+f"(d[55]), "+f"(d[56]), "+f"(d[57]), "+f"(d[58]), "+f"(d[59]), "+f"(d[60]), "+f"(d[61]), "+f"(d[62]), "+f"(d[63]), "+f"(d[64]), "+f"(d[65]), "+f"(d[66]), "+f"(d[67]), "+f"(d[68]), "+f"(d[69]), "+f"(d[70]), "+f"(d[71])
    : "r"(a0), "r"(a1), "r"(a2), "r"(a3), "l"(desc), "r"(scale_d));
}

template <int N> struct WG;
template <> struct WG<64>  { static __device__ __forceinline__ void f(float (&d)[32], const uint32_t* a, uint64_t ds, int s) { wgmma_rs_n64(d, a[0], a[1], a[2], a[3], ds, s); } };
template <> struct WG<72>  { static __device__ __forceinline__ void f(float (&d)[36], const uint32_t* a, uint64_t ds, int s) { wgmma_rs_n72(d, a[0], a[1], a[2], a[3], ds, s); } };
template <> struct WG<128> { static __device__ __forceinline__ void f(float (&d)[64], const uint32_t* a, uint64_t ds, int s) { wgmma_rs_n128(d, a[0], a[1], a[2], a[3], ds, s); } };
template <> struct WG<144> { static __device__ __forceinline__ void f(float (&d)[72], const uint32_t* a, uint64_t ds, int s) { wgmma_rs_n144(d, a[0], a[1], a[2], a[3], ds, s); } };

constexpr uint64_t DESC_SW128 = ((uint64_t)(8192 >> 4) << 16) | ((uint64_t)(1024 >> 4) << 32) | (1ull << 62);
constexpr uint64_t DESC_KV = ((uint64_t)(128 >> 4) << 16) | ((uint64_t)(768 >> 4) << 32);
constexpr uint64_t DESC_Q = ((uint64_t)(128 >> 4) << 16) | ((uint64_t)(1536 >> 4) << 32);

template <int V> struct IntC { static constexpr int value = V; };
enum { PS_KV, PS_Q, PS_WO, PS_FF, PS_FFA   };
template <int PS> __host__ __device__ constexpr int pass_slot(int i) {
  return PS == PS_KV ? (i < 3 ? 9 + i : i - 3) : PS == PS_WO ? 6 + i : i;
}

__device__ __forceinline__ void load_frag(uint32_t (&a)[144], int i, const uint8_t* sb, uint32_t uo, uint32_t t) {
  if (i < 32) ld16(&a[4 * i], sb, uo + t * 16, i * 2048);
  else { ld8(&a[4 * i], sb, uo + t * 8, i * 2048); ld8(&a[4 * i + 2], sb, uo + t * 8, i * 2048 + 1024); }
}
__device__ __forceinline__ void store_own(const uint32_t (&y)[18], uint8_t* sb, uint32_t uo, int j, uint32_t t) {
#pragma unroll
  for (int i = 0; i < 4; i++) st16(sb, uo + j * 8192 + t * 16, i * 2048, nz(y[4 * i]), y[4 * i + 1], y[4 * i + 2], y[4 * i + 3]);
  st8(sb, uo + j * 1024 + t * 8, 65536, nz(y[16]), y[17]);
}
__device__ __forceinline__ void load_own(uint32_t* y, const uint8_t* sb, uint32_t uo, int j) {
  const uint32_t t = tid_();
#pragma unroll
  for (int i = 0; i < 4; i++) ld16(&y[4 * i], sb, uo + j * 8192 + t * 16, i * 2048);
  ld8(&y[16], sb, uo + j * 1024 + t * 8, 65536);
}

struct NoTail { __device__ __forceinline__ void operator()() const {} };
template <int N, int PS, int KPS, int KSTEP, int CHK, bool SUB, bool HREL = false, class Tail = NoTail>
__device__ __forceinline__ void mma_pass(float (&acc)[N / 2], uint32_t (&a)[144], uint64_t desc, uint32_t par, const Rel& rel, int bar_id,
                                         const uint8_t* sb = nullptr, uint32_t uo = 0, uint32_t flag = 0, uint32_t m0 = 0, uint32_t m1 = 0, uint32_t park = 0, Tail tail = Tail()) {
  constexpr int NS = 36 / KPS;
  auto check = [&](int lo, int hi, uint32_t m0_) {
    while (true) {
      uint32_t m = m0_;
#pragma unroll
      for (int i = hi - 1; i >= lo; i--) m = min(m, i < 32 ? a[4 * i] : min(a[4 * i], a[4 * i + 2]));
      if (!__any_sync(0xffffffffu, (m | flag) == 0)) break;
      const uint32_t t = tid_();
#pragma unroll
      for (int i = lo; i < hi; i++) load_frag(a, i, sb, uo, t);
    }
  };
#pragma unroll
  for (int s = 0; s < NS; s++) {
    const int sl = pass_slot<PS>(s);
    if (CHK && s == 0 && !SUB) check(0, CHK * KPS, ~0u);
    if (CHK && s == CHK) check(CHK * KPS, 36, lds32(SM_EPOCH) | 1);
    if (SUB) {
#pragma unroll
      for (int i = s * KPS * 4; i < (s + 1) * KPS * 4; i += 2) { a[i] = bf2_sub(a[i], m0); a[i + 1] = bf2_sub(a[i + 1], m1); }
    }
    if (PS == PS_KV && s == 0) sts128(park + tid_() * 16, a[0], a[1], a[2], a[3]);
    mbar_wait(bar_full(sl), sl < 9 ? par : par ^ 1);
    wg_fence();
#pragma unroll
    for (int kk = 0; kk < KPS; kk++)
      WG<N>::f(acc, &a[(s * KPS + kk) * 4], desc + ((slot_addr(sl) + kk * KSTEP) >> 4), (s | kk) || PS == PS_FFA);
    wg_commit();
    if (s == (PS == PS_KV ? KV_LEAD : NS - 1) && bar_id >= 0) bar_arrive(bar_id, 256);
    if (s > 0) {
      wg_wait<1>();
      if (!(PS == PS_WO && s > 3)) rel(pass_slot<PS>(s - 1));
    }
    if (HREL && s == 3 && flag) {
#pragma unroll
      for (int i = 0; i < 12; i++) ld16(&a[4 * i], sb, uo, (i >> 2) * TILE + (i & 3) * 2048);
    }
  }
  tail();
  wg_wait<0>();
  if (PS != PS_WO) rel(pass_slot<PS>(NS - 1));
}

template <int NF, int N0 = 0> __device__ __forceinline__ void load_frags(uint32_t (&a)[144], const uint8_t* sb, uint32_t uo, uint32_t t) {
#pragma unroll
  for (int i = N0; i < NF; i++) load_frag(a, i, sb, uo, t);
}
__device__ __forceinline__ void ln_scalars(float s1, float s2, uint32_t& m, float& var, uint32_t zero) {
  const float mean = s1 * (1.f / DM);
  var = s2 * (1.f / DM) - mean * mean;
  m = pack_bf16(mean, mean) ^ (__float_as_uint(var) & zero);
}
__device__ __forceinline__ float ln_rstd(float var, float after, uint32_t zero) {
  var = __uint_as_float(__float_as_uint(var) ^ (__float_as_uint(after) & zero));
  float sd, r;
  asm("sqrt.approx.ftz.f32 %0, %1;" : "=f"(sd) : "f"(bf_round(bf_round(fmaxf(var, 0.f)) + 1e-5f)));
  asm("rcp.approx.ftz.f32 %0, %1;" : "=f"(r) : "f"(bf_round(sd)));
  return r;
}
template <int NF> __device__ __forceinline__ void gather_ln(uint32_t (&a)[144], const uint8_t* sb, uint32_t uo, uint32_t sto,
                                          uint32_t& m0, uint32_t& m1, float& r0, float& r1, uint32_t zero) {
  uint32_t u[32];
  const uint32_t t = tid_(), so = sto + (t >> 5) * 1024 + (t & 28) * 4;
#pragma unroll
  for (int i = 0; i < 8; i++) ld16(&u[4 * i], sb, so, OFF_ST + i * 128);
  load_frags<36>(a, sb, uo, t);
  while (true) {
    uint32_t m = a[4 * NF - 4];
#pragma unroll
    for (int i = NF - 2; i >= 0; i--) m = min(m, a[4 * i]);
#pragma unroll
    for (int i = 0; i < 8; i++) m = min(m, u[4 * i]);
    if (!__any_sync(0xffffffffu, m == 0)) break;
#pragma unroll
    for (int i = 0; i < 8; i++) ld16(&u[4 * i], sb, so, OFF_ST + i * 128);
    load_frags<NF>(a, sb, uo, t);
  }
  float v[4];
#pragma unroll
  for (int k = 0; k < 4; k++)
    v[k] = ((__uint_as_float(u[k]) + __uint_as_float(u[4 + k])) + (__uint_as_float(u[8 + k]) + __uint_as_float(u[12 + k]))) +
           ((__uint_as_float(u[16 + k]) + __uint_as_float(u[20 + k])) + (__uint_as_float(u[24 + k]) + __uint_as_float(u[28 + k])));
  ln_scalars(v[1], v[0], m0, r0, zero); ln_scalars(v[3], v[2], m1, r1, zero);
}
struct Stats {
  float s[4] = {0, 0, 0, 0}, d0[4] = {0, 0, 0, 0}, d1[4] = {0, 0, 0, 0};
  __device__ __forceinline__ void add16(const uint32_t* f) {
    mma16816(s, f[0], f[1], f[2], f[3], 0x3f803f80u, 0x3f803f80u);
    mma16816(d0, f[0], f[1], f[2], f[3], f[0], f[2]);
    mma16816(d1, f[0], f[1], f[2], f[3], f[1], f[3]);
  }
  __device__ __forceinline__ float sq0(int g) const { return (g & 1) ? d0[1] : d0[0]; }
  __device__ __forceinline__ float sq1(int g) const { return (g & 1) ? d1[3] : d1[2]; }
};
struct RowStats {
  float s[4] = {0, 0, 0, 0}, u[4] = {0, 0, 0, 0};
  template <int N> __device__ __forceinline__ void add(const uint32_t* y) {
#pragma unroll
    for (int i = 0; i < N; i++) {
      const float lo = bf_lo(y[i]), hi = bf_hi(y[i]);
      const int r = (i & 1) * 2;
      s[r] = fmaf(lo, lo, s[r]); u[r] = fmaf(hi, hi, u[r]); s[r + 1] += lo; u[r + 1] += hi;
    }
  }
  __device__ __forceinline__ uint32_t fold() {
    uint32_t x = 0;
#pragma unroll
    for (int i = 0; i < 4; i++) { s[i] += u[i]; u[i] = 0; x |= __float_as_uint(s[i]); }
    return x;
  }
  __device__ __forceinline__ void store(uint8_t* sb, uint32_t sto, uint32_t t) {
    fold();
#pragma unroll
    for (int i = 0; i < 4; i++) s[i] += __shfl_xor_sync(0xffffffffu, s[i], 1);
#pragma unroll
    for (int i = 0; i < 4; i++) s[i] += __shfl_xor_sync(0xffffffffu, s[i], 2);
    if ((t & 3) == 0) st16(sb, sto + (t >> 5) * 1024 + (t & 28) * 4, OFF_ST, __float_as_uint(s[0]) | 1u, __float_as_uint(s[1]), __float_as_uint(s[2]), __float_as_uint(s[3]));
  }
};
template <bool SET> __device__ __forceinline__ void add_piece(float* acc, uint32_t sm) {
#pragma unroll
  for (int i = 0; i < 4; i++) {
    uint32_t v[4];
    lds128(v, sm + i * 2048);
#pragma unroll
    for (int k = 0; k < 4; k++) {
      acc[8 * i + 2 * k] = SET ? bf_lo(v[k]) : acc[8 * i + 2 * k] + bf_lo(v[k]);
      acc[8 * i + 2 * k + 1] = SET ? bf_hi(v[k]) : acc[8 * i + 2 * k + 1] + bf_hi(v[k]);
    }
  }
}

#define TS(i) do {} while (0)
#define TSP(i) do {} while (0)
#define TSH(i) do {} while (0)

__host__ __device__ constexpr int role_j(int c) {
  return MAP == 0 ? (MC ? (c >> 1) & 7 : c & 7) : MAP == 1 ? c >> 4 : MAP == 2 ? ((c >> 6) << 2) | ((c >> 1) & 3)
       : MAP == 3 ? ((c >> 5) << 1) | ((c >> 2) & 1) : ((c >> 3) & 3) * 2 + ((c >> 2) & 1);
}
__host__ __device__ constexpr int role_rb(int c) {
  return MAP == 0 ? (MC ? (c >> 4) * 2 + (c & 1) : c >> 3) : MAP == 1 ? c & 15 : MAP == 2 ? ((c >> 3) & 7) * 2 + (c & 1)
       : MAP == 3 ? ((c >> 3) & 3) * 4 + (c & 3) : (c >> 5) * 4 + (c & 3);
}

__device__ __forceinline__ uint32_t row_off(int rb, int wg, uint32_t t) { return (rb * 128 + wg + ((t >> 5) * 16 + (t & 15)) * 2) * (2 * DM); }

__device__ __forceinline__ const __nv_bfloat16* wo_src(const __nv_bfloat16* wo, int k, int u, int j) {
  const int ko = k < 512 ? (k >> 6) * 72 + (k & 63) : ((k >> 3) & 7) * 72 + 64 + (k & 7);
  return wo + ko * 576 + (u < 8 ? j * 64 + u * 8 : 512 + j * 8);
}

struct Params {
  const __nv_bfloat16 *x, *wqkv, *wo, *wg, *wu, *wd;
  __nv_bfloat16* out;
  uint8_t* scr;
  uint8_t* times;
  unsigned zero;
};

__device__ __forceinline__ void tma_prefetch(const CUtensorMap* m, int c0, int c1) {
  asm volatile("cp.async.bulk.prefetch.tensor.2d.L2.global [%0, {%1, %2}];" ::"l"(m), "r"(c0), "r"(c1) : "memory");
}
__device__ __forceinline__ void fill_packed(int sl, uint32_t par, const uint8_t* src, uint32_t rank, uint32_t own) {
  mbar_wait(bar_empty(sl), par);
  mbar_expect_tx(bar_full(sl), PSLOT);
  if (MC) bulk_load_mc(own + slot_addr(sl) + rank * (PSLOT / 2), src + rank * (PSLOT / 2), PSLOT / 2, own + bar_full(sl));
  else bulk_load(slot_addr(sl), src, PSLOT, bar_full(sl));
}

__global__ void __launch_bounds__(384, 1)
fused_kernel(const __grid_constant__ CUtensorMap map_x, const __grid_constant__ CUtensorMap map_wg,
             const __grid_constant__ CUtensorMap map_wu, const __grid_constant__ CUtensorMap map_wd, const Params P) {
  const int wg = __shfl_sync(0xffffffffu, threadIdx.x >> 7, 0);
  const int cta = blockIdx.x, rank = MC ? cta & 1 : 0, j = role_j(cta), rb = role_rb(cta);
  const uint32_t own = win();
  unsigned* const flags = (unsigned*)(P.scr + OFF_FLAGS);
  if (__shfl_sync(0xffffffffu, threadIdx.x >> 5, 0) == 11) {
    if (threadIdx.x == 352) {
#pragma unroll
      for (int i = 0; i < 14; i++) { mbar_init(bar_full(i), 1); mbar_init(bar_empty(i), MC && i < 12 ? 4 : 2); }
      mbar_init(bar_full(14), 1); mbar_init(bar_empty(14), 1);
      asm volatile("fence.mbarrier_init.release.cluster;" ::: "memory");
      if (smem_u32(smem_raw) != own + SB) asm volatile("trap;");
    }
    __syncwarp();
    bar_arrive(0, 384);
    if (MC) asm volatile("barrier.cluster.arrive.relaxed.aligned;" ::: "memory");
    if (threadIdx.x == 352) {
#pragma unroll 1
      for (int c = 0; c < 9; c++) {
        mbar_expect_tx(bar_full(c), SLOT);
        tma_3d(own + slot_addr(c), &map_x, c * 64, rb * 64, 0, own + bar_full(c));
      }
    }
  } else {
    const bool on = threadIdx.x < 324;
    const int k = rb * 36 + (on ? threadIdx.x / 36 : 0) * 4 + (threadIdx.x & 3), u = (threadIdx.x % 36) >> 2;
    const uint4* s = (const uint4*)(P.wqkv + k * 1728 + j * 72 + u * 8);
    const uint4 vk = ldg_line(s + 72), vv = ldg_line(s + 144);
    const unsigned ep0 = *(volatile unsigned*)&flags[(72 + cta) * 8];
    if (MC) asm volatile("barrier.cluster.arrive.relaxed.aligned;" ::: "memory");
    bar_sync(0, 384);
    uint8_t* d = P.scr + OFF_WPACK + j * 24 * PSLOT;
    if (on) {
      const uint32_t dkv = (k / 48) * PSLOT + u * 768 + (k % 48) * 16;
      st16(d, dkv, 0, vk.x, vk.y, vk.z, vk.w);
      st16(d, dkv, 9 * 768, vv.x, vv.y, vv.z, vv.w);
    }
    asm volatile("fence.proxy.async.global;" ::: "memory");
    bar_arrive(NB_PUB + 3, 384);
    if (threadIdx.x == 351) sts32(SM_EPOCH, ep0);
    if (wg == 2) bar_sync(NB_PUB + 1, 96);
  }
  __syncwarp();
  if (MC) asm volatile("barrier.cluster.wait.acquire.aligned;" ::: "memory");

  if (wg == 2) {
    asm volatile("setmaxnreg.dec.sync.aligned.u32 24;");
    const int pw = __shfl_sync(0xffffffffu, (threadIdx.x >> 5) & 3, 0), lane = threadIdx.x & 31;
    auto tile_col = [](int t, int h, int j) { return t < 9 ? j * 576 + t * 64 : (t == 9 && h) ? 512 : ((j + ((h ? 0x05760 : 0x04123) >> (4 * (t - 9)))) & 7) * 64; };
    auto prefetch_tile = [&](int t) {
#pragma unroll 1
      for (int b = rb; b < 18; b += 16) {
        const int h = b & 1, k = b >> 1;
        if (t < 9) tma_prefetch(h ? &map_wu : &map_wg, tile_col(t, h, j), k * 64);
        else if (t != 13 || !h) tma_prefetch(&map_wd, tile_col(t, h, j), j * 576 + k * 64);
      }
    };
    if (pw == 0) {
      if (lane == 0) {
        flag_wait(&flags[j * 8], (lds32(SM_EPOCH) + 1) * 16);
        TSP(7);
        asm volatile("fence.proxy.async.global;" ::: "memory");
        const uint8_t* wp = P.scr + OFF_WPACK + j * 24 * PSLOT;
#pragma unroll 1
        for (int s = 0; s < 3; s++) fill_packed(9 + s, 1, wp + s * PSLOT, rank, own);
#pragma unroll 1
        for (int L = 0; L < 2; L++) {
#pragma unroll 1
          for (int s = 0; s < 21; s++) {
            if (s == 9 && L == 0) { flag_wait(&flags[(56 + j) * 8], (lds32(SM_EPOCH) + 1) * 16); asm volatile("fence.proxy.async.global;" ::: "memory"); }
            fill_packed(s < 9 ? s : s - 9, s >= 9 && s < 18, wp + (s + 3) * PSLOT, rank, own);
          }
#pragma unroll 1
          for (int t = 0; t < 14; t++) {
            const int p = t - 9;
            const CUtensorMap* ma = p < 0 ? &map_wg : &map_wd;
            const CUtensorMap* mb = p < 0 ? &map_wu : &map_wd;
            const int ca = tile_col(t, 0, j), cb = tile_col(t, 1, j), r0 = p < 0 ? 0 : j * 576;
            if (L * 14 + t + PF_AHEAD < 28) prefetch_tile((t + PF_AHEAD) % 14);
#pragma unroll 1
            for (int k = 0; k < 9; k++) {
              if (TH && t == 0 && k >= TH && k < 6) { mbar_wait(bar_full(k - TH), 1); for (int i = 0; i < THD; i++) __nanosleep(0); }
              mbar_wait(bar_empty(k), t & 1);
              mbar_expect_tx(bar_full(k), p == 4 ? 8192 : SLOT);
              const int r = r0 + (p < 0 || k == 8 ? k : k < 3 ? k + 5 : k - 3) * 64;
              if (MC) {
                if (p != 4) tma_2d_mc(own + slot_addr(k) + rank * 8192, rank ? mb : ma, rank ? cb : ca, r, own + bar_full(k));
                else if ((k & 1) == rank) tma_2d_mc(own + slot_addr(k), ma, ca, r, own + bar_full(k));
              } else {
                tma_2d(slot_addr(k), ma, ca, r, bar_full(k));
                if (p != 4) tma_2d(slot_addr(k) + 8192, mb, cb, r, bar_full(k));
              }
            }
            if (p == 1 && L == 0) {
              l2_prefetch(wp + rb * (24 * PSLOT / 16), 24 * PSLOT / 16);
#pragma unroll 1
              for (int s = 0; s < 3; s++) fill_packed(9 + s, 1, wp + s * PSLOT, rank, own);
            }
          }
        }
        flags[(72 + cta) * 8] = lds32(SM_EPOCH) + 1;
      }
    } else if (pw < 3) {
      const int hw = pw - 1;
      const uint32_t ep = __shfl_sync(0xffffffffu, lds32(SM_EPOCH), 0);
      uint8_t* const sb = P.scr + (rb * 2 + hw) * STRM;
      const uint32_t xs = slot_addr(12) + hw * SLOT, fb = bar_full(12) + hw * 8;
      uint32_t hph = 0;
#pragma unroll 1
      for (int L = 0; L < 2; L++) {
        const uint32_t tag = ep * 2 + L + 1;
        bar_sync(NB_FREE + hw, 160);
        if (rb > 0) hint_wait(sb + OFF_HINT + 512 + j * 128, tag);
        uint32_t bad;
        do {
          if (rb > 0) {
            if (lane == 0) {
              mbar_expect_tx(bar_full(14) + hw * 128, 3072);
              bulk_load(own + ytail(hw * 2), sb + OFF_HALO + (L * 8 + j) * 3072, 1536, own + bar_full(14) + hw * 128);
              bulk_load(own + ytail(hw * 2 + 1), sb + OFF_HALO + (L * 8 + j) * 3072 + 1536, 1536, own + bar_full(14) + hw * 128);
            }
            mbar_wait(bar_full(14) + hw * 128, hph);
            hph ^= 1;
          }
          bad = 0;
#pragma unroll 1
          for (int c = 0; c < 3; c++) {
            uint32_t u[4] = {tag, 0, 0, 0}, v[4] = {tag, 0, 0, 0};
            if (rb > 0) { lds128(u, ytail(hw * 2) + c * 512 + lane * 16); lds128(v, ytail(hw * 2 + 1) + c * 512 + lane * 16); }
            bad |= (u[0] ^ tag) | (v[0] ^ tag);
#pragma unroll
            for (int i = 0; i < 3; i++) { sts32(xs + KSTG + (c * 3 + i) * 128 + lane * 4, u[i + 1]); sts32(xs + (c * 3 + i) * 128 + lane * 4, v[i + 1]); }
          }
        } while (__any_sync(0xffffffffu, bad != 0));
        bar_arrive(NB_HALO + hw, 160);
#pragma unroll 1
        for (int p = 0; p < 4; p++) {
          if (L == 0 && p == 3) flag_wait(flags + (40 + rb) * 8, (ep + 1) * 8);
          bar_sync(NB_FREE + hw, 160);
          TSH(L * 12 + p * 3);
          hint_wait(sb + OFF_HINT + (lane & 3) * 128, (ep * 13 + L * 7 + p + 3) * 8);
          TSH(L * 12 + p * 3 + 1);
          if (lane == 0) {
            mbar_expect_tx(fb, p ? 16384 : 15360);
            bulk_load(own + xs, sb + OFF_P + j * PSRC + (p & 1) * 16384, p ? 16384 : 8192, own + fb);
            if (p == 0) bulk_load(own + xs + 8192, sb + OFF_P + j * PSRC + 32768, 7168, own + fb);
          }
          TSH(L * 12 + p * 3 + 2);
        }
      }
    } else {
      auto clear = [&](int t) {
        const uint32_t so = rb * 2 * STRM + (threadIdx.x & 31) * 16;
#pragma unroll 1
        for (int i = 0; i < 18; i++) {
          st16(P.scr, so + t * TILE + j * 9216 + i * 512, 0, 0, 0, 0, 0);
          st16(P.scr, so + t * TILE + j * 9216 + i * 512, STRM, 0, 0, 0, 0);
          __nanosleep(0);
        }
        if (t != 1) {
          st16(P.scr, so + (t ? t - 1 : 0) * 4096 + j * 512, OFF_ST, 0, 0, 0, 0);
          st16(P.scr, so + (t ? t - 1 : 0) * 4096 + j * 512, OFF_ST + STRM, 0, 0, 0, 0);
        }
      };
      bar_sync(NB_PUB + 3, 384);
      if (lane == 0) flag_signal(&flags[j * 8]);
      TSP(5);
      bar_sync(NB_PUB + 2, 288);
      if (lane == 0) flag_signal(&flags[(56 + j) * 8]);
      TSP(4);
      if (lane == 0) {
#pragma unroll 1
        for (int t = 0; t < PF_AHEAD; t++) prefetch_tile(t);
      }
      __syncwarp();
#pragma unroll 1
      for (int L = 0; L < 2; L++) {
        timed_wait(bar_empty(13), L);
#pragma unroll 1
        for (int t = L ^ 1; t < 4 - 2 * L; t++) clear(t);
        __syncwarp();
        if (lane == 0 && L == 0) flag_signal(flags + (40 + rb) * 8);
      }
      timed_wait(bar_empty(12), 0);
      if (MC) asm volatile("barrier.cluster.arrive.relaxed.aligned;\nbarrier.cluster.wait.aligned;" ::: "memory");
    }
  } else {
    asm volatile("setmaxnreg.inc.sync.aligned.u32 240;");
    const int w = __shfl_sync(0xffffffffu, (threadIdx.x >> 5) & 3, 0);
    const bool leader = (threadIdx.x & 127) == 0;
    const Rel rel{MC ? (threadIdx.x & 95) == 0 : leader, MC ? cta_window(w & 1) : 0};
    uint8_t* const sb = P.scr + (rb * 2 + wg) * STRM;
    uint8_t* const hint = sb + OFF_HINT + w * 128;
    auto hint_target = [](int e) { return (lds32(SM_EPOCH) * 13 + e + 1) * 8; };
    TS(0);
    uint32_t a[144];
#pragma unroll 1
    for (int L = 0; L < 2; L++) {
      uint32_t m0, m1; float r0, r1;
      if (L == 0) {
        Stats st;
        const int lane = tid_() & 31, g = lane >> 2;
        const int row = w * 16 + (lane & 15);
        const uint32_t ra = SB + wg * 8192 + row * 128;
        const uint32_t pt = tid_(), pu = (pt % 36) >> 2, pk = rb * 36 + (pt < 108 ? pt / 36 : 0) * 4 + (pt & 3);
        uint4 pv[3];
#pragma unroll
        for (int i = 0; i < 3; i++) pv[i] = ldg_line(wg ? wo_src(P.wo, pk + i * 12, pu, j) : P.wqkv + (pk + i * 12) * 1728 + j * 72 + pu * 8);
#pragma unroll
        for (int c = 0; c < 9; c++) {
          mbar_wait(bar_full(c), 0);
          if (c == 0) TS(60); if (c == 8) TS(62);
#pragma unroll
          for (int kk = 0; kk < 4; kk++) ldsm4(&a[c * 16 + kk * 4], ra + (((kk * 2 + (lane >> 4)) ^ (row & 7)) << 4) + c * SLOT);
          if (c == 8) {
            uint32_t y[18], z[4];
#pragma unroll
            for (int i = 0; i < 4; i++) ldsm4(&y[4 * i], ra + (((i * 2 + (lane >> 4)) ^ (row & 7)) << 4) + j * SLOT);
            ldsm4(z, ra + ((j ^ (row & 7)) << 4) + 8 * SLOT);
            y[16] = z[0]; y[17] = z[1];
            bar_sync(NB_WG + wg, 128);
#pragma unroll
            for (int i = 0; i < 9; i++) rel(i);
            if (pt < 108) {
#pragma unroll
              for (int i = 0; i < 3; i++) {
                const uint32_t k = pk + i * 12;
                st16(P.scr, (j * 24 + wg * 6 + k / 96) * PSLOT + pu * 1536 + (k % 96) * 16, OFF_WPACK + 12 * PSLOT, pv[i].x, pv[i].y, pv[i].z, pv[i].w);
              }
            }
            asm volatile("fence.proxy.async.global;" ::: "memory");
            bar_arrive(NB_PUB + 2, 288);
            store_own(y, sb, OFF_X2, j, tid_());
          }
#pragma unroll
          for (int kk = 0; kk < 4; kk++) st.add16(&a[c * 16 + kk * 4]);
        }
        const int dl = (lane & ~3) | (g >> 1);
        ln_scalars(st.s[0], __shfl_sync(0xffffffffu, st.sq0(g), dl), m0, r0, P.zero);
        ln_scalars(st.s[2], __shfl_sync(0xffffffffu, st.sq1(g), dl), m1, r1, P.zero);
      } else {
        hint_wait(hint, hint_target(6));
        TS(61);
        gather_ln<3 * D_KV>(a, sb, OFF_X2, 8192, m0, m1, r0, r1, P.zero);
      }
      TS(1 + L * 20);
      uint32_t kf[18], qf[18];
      {
        float acc[72];
        if (wg == 1) bar_sync(NB_ORD1, 256);
        mma_pass<144, PS_KV, 3, 256, D_KV, true>(acc, a, DESC_KV, 1, rel, wg == 0 ? NB_ORD1 : -1, sb, OFF_X2, L ^ 1, m0, m1, ytail(wg * 2));
        r0 = ln_rstd(r0, acc[0], P.zero); r1 = ln_rstd(r1, acc[0], P.zero);
        uint32_t vf[18];
#pragma unroll
        for (int c = 0; c < 9; c++) {
          kf[2 * c] = pack_bf16(acc[4 * c] * r0, acc[4 * c + 1] * r0);
          kf[2 * c + 1] = pack_bf16(acc[4 * c + 2] * r1, acc[4 * c + 3] * r1);
          vf[c] = pack_bf16(acc[36 + 4 * c] * r0, acc[36 + 4 * c + 1] * r0);
          vf[9 + c] = pack_bf16(acc[36 + 4 * c + 2] * r1, acc[36 + 4 * c + 3] * r1);
        }
        TS(2 + L * 20);
        const uint32_t l16 = (tid_() & 31) * 16, xs = slot_addr(12) + wg * SLOT + w * 1152;
#pragma unroll
        for (int i = 0; i < 4; i++) stsm4(xs + w * 1152 + 1152 + i * 512 + l16, vf[4 * i], vf[4 * i + 1], vf[4 * i + 2], vf[4 * i + 3]);
        sts32(xs + w * 1152 + 1152 + 2048 + l16 / 4, vf[16]); sts32(xs + w * 1152 + 1152 + 2176 + l16 / 4, vf[17]);
        if (w < 3) {
          stsm4(xs + KSTG + 1152 + l16, kf[1], kf[3], kf[5], kf[7]);
          stsm4(xs + KSTG + 1152 + 512 + l16, kf[9], kf[11], kf[13], kf[15]);
          sts32(xs + KSTG + 1152 + 1024 + l16 / 4, kf[17]);
        } else if (rb < 15) {
          const uint32_t tag = lds32(SM_EPOCH) * 2 + L + 1;
          const uint32_t ho = l16 + (L * 8 + j) * 3072;
#pragma unroll
          for (int c = 0; c < 3; c++) {
            st16(sb, ho, 2 * STRM + OFF_HALO + c * 512, tag, kf[6 * c + 1], kf[6 * c + 3], kf[6 * c + 5]);
            st16(sb, ho, 2 * STRM + OFF_HALO + 1536 + c * 512, tag, vf[9 + 3 * c], vf[10 + 3 * c], vf[11 + 3 * c]);
          }
          hint_post(sb + 2 * STRM + OFF_HINT + 512 + j * 128);
        }
      }
      lds128(a, ytail(wg * 2) + tid_() * 16);
      bar_arrive(NB_FREE + wg, 160);
      {
        float acc[36];
        if (wg == 1) bar_sync(NB_ORD1, 256);
        mma_pass<72, PS_Q, 6, 256, 0, false>(acc, a, DESC_Q, 0, rel, -1);
#pragma unroll
        for (int c = 0; c < 9; c++) {
          qf[2 * c] = pack_bf16(acc[4 * c] * r0, acc[4 * c + 1] * r0);
          qf[2 * c + 1] = pack_bf16(acc[4 * c + 2] * r1, acc[4 * c + 3] * r1);
        }
      }
      TS(3 + L * 20);
      uint32_t xr[18];
      {
        uint32_t kh[12], vt[28];
        const int tid = tid_(), g = (tid >> 2) & 7, q = tid & 3;
        bar_sync(NB_HALO + wg, 160);
        {
          const uint32_t xs = slot_addr(12) + wg * SLOT + w * 1152 + (tid & 31) * 16;
#pragma unroll
          for (int i = 0; i < 3; i++) ldsm4(&kh[4 * i], xs + KSTG + i * 512);
#pragma unroll
          for (int i = 0; i < 7; i++) ldsm4t(&vt[4 * i], xs + w * 1152 + i * 512);
        }
        TS(14 + L * 20);
        const bool nohalo = (rb == 0 && w == 0);
        const bool le0 = 2 * q <= g, le1 = 2 * q + 1 <= g;
        const uint32_t M = (le0 ? 0xffffu : 0u) | (le1 ? 0xffff0000u : 0u);
        const float sc = 0.23570226039551584f * 1.4426950408889634f;
        float l[16], t[8];
#pragma unroll
        for (int h = 0; h < 4; h++) {
          const uint32_t qa0 = q >= h ? qf[4 * h] : 0u, qa1 = q >= h ? qf[4 * h + 1] : 0u;
          const uint32_t qc0 = q <= h ? qf[4 * h + 4] : 0u, qc1 = q <= h ? qf[4 * h + 5] : 0u;
          float sm[4] = {0, 0, 0, 0}, s0[4] = {0, 0, 0, 0}, s1[4] = {0, 0, 0, 0};
          mma16816(s0, qa0, qa1, qf[4 * h + 2], qf[4 * h + 3], kf[4 * h], kf[4 * h + 2]);
          mma16816(s1, qa0, qa1, qf[4 * h + 2], qf[4 * h + 3], kf[4 * h + 1], kf[4 * h + 3]);
          mma16816(sm, qa0, qa1, qf[4 * h + 2], qf[4 * h + 3], kh[2 * h], kh[2 * h + 1]);
          mma1688(s0, qc0, qc1, kf[4 * h + 4]);
          mma1688(s1, qc0, qc1, kf[4 * h + 5]);
          mma1688(sm, qc0, qc1, kh[2 * h + 2]);
          if (nohalo) sm[0] = sm[1] = -1e9f / 0.23570226039551584f;
          l[4 * h] = le0 ? s0[0] : sm[0]; l[4 * h + 1] = le1 ? s0[1] : sm[1];
          l[4 * h + 2] = le0 ? s1[2] : s0[2]; l[4 * h + 3] = le1 ? s1[3] : s0[3];
        }
#pragma unroll
        for (int i = 0; i < 8; i++) t[i] = fmaxf(l[2 * i], l[2 * i + 1]);
#pragma unroll
        for (int i = 0; i < 8; i++) t[i] = fmaxf(t[i], __shfl_xor_sync(0xffffffffu, t[i], 1));
#pragma unroll
        for (int i = 0; i < 8; i++) t[i] = fmaxf(t[i], __shfl_xor_sync(0xffffffffu, t[i], 2)) * sc;
#pragma unroll
        for (int i = 0; i < 8; i++) { l[2 * i] = ex2(fmaf(l[2 * i], sc, -t[i])); l[2 * i + 1] = ex2(fmaf(l[2 * i + 1], sc, -t[i])); t[i] = l[2 * i] + l[2 * i + 1]; }
#pragma unroll
        for (int i = 0; i < 8; i++) t[i] += __shfl_xor_sync(0xffffffffu, t[i], 1);
#pragma unroll
        for (int i = 0; i < 8; i++) t[i] += __shfl_xor_sync(0xffffffffu, t[i], 2);
        uint32_t pf[16];
#pragma unroll
        for (int i = 0; i < 8; i++) {
          float r; asm("rcp.approx.ftz.f32 %0, %1;" : "=f"(r) : "f"(t[i]));
          const uint32_t p = pack_bf16(l[2 * i] * r, l[2 * i + 1] * r);
          pf[2 * i] = p & ~M; pf[2 * i + 1] = p & M;
        }
#pragma unroll
        for (int c = 0; c < 9; c++) {
          const int h = c == 8 ? 3 : c >> 1;
          float o[4] = {0, 0, 0, 0};
          mma16816(o, pf[4 * h], 0u, pf[4 * h + 1], pf[4 * h + 2], vt[c], vt[9 + c]);
          mma1688(o, 0u, pf[4 * h + 3], vt[18 + c]);
          if (c == 2 || c == 4 || c == 6) {
            float e[4] = {0, 0, 0, 0};
            mma16816(e, pf[4 * h - 4], 0u, pf[4 * h - 3], pf[4 * h - 2], vt[c], vt[9 + c]);
            mma1688(e, 0u, pf[4 * h - 1], vt[18 + c]);
            if (q < h) { o[0] = e[0]; o[1] = e[1]; o[2] = e[2]; o[3] = e[3]; }
          }
          qf[2 * c] = pack_bf16(o[0], o[1]); qf[2 * c + 1] = pack_bf16(o[2], o[3]);
        }
        store_own(qf, sb, OFF_O, j, tid);
        hint_post(hint);
        bar_arrive(NB_ORD1 - wg, 256);
        load_own(xr, sb, OFF_X2, j);
      }
      TS(4 + L * 20);
      {
        hint_wait(hint, hint_target(L * 7));
        TS(5 + L * 20);
        load_frags<N_WO>(a, sb, OFF_O, tid_());
        float acc[36];
        if (wg == 0) bar_sync(NB_ORD0, 256);
        load_frags<36, N_WO>(a, sb, OFF_O, tid_());
        TS(19 + L * 20);
        mma_pass<72, PS_WO, 6, 256, D_WO, false>(acc, a, DESC_Q, 0, rel, -1, sb, OFF_O);
        TS(6 + L * 20);
#pragma unroll
        for (int c = 0; c < 9; c++) {
          xr[2 * c] = bf2_add(xr[2 * c], pack_bf16(acc[4 * c], acc[4 * c + 1]));
          xr[2 * c + 1] = bf2_add(xr[2 * c + 1], pack_bf16(acc[4 * c + 2], acc[4 * c + 3]));
        }
        store_own(xr, sb, L * 3 * TILE, j, tid_());
        RowStats rs;
        rs.add<18>(xr);
        rs.store(sb, L * 4096 + j * 128, tid_());
        hint_post(hint);
      }
      TS(16 + L * 20);
      hint_wait(hint, hint_target(L * 7 + 1));
      TS(15 + L * 20);
      gather_ln<4 * D_T0>(a, sb, L * 3 * TILE, L * 4096, m0, m1, r0, r1, P.zero);
      TS(7 + L * 20);
      const uint32_t hb = (L ^ 1) * TILE + j * 9216;
      {
        float ka0, kb0, kc0, ka1, kb1, kc1;
        float acc[64];
        uint32_t hf[16];
        auto geglu = [&](auto chains, uint32_t hsm) {
          constexpr int CH = decltype(chains)::value & 15;
          float r[32];
#pragma unroll
          for (int e = 0; e < 32; e++) {
            float x = acc[e];
            if (e >= CH) x = __uint_as_float(__float_as_uint(x) ^ (__float_as_uint(r[e - CH]) & P.zero));
            if (decltype(chains)::value > 15 && e < 20) {
              const uint32_t ad = (e < 8 ? slot_addr(12) + e * 2048 + wg * 8192 : slot_addr(7 + (e >> 2)) + (e & 3) * 2048) + hsm;
              lds128(&a[48 + 4 * e], e >= CH ? ad ^ (__float_as_uint(r[e - CH]) & P.zero) : ad);
            }
            const bool hi = e & 2;
            float t = x * fmaf(x * x, hi ? kb1 : kb0, hi ? ka1 : ka0);
            asm("tanh.approx.f32 %0, %0;" : "+f"(t));
            const float u = x * acc[32 + e] * (hi ? kc1 : kc0);
            r[e] = fmaf(u, t, u);
            if (e & 1) hf[e >> 1] = pack_bf16(r[e - 1], r[e]);
          }
        };
        if (wg == 1) bar_sync(NB_ORD1, 256);
        mma_pass<128, PS_FF, 4, 2048, D_T0, true>(acc, a, DESC_SW128, 1, rel, NB_ORD1 - wg, sb, L * 3 * TILE, 0, m0, m1);
        TS(8 + L * 20);
        r0 = ln_rstd(r0, acc[0], P.zero); r1 = ln_rstd(r1, acc[0], P.zero);
        ka0 = 0.7978845608028654f * r0; kb0 = 0.035677408136300125f * r0 * r0 * r0; kc0 = 0.5f * r0 * r0;
        ka1 = 0.7978845608028654f * r1; kb1 = 0.035677408136300125f * r1 * r1 * r1; kc1 = 0.5f * r1 * r1;
#pragma unroll 1
        for (int t = 0; t < 8; t++) {
          geglu(IntC<2>(), 0);
          const uint32_t t16 = tid_() * 16;
          if (t < 5) {
            const uint32_t d = (t < 2 ? slot_addr(12) + wg * SLOT + t * 8192 : slot_addr(7) + t * SLOT + wg * 8192) + t16;
#pragma unroll
            for (int i = 0; i < 4; i++)
              sts128(d + i * 2048, hf[4 * i], hf[4 * i + 1], hf[4 * i + 2], hf[4 * i + 3]);
            if (t == 4) asm volatile("fence.proxy.async.shared::cta;" ::: "memory");
          } else {
#pragma unroll
            for (int i = 0; i < 4; i++) st16(sb, hb + (t - 5) * TILE + t16, i * 2048, hf[4 * i], hf[4 * i + 1], hf[4 * i + 2], hf[4 * i + 3]);
          }
          bar_sync(NB_ORD0 + wg, 256);
          mma_pass<128, PS_FF, 4, 2048, 0, false, true>(acc, a, DESC_SW128, t & 1, rel, NB_ORD1 - wg, sb, hb + t16, t == 7);
        }
        TS(9 + L * 20);
        const uint32_t hsm = wg * 8192 + tid_() * 16;
        geglu(IntC<16 + CH_LAST>(), hsm);
#pragma unroll
        for (int i = 0; i < 16; i++) a[128 + i] = hf[i];
      }
      TS(10 + L * 20);
      {
        const uint32_t xs = slot_addr(12) + wg * SLOT;
        auto verify = [&](int p, uint32_t t16) {
          mbar_wait(bar_full(12) + wg * 8, p & 1);
          TS(71 + L * 32 + p * 5);
          const uint32_t ta = p < 2, tb = (p & 1) ? ta : L ^ 1, nb = p ? 4 : 7, sh = p == 0;
          uint32_t m = 0;
#pragma unroll
          for (int s = 0; s < 4; s++) m |= (lds32(xs + s * 2048 + t16) ^ ta) | (lds32(xs + 8192 + ((s * 2048 + t16) >> sh)) ^ tb);
          if (p == 0) {
#pragma unroll
            for (int s = 4; s < 7; s++) m |= lds32(xs + 8192 + s * 1024 + t16 / 2) ^ tb;
          }
          if (__any_sync(0xffffffffu, m & 1)) {
#pragma unroll 1
            for (int s = 0; s < 4 + nb; s++) {
              const bool nar = sh && s >= 4;
              const uint32_t o = nar ? 4096 + s * 1024 + t16 / 2 : s * 2048 + t16;
              uint32_t v[4] = {0, 0, 0, 0};
              do {
                if (nar) ld8(v, sb, j * PSRC + o, OFF_P + 32768 - 8192);
                else ld16(v, sb, j * PSRC + (p & 1) * 16384 + o, OFF_P);
              } while (__any_sync(0xffffffffu, (v[0] ^ (s < 4 ? ta : tb)) & 1));
              sts64(xs + o, v[0], v[1]);
              if (!nar) sts64(xs + o + 8, v[2], v[3]);
            }
            asm volatile("fence.proxy.async.shared::cta;" ::: "memory");
          }
        };
        uint32_t t16 = (a[142] | a[143]) & P.zero;
#pragma unroll 1
        for (int p = 0; p < 4; p++) {
          float acc[64];
          bar_sync(NB_ORD0 + wg + (p ? 0 : t16), 256);
          TS(64 + L * 32 + p * 5);
          if (p == 0) { rel(9); rel(10); rel(11); }
          mma_pass<128, PS_FF, 4, 2048, 0, false, false>(acc, a, DESC_SW128, p & 1, rel, NB_ORD1 - wg, nullptr, 0, 0, 0, 0, 0, [&]() {
            t16 = tid_() * 16;
            if (p) verify(p - 1, t16);
          });
          TS(65 + L * 32 + p * 5);
          if (p == 1 || p == 2) add_piece<false>(acc, xs + t16);
          const uint32_t oa = ((j + (p < 3 ? 1 : 4)) & 7) * PSRC + (p & 1) * 16384 + t16;
#pragma unroll
          for (int i = 0; i < 4; i++)
            st16(sb, oa, OFF_P + i * 2048, (pack_bf16(acc[8 * i], acc[8 * i + 1]) & ~1u) | (p < 2), pack_bf16(acc[8 * i + 2], acc[8 * i + 3]),
                 pack_bf16(acc[8 * i + 4], acc[8 * i + 5]), pack_bf16(acc[8 * i + 6], acc[8 * i + 7]));
          if (p == 0) {
#pragma unroll
            for (int i = 0; i < 8; i++)
              send8(sb, j * 1024 + t16 / 2, OFF_P + 32768 + i * PSRC, xs + 15360 + t16 / 2, i, j,
                    (pack_bf16(acc[32 + 4 * i], acc[33 + 4 * i]) & ~1u) | (L ^ 1), pack_bf16(acc[34 + 4 * i], acc[35 + 4 * i]));
            if (t16 == 0) mbar_arrive(bar_empty(13));
          } else {
            if (p == 2) add_piece<false>(acc + 32, xs + 8192 + t16);
            const uint32_t ob = ((j + (p < 3 ? 7 : 5)) & 7) * PSRC + (p & 1) * 16384 + t16, tb = p == 2 ? L ^ 1 : p < 2;
#pragma unroll
            for (int i = 4; i < 8; i++)
              st16(sb, ob, OFF_P + i * 2048, (pack_bf16(acc[8 * i], acc[8 * i + 1]) & ~1u) | tb, pack_bf16(acc[8 * i + 2], acc[8 * i + 3]),
                   pack_bf16(acc[8 * i + 4], acc[8 * i + 5]), pack_bf16(acc[8 * i + 6], acc[8 * i + 7]));
          }
          hint_post(hint);
          TS(68 + L * 32 + p * 5);
          if (p == 1) {
            float s0 = 0.f, s1 = 0.f, s2 = 0.f, s3 = 0.f;
#pragma unroll
            for (int s = 0; s < 8; s++) {
              uint32_t u, v;
              lds64(u, v, xs + 8192 + s * 1024 + t16 / 2);
              s0 += bf_lo(u); s1 += bf_hi(u); s2 += bf_lo(v); s3 += bf_hi(v);
            }
            sts64(ytail(wg * 2) + t16 / 2, pack_bf16(s0, s1), pack_bf16(s2, s3));
          }
          if (p < 3) bar_arrive(NB_FREE + wg, 160);
          TS(67 + L * 32 + p * 5);
        }
        float acc[32];
        add_piece<true>(acc, xs + t16);
        add_piece<false>(acc, xs + 8192 + t16);
        bar_arrive(NB_FREE + wg, 160);
        load_own(xr, sb, L * 3 * TILE, j);
        bar_sync(NB_ORD0 + wg, 256);
        TS(84 + L * 32);
        mma_pass<64, PS_FFA, 4, 2048, 0, false>(acc, a, DESC_SW128, 0, rel, wg ? -1 : NB_ORD1);
        TS(11 + L * 20);
        const uint32_t t = tid_();
        uint32_t yn[2];
        lds64(yn[0], yn[1], ytail(wg * 2) + t * 8);
        verify(3, t * 16);
        TS(12 + L * 20);
        add_piece<false>(acc, xs + t * 16);
        add_piece<false>(acc, xs + 8192 + t * 16);
#pragma unroll
        for (int i = 0; i < 18; i++) xr[i] = bf2_add(xr[i], i < 16 ? pack_bf16(acc[2 * i], acc[2 * i + 1]) : yn[i - 16]);
        TS(18 + L * 20);
        if (L == 0) {
          store_own(xr, sb, OFF_X2, j, t);
          RowStats rs;
          rs.add<18>(xr);
          rs.store(sb, 8192 + j * 128, t);
          hint_post(hint);
        } else {
          __syncwarp();
#pragma unroll
          for (int i = 0; i < 4; i++) stsm4(xs + i * 2048 + t * 16, xr[4 * i], xr[4 * i + 1], xr[4 * i + 2], xr[4 * i + 3]);
          stsm4(xs + 8192 + t * 16, xr[16], xr[17], 0, 0);
          __syncwarp();
          uint8_t* op = (uint8_t*)P.out + row_off(rb, wg, t);
#pragma unroll
          for (int i = 0; i < 5; i++) {
            uint32_t r[4];
            lds128(r, xs + i * 2048 + t * 16);
            if (i < 4) *(uint4*)(op + i * 32 + j * 128 + (t & 16)) = make_uint4(r[0], r[1], r[2], r[3]);
            else if (!(t & 16)) *(uint4*)(op + 1024 + j * 16) = make_uint4(r[0], r[1], r[2], r[3]);
          }
        }
      }
      TS(13 + L * 20);
    }
    bar_sync(NB_WG + wg, 128);
    if (tid_() == 0) mbar_arrive(bar_empty(12));
  }
}

typedef CUresult (*EncodeFn)(CUtensorMap*, CUtensorMapDataType, cuuint32_t, void*, const cuuint64_t*, const cuuint64_t*, const cuuint32_t*,
                             const cuuint32_t*, CUtensorMapInterleave, CUtensorMapSwizzle, CUtensorMapL2promotion, CUtensorMapFloatOOBfill);

void encode(EncodeFn fn, CUtensorMap* m, const void* p, int rank, const cuuint64_t* dims, const cuuint64_t* str, const cuuint32_t* box) {
  const cuuint32_t es[3] = {1, 1, 1};
  fn(m, CU_TENSOR_MAP_DATA_TYPE_BFLOAT16, rank, const_cast<void*>(p), dims, str, box, es, CU_TENSOR_MAP_INTERLEAVE_NONE,
     CU_TENSOR_MAP_SWIZZLE_128B, CU_TENSOR_MAP_L2_PROMOTION_L2_256B, CU_TENSOR_MAP_FLOAT_OOB_FILL_NONE);
}

}

extern "C" void kernel_launch(void* const* d_in, const int* in_sizes, int n_in, void* d_out, int out_size) {
  (void)in_sizes; (void)n_in; (void)out_size;
  Params P;
  P.x = (const __nv_bfloat16*)d_in[0]; P.wqkv = (const __nv_bfloat16*)d_in[1]; P.wo = (const __nv_bfloat16*)d_in[2];
  P.wg = (const __nv_bfloat16*)d_in[4]; P.wu = (const __nv_bfloat16*)d_in[5]; P.wd = (const __nv_bfloat16*)d_in[6];
  P.out = (__nv_bfloat16*)d_out; P.zero = 0;
  cudaGetSymbolAddress((void**)&P.scr, g_scr);
  void* fnp = nullptr; cudaDriverEntryPointQueryResult qr;
  cudaGetDriverEntryPoint("cuTensorMapEncodeTiled", &fnp, cudaEnableDefault, &qr);
  EncodeFn fn = (EncodeFn)fnp;
  CUtensorMap mx, mg, mu, md;
  { const cuuint64_t dims[3] = {DM, SEQ / 2, 2}, str[2] = {DM * 4, DM * 2}; const cuuint32_t box[3] = {64, 64, 2}; encode(fn, &mx, P.x, 3, dims, str, box); }
  { const cuuint64_t dims[2] = {DFF, DM}, str[1] = {DFF * 2}; const cuuint32_t box[2] = {64, 64}; encode(fn, &mg, P.wg, 2, dims, str, box); encode(fn, &mu, P.wu, 2, dims, str, box); }
  { const cuuint64_t dims[2] = {DM, DFF}, str[1] = {DM * 2}; const cuuint32_t box[2] = {64, 64}; encode(fn, &md, P.wd, 2, dims, str, box); }
  cudaFuncSetAttribute(fused_kernel, cudaFuncAttributeMaxDynamicSharedMemorySize, SMEM_BYTES);
  fused_kernel<<<128, 384, SMEM_BYTES, cudaStreamPerThread>>>(mx, mg, mu, md, P);
}
```

```cpp
#include <cuda_runtime.h>
#include <cuda_bf16.h>
#include <cuda.h>
#include <stdint.h>

#define KV_LEAD 5
#define D_KV 6
#define D_WO 3
#define D_T0 4
#define PF_AHEAD 3
#define CH_LAST 3
#define MC 1
#define MAP 5
#define N_WO 18
#define TH 0
#define THD 0
#define DBG_PS 2
#define SMALLPOS 1
#define TIMING 0

namespace {

constexpr int SEQ = 2048, DM = 576, DFF = 4608;
constexpr uint32_t SB = 1024;
constexpr uint32_t SLOT = 16384;
constexpr uint32_t PSLOT = 13824;
constexpr uint32_t BARS = SB + 14 * SLOT;
constexpr int SMEM_BYTES = 14 * SLOT + 256 + 2560;
__host__ __device__ constexpr uint32_t slot_addr(int s) { return SB + s * SLOT; }
__host__ __device__ constexpr uint32_t bar_full(int s) { return BARS + 8 * s; }
__host__ __device__ constexpr uint32_t bar_empty(int s) { return BARS + 128 + 8 * s; }
enum { NB_ORD0 = 1, NB_ORD1 = 2, NB_WG = 3  , NB_HALO = 5  , NB_FREE = 7  , NB_PUB = 9   };
constexpr uint32_t SM_EPOCH = BARS + 120;
__host__ __device__ constexpr uint32_t ytail(uint32_t k) { return k < 3 ? slot_addr(9) + PSLOT + k * SLOT : BARS + 256; }
constexpr uint32_t KSTG = 9 * 1152;

constexpr uint32_t TILE = 36 * 2048;
constexpr uint32_t OFF_X1 = 0  , OFF_O = TILE, OFF_X2 = 2 * TILE, OFF_ST = 4 * TILE  ;
constexpr uint32_t PSRC = 2 * 16384 + 7 * 1024;
constexpr uint32_t OFF_P = OFF_ST + 3 * 4096, OFF_HALO = OFF_P + 8 * PSRC  , OFF_HINT = OFF_HALO + 2 * 8 * 3072  ,
                   STRM = OFF_HINT + 12 * 128;
constexpr uint32_t OFF_WPACK = 32 * STRM, OFF_FLAGS = OFF_WPACK + 8 * 24 * PSLOT;
__device__ __align__(1024) uint8_t g_scr[OFF_FLAGS + (8 + 64 + 128) * 32];

__device__ __forceinline__ uint32_t smem_u32(const void* p) { return (uint32_t)__cvta_generic_to_shared(p); }
extern __shared__ __align__(1024) uint8_t smem_raw[];
__device__ __forceinline__ uint32_t win() { return MC ? (blockIdx.x & 1) << 24 : 0; }
#define SA(A, W) ".reg .u32 sa;\nadd.u32 sa, " A ", " W ";\n"
__device__ __forceinline__ void mbar_init(uint32_t bar, uint32_t cnt) { asm volatile("{\n" SA("%0", "%2") "mbarrier.init.shared::cta.b64 [sa], %1;\n}" ::"r"(bar), "r"(cnt), "r"(win())); }
__device__ __forceinline__ void mbar_expect_tx(uint32_t bar, uint32_t bytes) { asm volatile("{\n" SA("%0", "%2") "mbarrier.arrive.expect_tx.shared::cta.b64 _, [sa], %1;\n}" ::"r"(bar), "r"(bytes), "r"(win()) : "memory"); }
__device__ __forceinline__ void mbar_arrive(uint32_t bar) { asm volatile("{\n" SA("%0", "%1") "mbarrier.arrive.shared::cta.b64 _, [sa];\n}" ::"r"(bar), "r"(win()) : "memory"); }
__device__ __forceinline__ uint32_t lds32(uint32_t a) { uint32_t v; asm volatile("{\n" SA("%1", "%2") "ld.shared.u32 %0, [sa];\n}" : "=r"(v) : "r"(a), "r"(win()) : "memory"); return v; }
__device__ __forceinline__ void lds64(uint32_t& x, uint32_t& y, uint32_t a) { asm volatile("{\n" SA("%2", "%3") "ld.shared.v2.u32 {%0,%1}, [sa];\n}" : "=r"(x), "=r"(y) : "r"(a), "r"(win()) : "memory"); }
__device__ __forceinline__ void lds128(uint32_t* v, uint32_t a) {
  asm volatile("{\n" SA("%4", "%5") "ld.shared.v4.u32 {%0,%1,%2,%3}, [sa];\n}" : "=r"(v[0]), "=r"(v[1]), "=r"(v[2]), "=r"(v[3]) : "r"(a), "r"(win()) : "memory");
}
__device__ __forceinline__ void stsm4(uint32_t a, uint32_t x, uint32_t y, uint32_t z, uint32_t w) {
  asm volatile("{\n" SA("%0", "%5") "stmatrix.sync.aligned.m8n8.x4.shared.b16 [sa], {%1,%2,%3,%4};\n}" ::"r"(a), "r"(x), "r"(y), "r"(z), "r"(w), "r"(win()) : "memory");
}
__device__ __forceinline__ void ldsm4(uint32_t* v, uint32_t a) {
  asm volatile("{\n" SA("%4", "%5") "ldmatrix.sync.aligned.m8n8.x4.shared.b16 {%0,%1,%2,%3}, [sa];\n}" : "=r"(v[0]), "=r"(v[1]), "=r"(v[2]), "=r"(v[3]) : "r"(a), "r"(win()) : "memory");
}
__device__ __forceinline__ void ldsm4t(uint32_t* v, uint32_t a) {
  asm volatile("{\n" SA("%4", "%5") "ldmatrix.sync.aligned.m8n8.x4.trans.shared.b16 {%0,%1,%2,%3}, [sa];\n}" : "=r"(v[0]), "=r"(v[1]), "=r"(v[2]), "=r"(v[3]) : "r"(a), "r"(win()) : "memory");
}
__device__ __forceinline__ void sts32(uint32_t a, uint32_t x) { asm volatile("{\n" SA("%0", "%2") "st.shared.u32 [sa], %1;\n}" ::"r"(a), "r"(x), "r"(win()) : "memory"); }
__device__ __forceinline__ void sts64(uint32_t a, uint32_t x, uint32_t y) { asm volatile("{\n" SA("%0", "%3") "st.shared.v2.u32 [sa], {%1,%2};\n}" ::"r"(a), "r"(x), "r"(y), "r"(win()) : "memory"); }
__device__ __forceinline__ void sts128(uint32_t a, uint32_t x, uint32_t y, uint32_t z, uint32_t w) {
  asm volatile("{\n" SA("%0", "%5") "st.shared.v4.u32 [sa], {%1,%2,%3,%4};\n}" ::"r"(a), "r"(x), "r"(y), "r"(z), "r"(w), "r"(win()) : "memory");
}
__device__ __forceinline__ void mbar_wait(uint32_t bar, uint32_t parity) {
  asm volatile("{\n.reg .pred p;\n" SA("%0", "%2") "LAB_WAIT:\nmbarrier.try_wait.parity.shared::cta.b64 p, [sa], %1;\n@!p bra LAB_WAIT;\n}" ::"r"(bar), "r"(parity), "r"(win()) : "memory");
}
__device__ __forceinline__ void timed_wait(uint32_t bar, uint32_t par) {
  asm volatile("{\n.reg .pred p;\n.reg .u64 t0, t1;\nmov.u64 t0, %%globaltimer;\nLAB_WD:\n"
               "mbarrier.try_wait.parity.shared::cta.b64 p, [%0], %1, 100000;\n@p bra LAB_OK;\n"
               "mov.u64 t1, %%globaltimer;\nsub.u64 t1, t1, t0;\nsetp.lt.u64 p, t1, 2000000000;\n@p bra LAB_WD;\ntrap;\nLAB_OK:\n}" ::"r"(bar + win()), "r"(par) : "memory");
}
__device__ __forceinline__ void flag_wait(const unsigned* flag, unsigned target) {
  asm volatile("{\n.reg .pred p;\n.reg .u32 v;\nLAB_WAIT:\nld.acquire.gpu.global.u32 v, [%0];\nsub.u32 v, v, %1;\n"
               "setp.lt.s32 p, v, 0;\n@p nanosleep.u32 100;\n@p bra LAB_WAIT;\n}" ::"l"(flag), "r"(target) : "memory");
}
__device__ __forceinline__ void hint_post(uint8_t* p) {
  __syncwarp();
  asm volatile("{\n.reg .pred p;\nelect.sync _|p, 0xffffffff;\n@p red.relaxed.gpu.global.add.u32 [%0], 1;\n}" ::"l"(p) : "memory");
}
__device__ __forceinline__ void hint_wait(const uint8_t* p, uint32_t target) {
  asm volatile("{\n.reg .pred p;\n.reg .u32 v;\nLAB_WAIT:\nld.relaxed.gpu.global.u32 v, [%0];\nsub.u32 v, v, %1;\n"
               "setp.lt.s32 p, v, 0;\nvote.sync.any.pred p, p, 0xffffffff;\n@p bra LAB_WAIT;\n}" ::"l"(p), "r"(target) : "memory");
}
__device__ __forceinline__ void flag_signal(unsigned* flag) { asm volatile("red.release.gpu.global.add.u32 [%0], 1;" ::"l"(flag) : "memory"); }
struct Rel {
  bool on; uint32_t base;
  __device__ __forceinline__ void operator()(int s) const {
    if (on) {
      if (MC) asm volatile("{\n" SA("%0", "%1") "mbarrier.arrive.shared::cluster.b64 _, [sa];\n}" ::"r"(bar_empty(s)), "r"(base) : "memory");
      else mbar_arrive(bar_empty(s));
    }
  }
};
__device__ __forceinline__ uint32_t cta_window(uint32_t rank) { uint32_t a; asm("mapa.shared::cluster.u32 %0, %1, %2;" : "=r"(a) : "r"(0), "r"(rank)); return a; }
__device__ __forceinline__ void tma_2d_mc(uint32_t dst, const CUtensorMap* m, int c0, int c1, uint32_t bar) {
  asm volatile("cp.async.bulk.tensor.2d.shared::cluster.global.mbarrier::complete_tx::bytes.multicast::cluster [%0], [%1, {%3, %4}], [%2], %5;"
               ::"r"(dst), "l"(m), "r"(bar), "r"(c0), "r"(c1), "h"((uint16_t)3) : "memory");
}
__device__ __forceinline__ void bulk_load_mc(uint32_t dst, const void* src, uint32_t bytes, uint32_t bar) {
  asm volatile("cp.async.bulk.shared::cluster.global.mbarrier::complete_tx::bytes.multicast::cluster [%0], [%1], %2, [%3], %4;"
               ::"r"(dst), "l"(src), "r"(bytes), "r"(bar), "h"((uint16_t)3) : "memory");
}
__device__ __forceinline__ void tma_2d(uint32_t dst, const CUtensorMap* m, int c0, int c1, uint32_t bar) {
  asm volatile("cp.async.bulk.tensor.2d.shared::cluster.global.mbarrier::complete_tx::bytes [%0], [%1, {%3, %4}], [%2];"
               ::"r"(dst), "l"(m), "r"(bar), "r"(c0), "r"(c1) : "memory");
}
__device__ __forceinline__ void tma_3d(uint32_t dst, const CUtensorMap* m, int c0, int c1, int c2, uint32_t bar) {
  asm volatile("cp.async.bulk.tensor.3d.shared::cluster.global.mbarrier::complete_tx::bytes [%0], [%1, {%3, %4, %5}], [%2];"
               ::"r"(dst), "l"(m), "r"(bar), "r"(c0), "r"(c1), "r"(c2) : "memory");
}
__device__ __forceinline__ void bulk_load(uint32_t dst, const void* src, uint32_t bytes, uint32_t bar) {
  asm volatile("cp.async.bulk.shared::cluster.global.mbarrier::complete_tx::bytes [%0], [%1], %2, [%3];" ::"r"(dst), "l"(src), "r"(bytes), "r"(bar) : "memory");
}
__device__ __forceinline__ void l2_prefetch(const void* src, uint32_t bytes) { asm volatile("cp.async.bulk.prefetch.L2.global [%0], %1;" ::"l"(src), "r"(bytes) : "memory"); }
__device__ __forceinline__ void wg_fence() { asm volatile("wgmma.fence.sync.aligned;" ::: "memory"); }
__device__ __forceinline__ void wg_commit() { asm volatile("wgmma.commit_group.sync.aligned;" ::: "memory"); }
template <int N> __device__ __forceinline__ void wg_wait() { asm volatile("wgmma.wait_group.sync.aligned %0;" ::"n"(N) : "memory"); }
__device__ __forceinline__ void bar_sync(int id, int n) { asm volatile("bar.sync %0, %1;" ::"r"(id), "r"(n) : "memory"); }
__device__ __forceinline__ void bar_arrive(int id, int n) { asm volatile("bar.arrive %0, %1;" ::"r"(id), "r"(n) : "memory"); }
__device__ __forceinline__ uint32_t pack_bf16(float lo, float hi) { uint32_t r; asm("cvt.rn.bf16x2.f32 %0, %1, %2;" : "=r"(r) : "f"(hi), "f"(lo)); return r; }
__device__ __forceinline__ float bf_lo(uint32_t w) { return __uint_as_float(w << 16); }
__device__ __forceinline__ float bf_hi(uint32_t w) { return __uint_as_float(w & 0xffff0000u); }
__device__ __forceinline__ float bf_round(float x) { return bf_lo(pack_bf16(x, 0.f)); }
__device__ __forceinline__ uint32_t bf2_sub(uint32_t a, uint32_t b) { uint32_t r; asm("sub.rn.bf16x2 %0, %1, %2;" : "=r"(r) : "r"(a), "r"(b)); return r; }
__device__ __forceinline__ uint32_t bf2_add(uint32_t a, uint32_t b) { uint32_t r; asm("add.rn.bf16x2 %0, %1, %2;" : "=r"(r) : "r"(a), "r"(b)); return r; }
#define GADDR(B, O, I) "cvt.u64.u32 ad, " O ";\nadd.u64 ad, ad, " B ";\nadd.u64 ad, ad, " I ";\n"
__device__ __forceinline__ void ld16(uint32_t* v, const uint8_t* ub, uint32_t off, uint32_t imm) {
  asm volatile("{\n.reg .b128 z;\n.reg .b64 x, y, ad;\n" GADDR("%4", "%5", "%6") "ld.relaxed.gpu.global.b128 z, [ad];\n"
               "mov.b128 {x, y}, z;\nmov.b64 {%0,%1}, x;\nmov.b64 {%2,%3}, y;\n}"
               : "=r"(v[0]), "=r"(v[1]), "=r"(v[2]), "=r"(v[3]) : "l"(ub), "r"(off), "l"((uint64_t)imm) : "memory");
}
__device__ __forceinline__ void ld8(uint32_t* v, const uint8_t* ub, uint32_t off, uint32_t imm) {
  asm volatile("{\n.reg .b64 x, ad;\n" GADDR("%2", "%3", "%4") "ld.relaxed.gpu.global.b64 x, [ad];\nmov.b64 {%0,%1}, x;\n}"
               : "=r"(v[0]), "=r"(v[1]) : "l"(ub), "r"(off), "l"((uint64_t)imm) : "memory");
}
__device__ __forceinline__ void st16(uint8_t* ub, uint32_t off, uint32_t imm, uint32_t a, uint32_t b, uint32_t c, uint32_t d) {
  asm volatile("{\n.reg .b128 z;\n.reg .b64 x, y, ad;\n" GADDR("%0", "%1", "%2") "mov.b64 x, {%3,%4};\nmov.b64 y, {%5,%6};\nmov.b128 z, {x, y};\n"
               "st.relaxed.gpu.global.b128 [ad], z;\n}" ::"l"(ub), "r"(off), "l"((uint64_t)imm), "r"(a), "r"(b), "r"(c), "r"(d) : "memory");
}
__device__ __forceinline__ void st8(uint8_t* ub, uint32_t off, uint32_t imm, uint32_t a, uint32_t b) {
  asm volatile("{\n.reg .b64 x, ad;\n" GADDR("%0", "%1", "%2") "mov.b64 x, {%3,%4};\nst.relaxed.gpu.global.b64 [ad], x;\n}"
               ::"l"(ub), "r"(off), "l"((uint64_t)imm), "r"(a), "r"(b) : "memory");
}
__device__ __forceinline__ void send8(uint8_t* ub, uint32_t off, uint32_t imm, uint32_t sm, int i, int j, uint32_t a, uint32_t b) {
  asm volatile("{\n.reg .pred p, q, e;\n.reg .b64 x, ad;\n" SA("%3", "%8") GADDR("%0", "%1", "%2")
               "setp.lt.s32 p, %4, %5;\nsetp.gt.s32 q, %4, %5;\nsetp.eq.s32 e, %4, %5;\nmov.b64 x, {%6,%7};\n"
               "@p st.relaxed.gpu.global.b64 [ad+-1024], x;\n@q st.relaxed.gpu.global.b64 [ad], x;\n@e st.shared.v2.u32 [sa], {%6,%7};\n}"
               ::"l"(ub), "r"(off), "l"((uint64_t)imm), "r"(sm), "r"(i), "r"(j), "r"(a), "r"(b), "r"(win()) : "memory");
}
__device__ __forceinline__ uint4 ldg_line(const void* p) {
  uint4 v; asm volatile("ld.global.nc.L2::128B.v4.u32 {%0,%1,%2,%3}, [%4];" : "=r"(v.x), "=r"(v.y), "=r"(v.z), "=r"(v.w) : "l"(p)); return v;
}
__device__ __forceinline__ void stg4(void* ub, uint32_t off, uint32_t imm, uint32_t v) {
  asm volatile("{\n.reg .b64 ad;\n" GADDR("%0", "%1", "%2") "st.global.u32 [ad], %3;\n}" ::"l"(ub), "r"(off), "l"((uint64_t)imm), "r"(v) : "memory");
}
__device__ __forceinline__ uint32_t tid_() { uint32_t t; asm volatile("mov.u32 %0, %%tid.x;" : "=r"(t)); return t & 127; }
__device__ __forceinline__ uint32_t nz(uint32_t w) { return max(w, 1u); }
__device__ __forceinline__ void mma16816(float (&c)[4], uint32_t a0, uint32_t a1, uint32_t a2, uint32_t a3, uint32_t b0, uint32_t b1) {
  asm("mma.sync.aligned.m16n8k16.row.col.f32.bf16.bf16.f32 {%0,%1,%2,%3}, {%4,%5,%6,%7}, {%8,%9}, {%0,%1,%2,%3};"
               : "+f"(c[0]), "+f"(c[1]), "+f"(c[2]), "+f"(c[3]) : "r"(a0), "r"(a1), "r"(a2), "r"(a3), "r"(b0), "r"(b1));
}
__device__ __forceinline__ void mma1688(float (&c)[4], uint32_t a0, uint32_t a1, uint32_t b0) {
  asm("mma.sync.aligned.m16n8k8.row.col.f32.bf16.bf16.f32 {%0,%1,%2,%3}, {%4,%5}, {%6}, {%0,%1,%2,%3};"
               : "+f"(c[0]), "+f"(c[1]), "+f"(c[2]), "+f"(c[3]) : "r"(a0), "r"(a1), "r"(b0));
}
__device__ __forceinline__ float ex2(float x) { float r; asm("ex2.approx.ftz.f32 %0, %1;" : "=f"(r) : "f"(x)); return r; }
__device__ __forceinline__ float quad_sum(float v) { v += __shfl_xor_sync(0xffffffffu, v, 1); v += __shfl_xor_sync(0xffffffffu, v, 2); return v; }
__device__ __forceinline__ float quad_max(float v) { v = fmaxf(v, __shfl_xor_sync(0xffffffffu, v, 1)); v = fmaxf(v, __shfl_xor_sync(0xffffffffu, v, 2)); return v; }

__device__ __forceinline__ void wgmma_rs_n64(float (&d)[32], uint32_t a0, uint32_t a1, uint32_t a2, uint32_t a3, uint64_t desc, int scale_d) {
  asm volatile("{\n.reg .pred p;\nsetp.ne.b32 p, %37, 0;\n"
    "wgmma.mma_async.sync.aligned.m64n64k16.f32.bf16.bf16 "
    "{%0, %1, %2, %3, %4, %5, %6, %7, %8, %9, %10, %11, %12, %13, %14, %15, %16, %17, %18, %19, %20, %21, %22, %23, %24, %25, %26, %27, %28, %29, %30, %31}, "
    "{%32, %33, %34, %35}, %36, p, 1, 1, 1;\n}\n"
    : "+f"(d[0]), "+f"(d[1]), "+f"(d[2]), "+f"(d[3]), "+f"(d[4]), "+f"(d[5]), "+f"(d[6]), "+f"(d[7]), "+f"(d[8]), "+f"(d[9]), "+f"(d[10]), "+f"(d[11]), "+f"(d[12]), "+f"(d[13]), "+f"(d[14]), "+f"(d[15]), "+f"(d[16]), "+f"(d[17]), "+f"(d[18]), "+f"(d[19]), "+f"(d[20]), "+f"(d[21]), "+f"(d[22]), "+f"(d[23]), "+f"(d[24]), "+f"(d[25]), "+f"(d[26]), "+f"(d[27]), "+f"(d[28]), "+f"(d[29]), "+f"(d[30]), "+f"(d[31])
    : "r"(a0), "r"(a1), "r"(a2), "r"(a3), "l"(desc), "r"(scale_d));
}

__device__ __forceinline__ void wgmma_rs_n72(float (&d)[36], uint32_t a0, uint32_t a1, uint32_t a2, uint32_t a3, uint64_t desc, int scale_d) {
  asm volatile("{\n.reg .pred p;\nsetp.ne.b32 p, %41, 0;\n"
    "wgmma.mma_async.sync.aligned.m64n72k16.f32.bf16.bf16 "
    "{%0, %1, %2, %3, %4, %5, %6, %7, %8, %9, %10, %11, %12, %13, %14, %15, %16, %17, %18, %19, %20, %21, %22, %23, %24, %25, %26, %27, %28, %29, %30, %31, %32, %33, %34, %35}, "
    "{%36, %37, %38, %39}, %40, p, 1, 1, 1;\n}\n"
    : "+f"(d[0]), "+f"(d[1]), "+f"(d[2]), "+f"(d[3]), "+f"(d[4]), "+f"(d[5]), "+f"(d[6]), "+f"(d[7]), "+f"(d[8]), "+f"(d[9]), "+f"(d[10]), "+f"(d[11]), "+f"(d[12]), "+f"(d[13]), "+f"(d[14]), "+f"(d[15]), "+f"(d[16]), "+f"(d[17]), "+f"(d[18]), "+f"(d[19]), "+f"(d[20]), "+f"(d[21]), "+f"(d[22]), "+f"(d[23]), "+f"(d[24]), "+f"(d[25]), "+f"(d[26]), "+f"(d[27]), "+f"(d[28]), "+f"(d[29]), "+f"(d[30]), "+f"(d[31]), "+f"(d[32]), "+f"(d[33]), "+f"(d[34]), "+f"(d[35])
    : "r"(a0), "r"(a1), "r"(a2), "r"(a3), "l"(desc), "r"(scale_d));
}

__device__ __forceinline__ void wgmma_rs_n128(float (&d)[64], uint32_t a0, uint32_t a1, uint32_t a2, uint32_t a3, uint64_t desc, int scale_d) {
  asm volatile("{\n.reg .pred p;\nsetp.ne.b32 p, %69, 0;\n"
    "wgmma.mma_async.sync.aligned.m64n128k16.f32.bf16.bf16 "
    "{%0, %1, %2, %3, %4, %5, %6, %7, %8, %9, %10, %11, %12, %13, %14, %15, %16, %17, %18, %19, %20, %21, %22, %23, %24, %25, %26, %27, %28, %29, %30, %31, %32, %33, %34, %35, %36, %37, %38, %39, %40, %41, %42, %43, %44, %45, %46, %47, %48, %49, %50, %51, %52, %53, %54, %55, %56, %57, %58, %59, %60, %61, %62, %63}, "
    "{%64, %65, %66, %67}, %68, p, 1, 1, 1;\n}\n"
    : "+f"(d[0]), "+f"(d[1]), "+f"(d[2]), "+f"(d[3]), "+f"(d[4]), "+f"(d[5]), "+f"(d[6]), "+f"(d[7]), "+f"(d[8]), "+f"(d[9]), "+f"(d[10]), "+f"(d[11]), "+f"(d[12]), "+f"(d[13]), "+f"(d[14]), "+f"(d[15]), "+f"(d[16]), "+f"(d[17]), "+f"(d[18]), "+f"(d[19]), "+f"(d[20]), "+f"(d[21]), "+f"(d[22]), "+f"(d[23]), "+f"(d[24]), "+f"(d[25]), "+f"(d[26]), "+f"(d[27]), "+f"(d[28]), "+f"(d[29]), "+f"(d[30]), "+f"(d[31]), "+f"(d[32]), "+f"(d[33]), "+f"(d[34]), "+f"(d[35]), "+f"(d[36]), "+f"(d[37]), "+f"(d[38]), "+f"(d[39]), "+f"(d[40]), "+f"(d[41]), "+f"(d[42]), "+f"(d[43]), "+f"(d[44]), "+f"(d[45]), "+f"(d[46]), "+f"(d[47]), "+f"(d[48]), "+f"(d[49]), "+f"(d[50]), "+f"(d[51]), "+f"(d[52]), "+f"(d[53]), "+f"(d[54]), "+f"(d[55]), "+f"(d[56]), "+f"(d[57]), "+f"(d[58]), "+f"(d[59]), "+f"(d[60]), "+f"(d[61]), "+f"(d[62]), "+f"(d[63])
    : "r"(a0), "r"(a1), "r"(a2), "r"(a3), "l"(desc), "r"(scale_d));
}

__device__ __forceinline__ void wgmma_rs_n144(float (&d)[72], uint32_t a0, uint32_t a1, uint32_t a2, uint32_t a3, uint64_t desc, int scale_d) {
  asm volatile("{\n.reg .pred p;\nsetp.ne.b32 p, %77, 0;\n"
    "wgmma.mma_async.sync.aligned.m64n144k16.f32.bf16.bf16 "
    "{%0, %1, %2, %3, %4, %5, %6, %7, %8, %9, %10, %11, %12, %13, %14, %15, %16, %17, %18, %19, %20, %21, %22, %23, %24, %25, %26, %27, %28, %29, %30, %31, %32, %33, %34, %35, %36, %37, %38, %39, %40, %41, %42, %43, %44, %45, %46, %47, %48, %49, %50, %51, %52, %53, %54, %55, %56, %57, %58, %59, %60, %61, %62, %63, %64, %65, %66, %67, %68, %69, %70, %71}, "
    "{%72, %73, %74, %75}, %76, p, 1, 1, 1;\n}\n"
    : "+f"(d[0]), "+f"(d[1]), "+f"(d[2]), "+f"(d[3]), "+f"(d[4]), "+f"(d[5]), "+f"(d[6]), "+f"(d[7]), "+f"(d[8]), "+f"(d[9]), "+f"(d[10]), "+f"(d[11]), "+f"(d[12]), "+f"(d[13]), "+f"(d[14]), "+f"(d[15]), "+f"(d[16]), "+f"(d[17]), "+f"(d[18]), "+f"(d[19]), "+f"(d[20]), "+f"(d[21]), "+f"(d[22]), "+f"(d[23]), "+f"(d[24]), "+f"(d[25]), "+f"(d[26]), "+f"(d[27]), "+f"(d[28]), "+f"(d[29]), "+f"(d[30]), "+f"(d[31]), "+f"(d[32]), "+f"(d[33]), "+f"(d[34]), "+f"(d[35]), "+f"(d[36]), "+f"(d[37]), "+f"(d[38]), "+f"(d[39]), "+f"(d[40]), "+f"(d[41]), "+f"(d[42]), "+f"(d[43]), "+f"(d[44]), "+f"(d[45]), "+f"(d[46]), "+f"(d[47]), "+f"(d[48]), "+f"(d[49]), "+f"(d[50]), "+f"(d[51]), "+f"(d[52]), "+f"(d[53]), "+f"(d[54]), "+f"(d[55]), "+f"(d[56]), "+f"(d[57]), "+f"(d[58]), "+f"(d[59]), "+f"(d[60]), "+f"(d[61]), "+f"(d[62]), "+f"(d[63]), "+f"(d[64]), "+f"(d[65]), "+f"(d[66]), "+f"(d[67]), "+f"(d[68]), "+f"(d[69]), "+f"(d[70]), "+f"(d[71])
    : "r"(a0), "r"(a1), "r"(a2), "r"(a3), "l"(desc), "r"(scale_d));
}

template <int N> struct WG;
template <> struct WG<64>  { static __device__ __forceinline__ void f(float (&d)[32], const uint32_t* a, uint64_t ds, int s) { wgmma_rs_n64(d, a[0], a[1], a[2], a[3], ds, s); } };
template <> struct WG<72>  { static __device__ __forceinline__ void f(float (&d)[36], const uint32_t* a, uint64_t ds, int s) { wgmma_rs_n72(d, a[0], a[1], a[2], a[3], ds, s); } };
template <> struct WG<128> { static __device__ __forceinline__ void f(float (&d)[64], const uint32_t* a, uint64_t ds, int s) { wgmma_rs_n128(d, a[0], a[1], a[2], a[3], ds, s); } };
template <> struct WG<144> { static __device__ __forceinline__ void f(float (&d)[72], const uint32_t* a, uint64_t ds, int s) { wgmma_rs_n144(d, a[0], a[1], a[2], a[3], ds, s); } };

constexpr uint64_t DESC_SW128 = ((uint64_t)(8192 >> 4) << 16) | ((uint64_t)(1024 >> 4) << 32) | (1ull << 62);
constexpr uint64_t DESC_KV = ((uint64_t)(128 >> 4) << 16) | ((uint64_t)(768 >> 4) << 32);
constexpr uint64_t DESC_Q = ((uint64_t)(128 >> 4) << 16) | ((uint64_t)(1536 >> 4) << 32);

template <int V> struct IntC { static constexpr int value = V; };
enum { PS_KV, PS_Q, PS_WO, PS_FF, PS_FFA   };
template <int PS> __host__ __device__ constexpr int pass_slot(int i) {
  return PS == PS_KV ? (i < 3 ? 9 + i : i - 3) : PS == PS_WO ? 6 + i : i;
}

__device__ __forceinline__ void load_frag(uint32_t (&a)[144], int i, const uint8_t* sb, uint32_t uo, uint32_t t) {
  if (i < 32) ld16(&a[4 * i], sb, uo + t * 16, i * 2048);
  else { ld8(&a[4 * i], sb, uo + t * 8, i * 2048); ld8(&a[4 * i + 2], sb, uo + t * 8, i * 2048 + 1024); }
}
__device__ __forceinline__ void store_own(const uint32_t (&y)[18], uint8_t* sb, uint32_t uo, int j, uint32_t t) {
#pragma unroll
  for (int i = 0; i < 4; i++) st16(sb, uo + j * 8192 + t * 16, i * 2048, nz(y[4 * i]), y[4 * i + 1], y[4 * i + 2], y[4 * i + 3]);
  st8(sb, uo + j * 1024 + t * 8, 65536, nz(y[16]), y[17]);
}
__device__ __forceinline__ void load_own(uint32_t* y, const uint8_t* sb, uint32_t uo, int j) {
  const uint32_t t = tid_();
#pragma unroll
  for (int i = 0; i < 4; i++) ld16(&y[4 * i], sb, uo + j * 8192 + t * 16, i * 2048);
  ld8(&y[16], sb, uo + j * 1024 + t * 8, 65536);
}

struct NoTail { __device__ __forceinline__ void operator()() const {} };
template <int N, int PS, int KPS, int KSTEP, int CHK, bool SUB, bool HREL = false, class Tail = NoTail>
__device__ __forceinline__ void mma_pass(float (&acc)[N / 2], uint32_t (&a)[144], uint64_t desc, uint32_t par, const Rel& rel, int bar_id,
                                         const uint8_t* sb = nullptr, uint32_t uo = 0, uint32_t flag = 0, uint32_t m0 = 0, uint32_t m1 = 0, uint32_t park = 0, Tail tail = Tail()) {
  constexpr int NS = 36 / KPS;
  auto check = [&](int lo, int hi, uint32_t m0_) {
    while (true) {
      uint32_t m = m0_;
#pragma unroll
      for (int i = hi - 1; i >= lo; i--) m = min(m, i < 32 ? a[4 * i] : min(a[4 * i], a[4 * i + 2]));
      if (!__any_sync(0xffffffffu, (m | flag) == 0)) break;
      const uint32_t t = tid_();
#pragma unroll
      for (int i = lo; i < hi; i++) load_frag(a, i, sb, uo, t);
    }
  };
#pragma unroll
  for (int s = 0; s < NS; s++) {
    const int sl = pass_slot<PS>(s);
    if (CHK && s == 0 && !SUB) check(0, CHK * KPS, ~0u);
    if (CHK && s == CHK) check(CHK * KPS, 36, lds32(SM_EPOCH) | 1);
    if (SUB) {
#pragma unroll
      for (int i = s * KPS * 4; i < (s + 1) * KPS * 4; i += 2) { a[i] = bf2_sub(a[i], m0); a[i + 1] = bf2_sub(a[i + 1], m1); }
    }
    if (PS == PS_KV && s == 0) sts128(park + tid_() * 16, a[0], a[1], a[2], a[3]);
    mbar_wait(bar_full(sl), sl < 9 ? par : par ^ 1);
    wg_fence();
#pragma unroll
    for (int kk = 0; kk < KPS; kk++)
      WG<N>::f(acc, &a[(s * KPS + kk) * 4], desc + ((slot_addr(sl) + kk * KSTEP) >> 4), (s | kk) || PS == PS_FFA);
    wg_commit();
    if (s == (PS == PS_KV ? KV_LEAD : NS - 1) && bar_id >= 0) bar_arrive(bar_id, 256);
    if (s > 0) {
      wg_wait<1>();
      if (!(PS == PS_WO && s > 3)) rel(pass_slot<PS>(s - 1));
    }
    if (HREL && s == 3 && flag) {
#pragma unroll
      for (int i = 0; i < 12; i++) ld16(&a[4 * i], sb, uo, (i >> 2) * TILE + (i & 3) * 2048);
    }
  }
  tail();
  wg_wait<0>();
  if (PS != PS_WO) rel(pass_slot<PS>(NS - 1));
}

template <int NF, int N0 = 0> __device__ __forceinline__ void load_frags(uint32_t (&a)[144], const uint8_t* sb, uint32_t uo, uint32_t t) {
#pragma unroll
  for (int i = N0; i < NF; i++) load_frag(a, i, sb, uo, t);
}
__device__ __forceinline__ void ln_scalars(float s1, float s2, uint32_t& m, float& var, uint32_t zero) {
  const float mean = s1 * (1.f / DM);
  var = s2 * (1.f / DM) - mean * mean;
  m = pack_bf16(mean, mean) ^ (__float_as_uint(var) & zero);
}
__device__ __forceinline__ float ln_rstd(float var, float after, uint32_t zero) {
  var = __uint_as_float(__float_as_uint(var) ^ (__float_as_uint(after) & zero));
  float sd, r;
  asm("sqrt.approx.ftz.f32 %0, %1;" : "=f"(sd) : "f"(bf_round(bf_round(fmaxf(var, 0.f)) + 1e-5f)));
  asm("rcp.approx.ftz.f32 %0, %1;" : "=f"(r) : "f"(bf_round(sd)));
  return r;
}
template <int NF> __device__ __forceinline__ void gather_ln(uint32_t (&a)[144], const uint8_t* sb, uint32_t uo, uint32_t sto,
                                          uint32_t& m0, uint32_t& m1, float& r0, float& r1, uint32_t zero) {
  uint32_t u[32];
  const uint32_t t = tid_(), so = sto + (t >> 5) * 1024 + (t & 28) * 4;
#pragma unroll
  for (int i = 0; i < 8; i++) ld16(&u[4 * i], sb, so, OFF_ST + i * 128);
  load_frags<36>(a, sb, uo, t);
  while (true) {
    uint32_t m = a[4 * NF - 4];
#pragma unroll
    for (int i = NF - 2; i >= 0; i--) m = min(m, a[4 * i]);
#pragma unroll
    for (int i = 0; i < 8; i++) m = min(m, u[4 * i]);
    if (!__any_sync(0xffffffffu, m == 0)) break;
#pragma unroll
    for (int i = 0; i < 8; i++) ld16(&u[4 * i], sb, so, OFF_ST + i * 128);
    load_frags<NF>(a, sb, uo, t);
  }
  float v[4];
#pragma unroll
  for (int k = 0; k < 4; k++)
    v[k] = ((__uint_as_float(u[k]) + __uint_as_float(u[4 + k])) + (__uint_as_float(u[8 + k]) + __uint_as_float(u[12 + k]))) +
           ((__uint_as_float(u[16 + k]) + __uint_as_float(u[20 + k])) + (__uint_as_float(u[24 + k]) + __uint_as_float(u[28 + k])));
  ln_scalars(v[1], v[0], m0, r0, zero); ln_scalars(v[3], v[2], m1, r1, zero);
}
struct Stats {
  float s[4] = {0, 0, 0, 0}, d0[4] = {0, 0, 0, 0}, d1[4] = {0, 0, 0, 0};
  __device__ __forceinline__ void add16(const uint32_t* f) {
    mma16816(s, f[0], f[1], f[2], f[3], 0x3f803f80u, 0x3f803f80u);
    mma16816(d0, f[0], f[1], f[2], f[3], f[0], f[2]);
    mma16816(d1, f[0], f[1], f[2], f[3], f[1], f[3]);
  }
  __device__ __forceinline__ float sq0(int g) const { return (g & 1) ? d0[1] : d0[0]; }
  __device__ __forceinline__ float sq1(int g) const { return (g & 1) ? d1[3] : d1[2]; }
};
struct RowStats {
  float s[4] = {0, 0, 0, 0}, u[4] = {0, 0, 0, 0};
  template <int N> __device__ __forceinline__ void add(const uint32_t* y) {
#pragma unroll
    for (int i = 0; i < N; i++) {
      const float lo = bf_lo(y[i]), hi = bf_hi(y[i]);
      const int r = (i & 1) * 2;
      s[r] = fmaf(lo, lo, s[r]); u[r] = fmaf(hi, hi, u[r]); s[r + 1] += lo; u[r + 1] += hi;
    }
  }
  __device__ __forceinline__ uint32_t fold() {
    uint32_t x = 0;
#pragma unroll
    for (int i = 0; i < 4; i++) { s[i] += u[i]; u[i] = 0; x |= __float_as_uint(s[i]); }
    return x;
  }
  __device__ __forceinline__ void store(uint8_t* sb, uint32_t sto, uint32_t t) {
    fold();
#pragma unroll
    for (int i = 0; i < 4; i++) s[i] += __shfl_xor_sync(0xffffffffu, s[i], 1);
#pragma unroll
    for (int i = 0; i < 4; i++) s[i] += __shfl_xor_sync(0xffffffffu, s[i], 2);
    if ((t & 3) == 0) st16(sb, sto + (t >> 5) * 1024 + (t & 28) * 4, OFF_ST, __float_as_uint(s[0]) | 1u, __float_as_uint(s[1]), __float_as_uint(s[2]), __float_as_uint(s[3]));
  }
};
template <bool SET> __device__ __forceinline__ void add_piece(float* acc, uint32_t sm) {
#pragma unroll
  for (int i = 0; i < 4; i++) {
    uint32_t v[4];
    lds128(v, sm + i * 2048);
#pragma unroll
    for (int k = 0; k < 4; k++) {
      acc[8 * i + 2 * k] = SET ? bf_lo(v[k]) : acc[8 * i + 2 * k] + bf_lo(v[k]);
      acc[8 * i + 2 * k + 1] = SET ? bf_hi(v[k]) : acc[8 * i + 2 * k + 1] + bf_hi(v[k]);
    }
  }
}

#define TS(i) do {} while (0)
#define TSP(i) do {} while (0)
#define TSH(i) do {} while (0)

__host__ __device__ constexpr int cl_grp(int c) { return c < 4 ? 8 + SMALLPOS : c < 36 ? (c - 4) & 7 : 8 + (c - 36) % 7 + ((c - 36) % 7 >= SMALLPOS); }
__host__ __device__ constexpr int cl_mem(int c) { return c < 4 ? c : c < 36 ? (c - 4) >> 3 : (c - 36) / 7; }
__host__ __device__ constexpr int role_j(int c) {
  return MAP == 0 ? (MC ? (c >> 1) & 7 : c & 7) : MAP == 1 ? c >> 4 : MAP == 2 ? ((c >> 6) << 2) | ((c >> 1) & 3)
       : MAP == 3 ? ((c >> 5) << 1) | ((c >> 2) & 1) : MAP == 4 ? ((c >> 3) & 3) * 2 + ((c >> 2) & 1)
       : MAP == 5 ? (cl_grp(c >> 1) >> 3) * 4 + cl_mem(c >> 1) : MAP == 6 ? (cl_grp(c >> 1) >> 2) * 2 + (cl_mem(c >> 1) & 1)
       : ((cl_grp(c >> 1) >> 1) & 3) * 2 + (cl_mem(c >> 1) & 1);
}
__host__ __device__ constexpr int role_rb(int c) {
  return MAP == 0 ? (MC ? (c >> 4) * 2 + (c & 1) : c >> 3) : MAP == 1 ? c & 15 : MAP == 2 ? ((c >> 3) & 7) * 2 + (c & 1)
       : MAP == 3 ? ((c >> 3) & 3) * 4 + (c & 3) : MAP == 4 ? (c >> 5) * 4 + (c & 3)
       : MAP == 5 ? (cl_grp(c >> 1) & 7) * 2 + (c & 1) : MAP == 6 ? (cl_grp(c >> 1) & 3) * 4 + (cl_mem(c >> 1) >> 1) * 2 + (c & 1)
       : ((cl_grp(c >> 1) >> 3) * 2 + (cl_grp(c >> 1) & 1)) * 4 + (cl_mem(c >> 1) >> 1) * 2 + (c & 1);
}

__device__ __forceinline__ uint32_t row_off(int rb, int wg, uint32_t t) { return (rb * 128 + wg + ((t >> 5) * 16 + (t & 15)) * 2) * (2 * DM); }

__device__ __forceinline__ const __nv_bfloat16* wo_src(const __nv_bfloat16* wo, int k, int u, int j) {
  const int ko = k < 512 ? (k >> 6) * 72 + (k & 63) : ((k >> 3) & 7) * 72 + 64 + (k & 7);
  return wo + ko * 576 + (u < 8 ? j * 64 + u * 8 : 512 + j * 8);
}

struct Params {
  const __nv_bfloat16 *x, *wqkv, *wo, *wg, *wu, *wd;
  __nv_bfloat16* out;
  uint8_t* scr;
  uint8_t* times;
  unsigned zero;
};

__device__ __forceinline__ void tma_prefetch(const CUtensorMap* m, int c0, int c1) {
  asm volatile("cp.async.bulk.prefetch.tensor.2d.L2.global [%0, {%1, %2}];" ::"l"(m), "r"(c0), "r"(c1) : "memory");
}
__device__ __forceinline__ void fill_packed(int sl, uint32_t par, const uint8_t* src, uint32_t rank, uint32_t own) {
  mbar_wait(bar_empty(sl), par);
  mbar_expect_tx(bar_full(sl), PSLOT);
  if (MC) bulk_load_mc(own + slot_addr(sl) + rank * (PSLOT / 2), src + rank * (PSLOT / 2), PSLOT / 2, own + bar_full(sl));
  else bulk_load(slot_addr(sl), src, PSLOT, bar_full(sl));
}

__cluster_dims__(2, 1, 1)
__global__ void __launch_bounds__(384, 1)
fused_kernel(const __grid_constant__ CUtensorMap map_x, const __grid_constant__ CUtensorMap map_wg,
             const __grid_constant__ CUtensorMap map_wu, const __grid_constant__ CUtensorMap map_wd, const Params P) {
  const int wg = __shfl_sync(0xffffffffu, threadIdx.x >> 7, 0);
  const int cta = blockIdx.x, rank = MC ? cta & 1 : 0, j = role_j(cta), rb = role_rb(cta);
  const uint32_t own = win();
  unsigned* const flags = (unsigned*)(P.scr + OFF_FLAGS);
  if (__shfl_sync(0xffffffffu, threadIdx.x >> 5, 0) == 11) {
    if (threadIdx.x == 352) {
#pragma unroll
      for (int i = 0; i < 14; i++) { mbar_init(bar_full(i), 1); mbar_init(bar_empty(i), MC && i < 12 ? 4 : 2); }
      mbar_init(bar_full(14), 1); mbar_init(bar_empty(14), 1);
      asm volatile("fence.mbarrier_init.release.cluster;" ::: "memory");
      if (smem_u32(smem_raw) != own + SB) asm volatile("trap;");
    }
    __syncwarp();
    bar_arrive(0, 384);
    if (MC) asm volatile("barrier.cluster.arrive.relaxed.aligned;" ::: "memory");
    if (threadIdx.x == 352) {
#pragma unroll 1
      for (int c = 0; c < 9; c++) {
        mbar_expect_tx(bar_full(c), SLOT);
        tma_3d(own + slot_addr(c), &map_x, c * 64, rb * 64, 0, own + bar_full(c));
      }
    }
  } else {
    const bool on = threadIdx.x < 324;
    const int k = rb * 36 + (on ? threadIdx.x / 36 : 0) * 4 + (threadIdx.x & 3), u = (threadIdx.x % 36) >> 2;
    const uint4* s = (const uint4*)(P.wqkv + k * 1728 + j * 72 + u * 8);
    const uint4 vk = ldg_line(s + 72), vv = ldg_line(s + 144);
    const unsigned ep0 = *(volatile unsigned*)&flags[(72 + cta) * 8];
    if (MC) asm volatile("barrier.cluster.arrive.relaxed.aligned;" ::: "memory");
    bar_sync(0, 384);
    uint8_t* d = P.scr + OFF_WPACK + j * 24 * PSLOT;
    if (on) {
      const uint32_t dkv = (k / 48) * PSLOT + u * 768 + (k % 48) * 16;
      st16(d, dkv, 0, vk.x, vk.y, vk.z, vk.w);
      st16(d, dkv, 9 * 768, vv.x, vv.y, vv.z, vv.w);
    }
    asm volatile("fence.proxy.async.global;" ::: "memory");
    bar_arrive(NB_PUB + 3, 384);
    if (threadIdx.x == 351) sts32(SM_EPOCH, ep0);
    if (wg == 2) bar_sync(NB_PUB + 1, 96);
  }
  __syncwarp();
  if (MC) asm volatile("barrier.cluster.wait.acquire.aligned;" ::: "memory");

  if (wg == 2) {
    asm volatile("setmaxnreg.dec.sync.aligned.u32 24;");
    const int pw = __shfl_sync(0xffffffffu, (threadIdx.x >> 5) & 3, 0), lane = threadIdx.x & 31;
    auto tile_col = [](int t, int h, int j) { return t < 9 ? j * 576 + t * 64 : (t == 9 && h) ? 512 : ((j + ((h ? 0x05760 : 0x04123) >> (4 * (t - 9)))) & 7) * 64; };
    auto prefetch_tile = [&](int t) {
#pragma unroll 1
      for (int b = rb; b < 18; b += 16) {
        const int h = b & 1, k = b >> 1;
        if (t < 9) tma_prefetch(h ? &map_wu : &map_wg, tile_col(t, h, j), k * 64);
        else if (t != 13 || !h) tma_prefetch(&map_wd, tile_col(t, h, j), j * 576 + k * 64);
      }
    };
    if (pw == 0) {
      if (lane == 0) {
        flag_wait(&flags[j * 8], (lds32(SM_EPOCH) + 1) * 16);
        TSP(7);
        asm volatile("fence.proxy.async.global;" ::: "memory");
        const uint8_t* wp = P.scr + OFF_WPACK + j * 24 * PSLOT;
#pragma unroll 1
        for (int s = 0; s < 3; s++) fill_packed(9 + s, 1, wp + s * PSLOT, rank, own);
#pragma unroll 1
        for (int L = 0; L < 2; L++) {
#pragma unroll 1
          for (int s = 0; s < 21; s++) {
            if (s == 9 && L == 0) { flag_wait(&flags[(56 + j) * 8], (lds32(SM_EPOCH) + 1) * 16); asm volatile("fence.proxy.async.global;" ::: "memory"); }
            fill_packed(s < 9 ? s : s - 9, s >= 9 && s < 18, wp + (s + 3) * PSLOT, rank, own);
          }
#pragma unroll 1
          for (int t = 0; t < 14; t++) {
            const int p = t - 9;
            const CUtensorMap* ma = p < 0 ? &map_wg : &map_wd;
            const CUtensorMap* mb = p < 0 ? &map_wu : &map_wd;
            const int ca = tile_col(t, 0, j), cb = tile_col(t, 1, j), r0 = p < 0 ? 0 : j * 576;
            if (L * 14 + t + PF_AHEAD < 28) prefetch_tile((t + PF_AHEAD) % 14);
#pragma unroll 1
            for (int k = 0; k < 9; k++) {
              if (TH && t == 0 && k >= TH && k < 6) { mbar_wait(bar_full(k - TH), 1); for (int i = 0; i < THD; i++) __nanosleep(0); }
              mbar_wait(bar_empty(k), t & 1);
              mbar_expect_tx(bar_full(k), p == 4 ? 8192 : SLOT);
              const int r = r0 + (p < 0 || k == 8 ? k : k < 3 ? k + 5 : k - 3) * 64;
              if (MC) {
                if (p != 4) tma_2d_mc(own + slot_addr(k) + rank * 8192, rank ? mb : ma, rank ? cb : ca, r, own + bar_full(k));
                else if ((k & 1) == rank) tma_2d_mc(own + slot_addr(k), ma, ca, r, own + bar_full(k));
              } else {
                tma_2d(slot_addr(k), ma, ca, r, bar_full(k));
                if (p != 4) tma_2d(slot_addr(k) + 8192, mb, cb, r, bar_full(k));
              }
            }
            if (p == 1 && L == 0) {
              l2_prefetch(wp + rb * (24 * PSLOT / 16), 24 * PSLOT / 16);
#pragma unroll 1
              for (int s = 0; s < 3; s++) fill_packed(9 + s, 1, wp + s * PSLOT, rank, own);
            }
          }
        }
        flags[(72 + cta) * 8] = lds32(SM_EPOCH) + 1;
      }
    } else if (pw < 3) {
      const int hw = pw - 1;
      const uint32_t ep = __shfl_sync(0xffffffffu, lds32(SM_EPOCH), 0);
      uint8_t* const sb = P.scr + (rb * 2 + hw) * STRM;
      const uint32_t xs = slot_addr(12) + hw * SLOT, fb = bar_full(12) + hw * 8;
      uint32_t hph = 0;
#pragma unroll 1
      for (int L = 0; L < 2; L++) {
        const uint32_t tag = ep * 2 + L + 1;
        bar_sync(NB_FREE + hw, 160);
        if (rb > 0) hint_wait(sb + OFF_HINT + 512 + j * 128, tag);
        uint32_t bad;
        do {
          if (rb > 0) {
            if (lane == 0) {
              mbar_expect_tx(bar_full(14) + hw * 128, 3072);
              bulk_load(own + ytail(hw * 2), sb + OFF_HALO + (L * 8 + j) * 3072, 1536, own + bar_full(14) + hw * 128);
              bulk_load(own + ytail(hw * 2 + 1), sb + OFF_HALO + (L * 8 + j) * 3072 + 1536, 1536, own + bar_full(14) + hw * 128);
            }
            mbar_wait(bar_full(14) + hw * 128, hph);
            hph ^= 1;
          }
          bad = 0;
#pragma unroll 1
          for (int c = 0; c < 3; c++) {
            uint32_t u[4] = {tag, 0, 0, 0}, v[4] = {tag, 0, 0, 0};
            if (rb > 0) { lds128(u, ytail(hw * 2) + c * 512 + lane * 16); lds128(v, ytail(hw * 2 + 1) + c * 512 + lane * 16); }
            bad |= (u[0] ^ tag) | (v[0] ^ tag);
#pragma unroll
            for (int i = 0; i < 3; i++) { sts32(xs + KSTG + (c * 3 + i) * 128 + lane * 4, u[i + 1]); sts32(xs + (c * 3 + i) * 128 + lane * 4, v[i + 1]); }
          }
        } while (__any_sync(0xffffffffu, bad != 0));
        bar_arrive(NB_HALO + hw, 160);
#pragma unroll 1
        for (int p = 0; p < 4; p++) {
          if (L == 0 && p == 3) flag_wait(flags + (40 + rb) * 8, (ep + 1) * 8);
          bar_sync(NB_FREE + hw, 160);
          TSH(L * 12 + p * 3);
          hint_wait(sb + OFF_HINT + (lane & 3) * 128, (ep * 13 + L * 7 + p + 3) * 8);
          TSH(L * 12 + p * 3 + 1);
          if (lane == 0) {
            mbar_expect_tx(fb, p ? 16384 : 15360);
            bulk_load(own + xs, sb + OFF_P + j * PSRC + (p & 1) * 16384, p ? 16384 : 8192, own + fb);
            if (p == 0) bulk_load(own + xs + 8192, sb + OFF_P + j * PSRC + 32768, 7168, own + fb);
          }
          TSH(L * 12 + p * 3 + 2);
        }
      }
    } else {
      auto clear = [&](int t) {
        const uint32_t so = rb * 2 * STRM + (threadIdx.x & 31) * 16;
#pragma unroll 1
        for (int i = 0; i < 18; i++) {
          st16(P.scr, so + t * TILE + j * 9216 + i * 512, 0, 0, 0, 0, 0);
          st16(P.scr, so + t * TILE + j * 9216 + i * 512, STRM, 0, 0, 0, 0);
          __nanosleep(0);
        }
        if (t != 1) {
          st16(P.scr, so + (t ? t - 1 : 0) * 4096 + j * 512, OFF_ST, 0, 0, 0, 0);
          st16(P.scr, so + (t ? t - 1 : 0) * 4096 + j * 512, OFF_ST + STRM, 0, 0, 0, 0);
        }
      };
      bar_sync(NB_PUB + 3, 384);
      if (lane == 0) flag_signal(&flags[j * 8]);
      TSP(5);
      bar_sync(NB_PUB + 2, 288);
      if (lane == 0) flag_signal(&flags[(56 + j) * 8]);
      TSP(4);
      if (lane == 0) {
#pragma unroll 1
        for (int t = 0; t < PF_AHEAD; t++) prefetch_tile(t);
      }
      __syncwarp();
#pragma unroll 1
      for (int L = 0; L < 2; L++) {
        timed_wait(bar_empty(13), L);
#pragma unroll 1
        for (int t = L ^ 1; t < 4 - 2 * L; t++) clear(t);
        __syncwarp();
        if (lane == 0 && L == 0) flag_signal(flags + (40 + rb) * 8);
      }
      timed_wait(bar_empty(12), 0);
      if (MC) asm volatile("barrier.cluster.arrive.relaxed.aligned;\nbarrier.cluster.wait.aligned;" ::: "memory");
    }
  } else {
    asm volatile("setmaxnreg.inc.sync.aligned.u32 240;");
    const int w = __shfl_sync(0xffffffffu, (threadIdx.x >> 5) & 3, 0);
    const bool leader = (threadIdx.x & 127) == 0;
    const Rel rel{MC ? (threadIdx.x & 95) == 0 : leader, MC ? cta_window(w & 1) : 0};
    uint8_t* const sb = P.scr + (rb * 2 + wg) * STRM;
    uint8_t* const hint = sb + OFF_HINT + w * 128;
    auto hint_target = [](int e) { return (lds32(SM_EPOCH) * 13 + e + 1) * 8; };
    TS(0);
    uint32_t a[144];
#pragma unroll 1
    for (int L = 0; L < 2; L++) {
      uint32_t m0, m1; float r0, r1;
      if (L == 0) {
        Stats st;
        const int lane = tid_() & 31, g = lane >> 2;
        const int row = w * 16 + (lane & 15);
        const uint32_t ra = SB + wg * 8192 + row * 128;
        const uint32_t pt = tid_(), pu = (pt % 36) >> 2, pk = rb * 36 + (pt < 108 ? pt / 36 : 0) * 4 + (pt & 3);
        uint4 pv[3];
#pragma unroll
        for (int i = 0; i < 3; i++) pv[i] = ldg_line(wg ? wo_src(P.wo, pk + i * 12, pu, j) : P.wqkv + (pk + i * 12) * 1728 + j * 72 + pu * 8);
#pragma unroll
        for (int c = 0; c < 9; c++) {
          mbar_wait(bar_full(c), 0);
          if (c == 0) TS(60); if (c == 8) TS(62);
#pragma unroll
          for (int kk = 0; kk < 4; kk++) ldsm4(&a[c * 16 + kk * 4], ra + (((kk * 2 + (lane >> 4)) ^ (row & 7)) << 4) + c * SLOT);
          if (c == 8) {
            uint32_t y[18], z[4];
#pragma unroll
            for (int i = 0; i < 4; i++) ldsm4(&y[4 * i], ra + (((i * 2 + (lane >> 4)) ^ (row & 7)) << 4) + j * SLOT);
            ldsm4(z, ra + ((j ^ (row & 7)) << 4) + 8 * SLOT);
            y[16] = z[0]; y[17] = z[1];
            bar_sync(NB_WG + wg, 128);
#pragma unroll
            for (int i = 0; i < 9; i++) rel(i);
            if (pt < 108) {
#pragma unroll
              for (int i = 0; i < 3; i++) {
                const uint32_t k = pk + i * 12;
                st16(P.scr, (j * 24 + wg * 6 + k / 96) * PSLOT + pu * 1536 + (k % 96) * 16, OFF_WPACK + 12 * PSLOT, pv[i].x, pv[i].y, pv[i].z, pv[i].w);
              }
            }
            asm volatile("fence.proxy.async.global;" ::: "memory");
            bar_arrive(NB_PUB + 2, 288);
            store_own(y, sb, OFF_X2, j, tid_());
          }
#pragma unroll
          for (int kk = 0; kk < 4; kk++) st.add16(&a[c * 16 + kk * 4]);
        }
        const int dl = (lane & ~3) | (g >> 1);
        ln_scalars(st.s[0], __shfl_sync(0xffffffffu, st.sq0(g), dl), m0, r0, P.zero);
        ln_scalars(st.s[2], __shfl_sync(0xffffffffu, st.sq1(g), dl), m1, r1, P.zero);
      } else {
        hint_wait(hint, hint_target(6));
        TS(61);
        gather_ln<3 * D_KV>(a, sb, OFF_X2, 8192, m0, m1, r0, r1, P.zero);
      }
      TS(1 + L * 20);
      uint32_t kf[18], qf[18];
      {
        float acc[72];
        if (wg == 1) bar_sync(NB_ORD1, 256);
        mma_pass<144, PS_KV, 3, 256, D_KV, true>(acc, a, DESC_KV, 1, rel, wg == 0 ? NB_ORD1 : -1, sb, OFF_X2, L ^ 1, m0, m1, ytail(wg * 2));
        r0 = ln_rstd(r0, acc[0], P.zero); r1 = ln_rstd(r1, acc[0], P.zero);
        uint32_t vf[18];
#pragma unroll
        for (int c = 0; c < 9; c++) {
          kf[2 * c] = pack_bf16(acc[4 * c] * r0, acc[4 * c + 1] * r0);
          kf[2 * c + 1] = pack_bf16(acc[4 * c + 2] * r1, acc[4 * c + 3] * r1);
          vf[c] = pack_bf16(acc[36 + 4 * c] * r0, acc[36 + 4 * c + 1] * r0);
          vf[9 + c] = pack_bf16(acc[36 + 4 * c + 2] * r1, acc[36 + 4 * c + 3] * r1);
        }
        TS(2 + L * 20);
        const uint32_t l16 = (tid_() & 31) * 16, xs = slot_addr(12) + wg * SLOT + w * 1152;
#pragma unroll
        for (int i = 0; i < 4; i++) stsm4(xs + w * 1152 + 1152 + i * 512 + l16, vf[4 * i], vf[4 * i + 1], vf[4 * i + 2], vf[4 * i + 3]);
        sts32(xs + w * 1152 + 1152 + 2048 + l16 / 4, vf[16]); sts32(xs + w * 1152 + 1152 + 2176 + l16 / 4, vf[17]);
        if (w < 3) {
          stsm4(xs + KSTG + 1152 + l16, kf[1], kf[3], kf[5], kf[7]);
          stsm4(xs + KSTG + 1152 + 512 + l16, kf[9], kf[11], kf[13], kf[15]);
          sts32(xs + KSTG + 1152 + 1024 + l16 / 4, kf[17]);
        } else if (rb < 15) {
          const uint32_t tag = lds32(SM_EPOCH) * 2 + L + 1;
          const uint32_t ho = l16 + (L * 8 + j) * 3072;
#pragma unroll
          for (int c = 0; c < 3; c++) {
            st16(sb, ho, 2 * STRM + OFF_HALO + c * 512, tag, kf[6 * c + 1], kf[6 * c + 3], kf[6 * c + 5]);
            st16(sb, ho, 2 * STRM + OFF_HALO + 1536 + c * 512, tag, vf[9 + 3 * c], vf[10 + 3 * c], vf[11 + 3 * c]);
          }
          hint_post(sb + 2 * STRM + OFF_HINT + 512 + j * 128);
        }
      }
      lds128(a, ytail(wg * 2) + tid_() * 16);
      bar_arrive(NB_FREE + wg, 160);
      {
        float acc[36];
        if (wg == 1) bar_sync(NB_ORD1, 256);
        mma_pass<72, PS_Q, 6, 256, 0, false>(acc, a, DESC_Q, 0, rel, -1);
#pragma unroll
        for (int c = 0; c < 9; c++) {
          qf[2 * c] = pack_bf16(acc[4 * c] * r0, acc[4 * c + 1] * r0);
          qf[2 * c + 1] = pack_bf16(acc[4 * c + 2] * r1, acc[4 * c + 3] * r1);
        }
      }
      TS(3 + L * 20);
      uint32_t xr[18];
      {
        uint32_t kh[12], vt[28];
        const int tid = tid_(), g = (tid >> 2) & 7, q = tid & 3;
        bar_sync(NB_HALO + wg, 160);
        {
          const uint32_t xs = slot_addr(12) + wg * SLOT + w * 1152 + (tid & 31) * 16;
#pragma unroll
          for (int i = 0; i < 3; i++) ldsm4(&kh[4 * i], xs + KSTG + i * 512);
#pragma unroll
          for (int i = 0; i < 7; i++) ldsm4t(&vt[4 * i], xs + w * 1152 + i * 512);
        }
        TS(14 + L * 20);
        const bool nohalo = (rb == 0 && w == 0);
        const bool le0 = 2 * q <= g, le1 = 2 * q + 1 <= g;
        const uint32_t M = (le0 ? 0xffffu : 0u) | (le1 ? 0xffff0000u : 0u);
        const float sc = 0.23570226039551584f * 1.4426950408889634f;
        float l[16], t[8];
#pragma unroll
        for (int h = 0; h < 4; h++) {
          const uint32_t qa0 = q >= h ? qf[4 * h] : 0u, qa1 = q >= h ? qf[4 * h + 1] : 0u;
          const uint32_t qc0 = q <= h ? qf[4 * h + 4] : 0u, qc1 = q <= h ? qf[4 * h + 5] : 0u;
          float sm[4] = {0, 0, 0, 0}, s0[4] = {0, 0, 0, 0}, s1[4] = {0, 0, 0, 0};
          mma16816(s0, qa0, qa1, qf[4 * h + 2], qf[4 * h + 3], kf[4 * h], kf[4 * h + 2]);
          mma16816(s1, qa0, qa1, qf[4 * h + 2], qf[4 * h + 3], kf[4 * h + 1], kf[4 * h + 3]);
          mma16816(sm, qa0, qa1, qf[4 * h + 2], qf[4 * h + 3], kh[2 * h], kh[2 * h + 1]);
          mma1688(s0, qc0, qc1, kf[4 * h + 4]);
          mma1688(s1, qc0, qc1, kf[4 * h + 5]);
          mma1688(sm, qc0, qc1, kh[2 * h + 2]);
          if (nohalo) sm[0] = sm[1] = -1e9f / 0.23570226039551584f;
          l[4 * h] = le0 ? s0[0] : sm[0]; l[4 * h + 1] = le1 ? s0[1] : sm[1];
          l[4 * h + 2] = le0 ? s1[2] : s0[2]; l[4 * h + 3] = le1 ? s1[3] : s0[3];
        }
#pragma unroll
        for (int i = 0; i < 8; i++) t[i] = fmaxf(l[2 * i], l[2 * i + 1]);
#pragma unroll
        for (int i = 0; i < 8; i++) t[i] = fmaxf(t[i], __shfl_xor_sync(0xffffffffu, t[i], 1));
#pragma unroll
        for (int i = 0; i < 8; i++) t[i] = fmaxf(t[i], __shfl_xor_sync(0xffffffffu, t[i], 2)) * sc;
#pragma unroll
        for (int i = 0; i < 8; i++) { l[2 * i] = ex2(fmaf(l[2 * i], sc, -t[i])); l[2 * i + 1] = ex2(fmaf(l[2 * i + 1], sc, -t[i])); t[i] = l[2 * i] + l[2 * i + 1]; }
#pragma unroll
        for (int i = 0; i < 8; i++) t[i] += __shfl_xor_sync(0xffffffffu, t[i], 1);
#pragma unroll
        for (int i = 0; i < 8; i++) t[i] += __shfl_xor_sync(0xffffffffu, t[i], 2);
        uint32_t pf[16];
#pragma unroll
        for (int i = 0; i < 8; i++) {
          float r; asm("rcp.approx.ftz.f32 %0, %1;" : "=f"(r) : "f"(t[i]));
          const uint32_t p = pack_bf16(l[2 * i] * r, l[2 * i + 1] * r);
          pf[2 * i] = p & ~M; pf[2 * i + 1] = p & M;
        }
#pragma unroll
        for (int c = 0; c < 9; c++) {
          const int h = c == 8 ? 3 : c >> 1;
          float o[4] = {0, 0, 0, 0};
          mma16816(o, pf[4 * h], 0u, pf[4 * h + 1], pf[4 * h + 2], vt[c], vt[9 + c]);
          mma1688(o, 0u, pf[4 * h + 3], vt[18 + c]);
          if (c == 2 || c == 4 || c == 6) {
            float e[4] = {0, 0, 0, 0};
            mma16816(e, pf[4 * h - 4], 0u, pf[4 * h - 3], pf[4 * h - 2], vt[c], vt[9 + c]);
            mma1688(e, 0u, pf[4 * h - 1], vt[18 + c]);
            if (q < h) { o[0] = e[0]; o[1] = e[1]; o[2] = e[2]; o[3] = e[3]; }
          }
          qf[2 * c] = pack_bf16(o[0], o[1]); qf[2 * c + 1] = pack_bf16(o[2], o[3]);
        }
        store_own(qf, sb, OFF_O, j, tid);
        hint_post(hint);
        bar_arrive(NB_ORD1 - wg, 256);
        load_own(xr, sb, OFF_X2, j);
      }
      TS(4 + L * 20);
      {
        hint_wait(hint, hint_target(L * 7));
        TS(5 + L * 20);
        load_frags<N_WO>(a, sb, OFF_O, tid_());
        float acc[36];
        if (wg == 0) bar_sync(NB_ORD0, 256);
        load_frags<36, N_WO>(a, sb, OFF_O, tid_());
        TS(19 + L * 20);
        mma_pass<72, PS_WO, 6, 256, D_WO, false>(acc, a, DESC_Q, 0, rel, -1, sb, OFF_O);
        TS(6 + L * 20);
#pragma unroll
        for (int c = 0; c < 9; c++) {
          xr[2 * c] = bf2_add(xr[2 * c], pack_bf16(acc[4 * c], acc[4 * c + 1]));
          xr[2 * c + 1] = bf2_add(xr[2 * c + 1], pack_bf16(acc[4 * c + 2], acc[4 * c + 3]));
        }
        store_own(xr, sb, L * 3 * TILE, j, tid_());
        RowStats rs;
        rs.add<18>(xr);
        rs.store(sb, L * 4096 + j * 128, tid_());
        hint_post(hint);
      }
      TS(16 + L * 20);
      hint_wait(hint, hint_target(L * 7 + 1));
      TS(15 + L * 20);
      gather_ln<4 * D_T0>(a, sb, L * 3 * TILE, L * 4096, m0, m1, r0, r1, P.zero);
      TS(7 + L * 20);
      const uint32_t hb = (L ^ 1) * TILE + j * 9216;
      {
        float ka0, kb0, kc0, ka1, kb1, kc1;
        float acc[64];
        uint32_t hf[16];
        auto geglu = [&](auto chains, uint32_t hsm) {
          constexpr int CH = decltype(chains)::value & 15;
          float r[32];
#pragma unroll
          for (int e = 0; e < 32; e++) {
            float x = acc[e];
            if (e >= CH) x = __uint_as_float(__float_as_uint(x) ^ (__float_as_uint(r[e - CH]) & P.zero));
            if (decltype(chains)::value > 15 && e < 20) {
              const uint32_t ad = (e < 8 ? slot_addr(12) + e * 2048 + wg * 8192 : slot_addr(7 + (e >> 2)) + (e & 3) * 2048) + hsm;
              lds128(&a[48 + 4 * e], e >= CH ? ad ^ (__float_as_uint(r[e - CH]) & P.zero) : ad);
            }
            const bool hi = e & 2;
            float t = x * fmaf(x * x, hi ? kb1 : kb0, hi ? ka1 : ka0);
            asm("tanh.approx.f32 %0, %0;" : "+f"(t));
            const float u = x * acc[32 + e] * (hi ? kc1 : kc0);
            r[e] = fmaf(u, t, u);
            if (e & 1) hf[e >> 1] = pack_bf16(r[e - 1], r[e]);
          }
        };
        if (wg == 1) bar_sync(NB_ORD1, 256);
        mma_pass<128, PS_FF, 4, 2048, D_T0, true>(acc, a, DESC_SW128, 1, rel, NB_ORD1 - wg, sb, L * 3 * TILE, 0, m0, m1);
        TS(8 + L * 20);
        r0 = ln_rstd(r0, acc[0], P.zero); r1 = ln_rstd(r1, acc[0], P.zero);
        ka0 = 0.7978845608028654f * r0; kb0 = 0.035677408136300125f * r0 * r0 * r0; kc0 = 0.5f * r0 * r0;
        ka1 = 0.7978845608028654f * r1; kb1 = 0.035677408136300125f * r1 * r1 * r1; kc1 = 0.5f * r1 * r1;
#pragma unroll 1
        for (int t = 0; t < 8; t++) {
          geglu(IntC<2>(), 0);
          const uint32_t t16 = tid_() * 16;
          if (t < 5) {
            const uint32_t d = (t < 2 ? slot_addr(12) + wg * SLOT + t * 8192 : slot_addr(7) + t * SLOT + wg * 8192) + t16;
#pragma unroll
            for (int i = 0; i < 4; i++)
              sts128(d + i * 2048, hf[4 * i], hf[4 * i + 1], hf[4 * i + 2], hf[4 * i + 3]);
            if (t == 4) asm volatile("fence.proxy.async.shared::cta;" ::: "memory");
          } else {
#pragma unroll
            for (int i = 0; i < 4; i++) st16(sb, hb + (t - 5) * TILE + t16, i * 2048, hf[4 * i], hf[4 * i + 1], hf[4 * i + 2], hf[4 * i + 3]);
          }
          bar_sync(NB_ORD0 + wg, 256);
          mma_pass<128, PS_FF, 4, 2048, 0, false, true>(acc, a, DESC_SW128, t & 1, rel, NB_ORD1 - wg, sb, hb + t16, t == 7);
        }
        TS(9 + L * 20);
        const uint32_t hsm = wg * 8192 + tid_() * 16;
        geglu(IntC<16 + CH_LAST>(), hsm);
#pragma unroll
        for (int i = 0; i < 16; i++) a[128 + i] = hf[i];
      }
      TS(10 + L * 20);
      {
        const uint32_t xs = slot_addr(12) + wg * SLOT;
        auto verify = [&](int p, uint32_t t16) {
          mbar_wait(bar_full(12) + wg * 8, p & 1);
          TS(71 + L * 32 + p * 5);
          const uint32_t ta = p < 2, tb = (p & 1) ? ta : L ^ 1, nb = p ? 4 : 7, sh = p == 0;
          uint32_t m = 0;
#pragma unroll
          for (int s = 0; s < 4; s++) m |= (lds32(xs + s * 2048 + t16) ^ ta) | (lds32(xs + 8192 + ((s * 2048 + t16) >> sh)) ^ tb);
          if (p == 0) {
#pragma unroll
            for (int s = 4; s < 7; s++) m |= lds32(xs + 8192 + s * 1024 + t16 / 2) ^ tb;
          }
          if (__any_sync(0xffffffffu, m & 1)) {
#pragma unroll 1
            for (int s = 0; s < 4 + nb; s++) {
              const bool nar = sh && s >= 4;
              const uint32_t o = nar ? 4096 + s * 1024 + t16 / 2 : s * 2048 + t16;
              uint32_t v[4] = {0, 0, 0, 0};
              do {
                if (nar) ld8(v, sb, j * PSRC + o, OFF_P + 32768 - 8192);
                else ld16(v, sb, j * PSRC + (p & 1) * 16384 + o, OFF_P);
              } while (__any_sync(0xffffffffu, (v[0] ^ (s < 4 ? ta : tb)) & 1));
              sts64(xs + o, v[0], v[1]);
              if (!nar) sts64(xs + o + 8, v[2], v[3]);
            }
            asm volatile("fence.proxy.async.shared::cta;" ::: "memory");
          }
        };
        uint32_t t16 = (a[142] | a[143]) & P.zero;
#pragma unroll 1
        for (int p = 0; p < 4; p++) {
          float acc[64];
          bar_sync(NB_ORD0 + wg + (p ? 0 : t16), 256);
          TS(64 + L * 32 + p * 5);
          if (p == 0) { rel(9); rel(10); rel(11); }
          mma_pass<128, PS_FF, 4, 2048, 0, false, false>(acc, a, DESC_SW128, p & 1, rel, NB_ORD1 - wg, nullptr, 0, 0, 0, 0, 0, [&]() {
            t16 = tid_() * 16;
            if (p) verify(p - 1, t16);
          });
          TS(65 + L * 32 + p * 5);
          if (p == 1 || p == 2) add_piece<false>(acc, xs + t16);
          const uint32_t oa = ((j + (p < 3 ? 1 : 4)) & 7) * PSRC + (p & 1) * 16384 + t16;
#pragma unroll
          for (int i = 0; i < 4; i++)
            st16(sb, oa, OFF_P + i * 2048, (pack_bf16(acc[8 * i], acc[8 * i + 1]) & ~1u) | (p < 2), pack_bf16(acc[8 * i + 2], acc[8 * i + 3]),
                 pack_bf16(acc[8 * i + 4], acc[8 * i + 5]), pack_bf16(acc[8 * i + 6], acc[8 * i + 7]));
          if (p == 0) {
#pragma unroll
            for (int i = 0; i < 8; i++)
              send8(sb, j * 1024 + t16 / 2, OFF_P + 32768 + i * PSRC, xs + 15360 + t16 / 2, i, j,
                    (pack_bf16(acc[32 + 4 * i], acc[33 + 4 * i]) & ~1u) | (L ^ 1), pack_bf16(acc[34 + 4 * i], acc[35 + 4 * i]));
            if (t16 == 0) mbar_arrive(bar_empty(13));
          } else {
            if (p == 2) add_piece<false>(acc + 32, xs + 8192 + t16);
            const uint32_t ob = ((j + (p < 3 ? 7 : 5)) & 7) * PSRC + (p & 1) * 16384 + t16, tb = p == 2 ? L ^ 1 : p < 2;
#pragma unroll
            for (int i = 4; i < 8; i++)
              st16(sb, ob, OFF_P + i * 2048, (pack_bf16(acc[8 * i], acc[8 * i + 1]) & ~1u) | tb, pack_bf16(acc[8 * i + 2], acc[8 * i + 3]),
                   pack_bf16(acc[8 * i + 4], acc[8 * i + 5]), pack_bf16(acc[8 * i + 6], acc[8 * i + 7]));
          }
          hint_post(hint);
          TS(68 + L * 32 + p * 5);
          if (p == 1) {
            float s0 = 0.f, s1 = 0.f, s2 = 0.f, s3 = 0.f;
#pragma unroll
            for (int s = 0; s < 8; s++) {
              uint32_t u, v;
              lds64(u, v, xs + 8192 + s * 1024 + t16 / 2);
              s0 += bf_lo(u); s1 += bf_hi(u); s2 += bf_lo(v); s3 += bf_hi(v);
            }
            sts64(ytail(wg * 2) + t16 / 2, pack_bf16(s0, s1), pack_bf16(s2, s3));
          }
          if (p < 3) bar_arrive(NB_FREE + wg, 160);
          TS(67 + L * 32 + p * 5);
        }
        float acc[32];
        add_piece<true>(acc, xs + t16);
        add_piece<false>(acc, xs + 8192 + t16);
        bar_arrive(NB_FREE + wg, 160);
        load_own(xr, sb, L * 3 * TILE, j);
        bar_sync(NB_ORD0 + wg, 256);
        TS(84 + L * 32);
        uint32_t t, yn[2];
        mma_pass<64, PS_FFA, 4, 2048, 0, false, false>(acc, a, DESC_SW128, 0, rel, wg ? -1 : NB_ORD1, nullptr, 0, 0, 0, 0, 0, [&]() {
          t = tid_();
          lds64(yn[0], yn[1], ytail(wg * 2) + t * 8);
          mbar_wait(bar_full(12) + wg * 8, 1);
#pragma unroll
          for (int i = 0; i < 8; i++) lds128(&a[4 * i], xs + i * 2048 + t * 16);
        });
        TS(11 + L * 20);
        while (true) {
          uint32_t m = 0;
#pragma unroll
          for (int i = 0; i < 8; i++) m |= a[4 * i];
          if (!__any_sync(0xffffffffu, m & 1)) break;
#pragma unroll
          for (int i = 0; i < 8; i++) ld16(&a[4 * i], sb, j * PSRC + t * 16, OFF_P + 16384 + i * 2048);
        }
        TS(12 + L * 20);
#pragma unroll
        for (int i = 0; i < 18; i++)
          xr[i] = bf2_add(xr[i], i < 16 ? pack_bf16(acc[2 * i] + (bf_lo(a[i]) + bf_lo(a[16 + i])), acc[2 * i + 1] + (bf_hi(a[i]) + bf_hi(a[16 + i]))) : yn[i - 16]);
        TS(18 + L * 20);
        if (L == 0) {
          store_own(xr, sb, OFF_X2, j, t);
          RowStats rs;
          rs.add<18>(xr);
          rs.store(sb, 8192 + j * 128, t);
          hint_post(hint);
        } else {
          __syncwarp();
#pragma unroll
          for (int i = 0; i < 4; i++) stsm4(xs + i * 2048 + t * 16, xr[4 * i], xr[4 * i + 1], xr[4 * i + 2], xr[4 * i + 3]);
          stsm4(xs + 8192 + t * 16, xr[16], xr[17], 0, 0);
          __syncwarp();
          uint8_t* op = (uint8_t*)P.out + row_off(rb, wg, t);
#pragma unroll
          for (int i = 0; i < 5; i++) {
            uint32_t r[4];
            lds128(r, xs + i * 2048 + t * 16);
            if (i < 4) *(uint4*)(op + i * 32 + j * 128 + (t & 16)) = make_uint4(r[0], r[1], r[2], r[3]);
            else if (!(t & 16)) *(uint4*)(op + 1024 + j * 16) = make_uint4(r[0], r[1], r[2], r[3]);
          }
        }
      }
      TS(13 + L * 20);
    }
    bar_sync(NB_WG + wg, 128);
    if (tid_() == 0) mbar_arrive(bar_empty(12));
  }
}

typedef CUresult (*EncodeFn)(CUtensorMap*, CUtensorMapDataType, cuuint32_t, void*, const cuuint64_t*, const cuuint64_t*, const cuuint32_t*,
                             const cuuint32_t*, CUtensorMapInterleave, CUtensorMapSwizzle, CUtensorMapL2promotion, CUtensorMapFloatOOBfill);

void encode(EncodeFn fn, CUtensorMap* m, const void* p, int rank, const cuuint64_t* dims, const cuuint64_t* str, const cuuint32_t* box) {
  const cuuint32_t es[3] = {1, 1, 1};
  fn(m, CU_TENSOR_MAP_DATA_TYPE_BFLOAT16, rank, const_cast<void*>(p), dims, str, box, es, CU_TENSOR_MAP_INTERLEAVE_NONE,
     CU_TENSOR_MAP_SWIZZLE_128B, CU_TENSOR_MAP_L2_PROMOTION_L2_256B, CU_TENSOR_MAP_FLOAT_OOB_FILL_NONE);
}

}

extern "C" void kernel_launch(void* const* d_in, const int* in_sizes, int n_in, void* d_out, int out_size) {
  (void)in_sizes; (void)n_in; (void)out_size;
  Params P;
  P.x = (const __nv_bfloat16*)d_in[0]; P.wqkv = (const __nv_bfloat16*)d_in[1]; P.wo = (const __nv_bfloat16*)d_in[2];
  P.wg = (const __nv_bfloat16*)d_in[4]; P.wu = (const __nv_bfloat16*)d_in[5]; P.wd = (const __nv_bfloat16*)d_in[6];
  P.out = (__nv_bfloat16*)d_out; P.zero = 0;
  cudaGetSymbolAddress((void**)&P.scr, g_scr);
  void* fnp = nullptr; cudaDriverEntryPointQueryResult qr;
  cudaGetDriverEntryPoint("cuTensorMapEncodeTiled", &fnp, cudaEnableDefault, &qr);
  EncodeFn fn = (EncodeFn)fnp;
  CUtensorMap mx, mg, mu, md;
  { const cuuint64_t dims[3] = {DM, SEQ / 2, 2}, str[2] = {DM * 4, DM * 2}; const cuuint32_t box[3] = {64, 64, 2}; encode(fn, &mx, P.x, 3, dims, str, box); }
  { const cuuint64_t dims[2] = {DFF, DM}, str[1] = {DFF * 2}; const cuuint32_t box[2] = {64, 64}; encode(fn, &mg, P.wg, 2, dims, str, box); encode(fn, &mu, P.wu, 2, dims, str, box); }
  { const cuuint64_t dims[2] = {DM, DFF}, str[1] = {DM * 2}; const cuuint32_t box[2] = {64, 64}; encode(fn, &md, P.wd, 2, dims, str, box); }
  cudaFuncSetAttribute(fused_kernel, cudaFuncAttributeMaxDynamicSharedMemorySize, SMEM_BYTES);
  fused_kernel<<<128, 384, SMEM_BYTES, cudaStreamPerThread>>>(mx, mg, mu, md, P);
}
```

```cpp
#include <cuda_runtime.h>
#include <cuda_bf16.h>
#include <cuda.h>
#include <stdint.h>

#define KV_LEAD 5
#define D_KV 6
#define D_WO 3
#define D_T0 5
#define PF_AHEAD 3
#define CH_LAST 3
#define MC 1
#define MAP 5
#define N_WO 12
#define TH 0
#define THD 0
#define DBG_PS 2
#define SMALLPOS 1
#define Q_SPLIT 2
#define N_UP 26
#define TIMING 0

namespace {

constexpr int SEQ = 2048, DM = 576, DFF = 4608;
constexpr uint32_t SB = 1024;
constexpr uint32_t SLOT = 16384;
constexpr uint32_t PSLOT = 13824;
constexpr uint32_t BARS = SB + 14 * SLOT;
constexpr int SMEM_BYTES = 14 * SLOT + 256 + 2560;
__host__ __device__ constexpr uint32_t slot_addr(int s) { return SB + s * SLOT; }
__host__ __device__ constexpr uint32_t bar_full(int s) { return BARS + 8 * s; }
__host__ __device__ constexpr uint32_t bar_empty(int s) { return BARS + 128 + 8 * s; }
enum { NB_ORD0 = 1, NB_ORD1 = 2, NB_WG = 3  , NB_HALO = 5  , NB_FREE = 7  , NB_PUB = 9  , NB_ORD2 = 13 };
constexpr uint32_t SM_EPOCH = BARS + 120;
__host__ __device__ constexpr uint32_t ytail(uint32_t k) { return k < 3 ? slot_addr(9) + PSLOT + k * SLOT : BARS + 256; }
constexpr uint32_t KSTG = 9 * 1152;

constexpr uint32_t TILE = 36 * 2048;
constexpr uint32_t OFF_X1 = 0  , OFF_O = TILE, OFF_X2 = 2 * TILE, OFF_ST = 4 * TILE  ;
constexpr uint32_t PSRC = 2 * 16384 + 7 * 1024;
constexpr uint32_t OFF_P = OFF_ST + 3 * 4096, OFF_HALO = OFF_P + 8 * PSRC  , OFF_HINT = OFF_HALO + 2 * 8 * 3072  ,
                   STRM = OFF_HINT + 12 * 128;
constexpr uint32_t OFF_WPACK = 32 * STRM, OFF_FLAGS = OFF_WPACK + 8 * 24 * PSLOT;
__device__ __align__(1024) uint8_t g_scr[OFF_FLAGS + (8 + 64 + 128) * 32];

__device__ __forceinline__ uint32_t smem_u32(const void* p) { return (uint32_t)__cvta_generic_to_shared(p); }
extern __shared__ __align__(1024) uint8_t smem_raw[];
__device__ __forceinline__ uint32_t win() { return MC ? (blockIdx.x & 1) << 24 : 0; }
#define SA(A, W) ".reg .u32 sa;\nadd.u32 sa, " A ", " W ";\n"
__device__ __forceinline__ void mbar_init(uint32_t bar, uint32_t cnt) { asm volatile("{\n" SA("%0", "%2") "mbarrier.init.shared::cta.b64 [sa], %1;\n}" ::"r"(bar), "r"(cnt), "r"(win())); }
__device__ __forceinline__ void mbar_expect_tx(uint32_t bar, uint32_t bytes) { asm volatile("{\n" SA("%0", "%2") "mbarrier.arrive.expect_tx.shared::cta.b64 _, [sa], %1;\n}" ::"r"(bar), "r"(bytes), "r"(win()) : "memory"); }
__device__ __forceinline__ void mbar_arrive(uint32_t bar) { asm volatile("{\n" SA("%0", "%1") "mbarrier.arrive.shared::cta.b64 _, [sa];\n}" ::"r"(bar), "r"(win()) : "memory"); }
__device__ __forceinline__ uint32_t lds32(uint32_t a) { uint32_t v; asm volatile("{\n" SA("%1", "%2") "ld.shared.u32 %0, [sa];\n}" : "=r"(v) : "r"(a), "r"(win()) : "memory"); return v; }
__device__ __forceinline__ void lds64(uint32_t& x, uint32_t& y, uint32_t a) { asm volatile("{\n" SA("%2", "%3") "ld.shared.v2.u32 {%0,%1}, [sa];\n}" : "=r"(x), "=r"(y) : "r"(a), "r"(win()) : "memory"); }
__device__ __forceinline__ void lds128(uint32_t* v, uint32_t a) {
  asm volatile("{\n" SA("%4", "%5") "ld.shared.v4.u32 {%0,%1,%2,%3}, [sa];\n}" : "=r"(v[0]), "=r"(v[1]), "=r"(v[2]), "=r"(v[3]) : "r"(a), "r"(win()) : "memory");
}
__device__ __forceinline__ void stsm4(uint32_t a, uint32_t x, uint32_t y, uint32_t z, uint32_t w) {
  asm volatile("{\n" SA("%0", "%5") "stmatrix.sync.aligned.m8n8.x4.shared.b16 [sa], {%1,%2,%3,%4};\n}" ::"r"(a), "r"(x), "r"(y), "r"(z), "r"(w), "r"(win()) : "memory");
}
__device__ __forceinline__ void ldsm4(uint32_t* v, uint32_t a) {
  asm volatile("{\n" SA("%4", "%5") "ldmatrix.sync.aligned.m8n8.x4.shared.b16 {%0,%1,%2,%3}, [sa];\n}" : "=r"(v[0]), "=r"(v[1]), "=r"(v[2]), "=r"(v[3]) : "r"(a), "r"(win()) : "memory");
}
__device__ __forceinline__ void ldsm4t(uint32_t* v, uint32_t a) {
  asm volatile("{\n" SA("%4", "%5") "ldmatrix.sync.aligned.m8n8.x4.trans.shared.b16 {%0,%1,%2,%3}, [sa];\n}" : "=r"(v[0]), "=r"(v[1]), "=r"(v[2]), "=r"(v[3]) : "r"(a), "r"(win()) : "memory");
}
__device__ __forceinline__ void sts32(uint32_t a, uint32_t x) { asm volatile("{\n" SA("%0", "%2") "st.shared.u32 [sa], %1;\n}" ::"r"(a), "r"(x), "r"(win()) : "memory"); }
__device__ __forceinline__ void sts64(uint32_t a, uint32_t x, uint32_t y) { asm volatile("{\n" SA("%0", "%3") "st.shared.v2.u32 [sa], {%1,%2};\n}" ::"r"(a), "r"(x), "r"(y), "r"(win()) : "memory"); }
__device__ __forceinline__ void sts128(uint32_t a, uint32_t x, uint32_t y, uint32_t z, uint32_t w) {
  asm volatile("{\n" SA("%0", "%5") "st.shared.v4.u32 [sa], {%1,%2,%3,%4};\n}" ::"r"(a), "r"(x), "r"(y), "r"(z), "r"(w), "r"(win()) : "memory");
}
__device__ __forceinline__ void mbar_wait(uint32_t bar, uint32_t parity) {
  asm volatile("{\n.reg .pred p;\n" SA("%0", "%2") "LAB_WAIT:\nmbarrier.try_wait.parity.shared::cta.b64 p, [sa], %1;\n@!p bra LAB_WAIT;\n}" ::"r"(bar), "r"(parity), "r"(win()) : "memory");
}
__device__ __forceinline__ void timed_wait(uint32_t bar, uint32_t par) {
  asm volatile("{\n.reg .pred p;\n.reg .u64 t0, t1;\nmov.u64 t0, %%globaltimer;\nLAB_WD:\n"
               "mbarrier.try_wait.parity.shared::cta.b64 p, [%0], %1, 100000;\n@p bra LAB_OK;\n"
               "mov.u64 t1, %%globaltimer;\nsub.u64 t1, t1, t0;\nsetp.lt.u64 p, t1, 2000000000;\n@p bra LAB_WD;\ntrap;\nLAB_OK:\n}" ::"r"(bar + win()), "r"(par) : "memory");
}
__device__ __forceinline__ void flag_wait(const unsigned* flag, unsigned target) {
  asm volatile("{\n.reg .pred p;\n.reg .u32 v;\nLAB_WAIT:\nld.acquire.gpu.global.u32 v, [%0];\nsub.u32 v, v, %1;\n"
               "setp.lt.s32 p, v, 0;\n@p nanosleep.u32 100;\n@p bra LAB_WAIT;\n}" ::"l"(flag), "r"(target) : "memory");
}
__device__ __forceinline__ void hint_post(uint8_t* p) {
  __syncwarp();
  asm volatile("{\n.reg .pred p;\nelect.sync _|p, 0xffffffff;\n@p red.relaxed.gpu.global.add.u32 [%0], 1;\n}" ::"l"(p) : "memory");
}
__device__ __forceinline__ void hint_wait(const uint8_t* p, uint32_t target) {
  asm volatile("{\n.reg .pred p;\n.reg .u32 v;\nLAB_WAIT:\nld.relaxed.gpu.global.u32 v, [%0];\nsub.u32 v, v, %1;\n"
               "setp.lt.s32 p, v, 0;\nvote.sync.any.pred p, p, 0xffffffff;\n@p bra LAB_WAIT;\n}" ::"l"(p), "r"(target) : "memory");
}
__device__ __forceinline__ void flag_signal(unsigned* flag) { asm volatile("red.release.gpu.global.add.u32 [%0], 1;" ::"l"(flag) : "memory"); }
struct Rel {
  bool on; uint32_t base;
  __device__ __forceinline__ void operator()(int s) const {
    if (on) {
      if (MC) asm volatile("{\n" SA("%0", "%1") "mbarrier.arrive.shared::cluster.b64 _, [sa];\n}" ::"r"(bar_empty(s)), "r"(base) : "memory");
      else mbar_arrive(bar_empty(s));
    }
  }
};
__device__ __forceinline__ uint32_t cta_window(uint32_t rank) { uint32_t a; asm("mapa.shared::cluster.u32 %0, %1, %2;" : "=r"(a) : "r"(0), "r"(rank)); return a; }
__device__ __forceinline__ void tma_2d_mc(uint32_t dst, const CUtensorMap* m, int c0, int c1, uint32_t bar) {
  asm volatile("cp.async.bulk.tensor.2d.shared::cluster.global.mbarrier::complete_tx::bytes.multicast::cluster [%0], [%1, {%3, %4}], [%2], %5;"
               ::"r"(dst), "l"(m), "r"(bar), "r"(c0), "r"(c1), "h"((uint16_t)3) : "memory");
}
__device__ __forceinline__ void bulk_load_mc(uint32_t dst, const void* src, uint32_t bytes, uint32_t bar) {
  asm volatile("cp.async.bulk.shared::cluster.global.mbarrier::complete_tx::bytes.multicast::cluster [%0], [%1], %2, [%3], %4;"
               ::"r"(dst), "l"(src), "r"(bytes), "r"(bar), "h"((uint16_t)3) : "memory");
}
__device__ __forceinline__ void tma_2d(uint32_t dst, const CUtensorMap* m, int c0, int c1, uint32_t bar) {
  asm volatile("cp.async.bulk.tensor.2d.shared::cluster.global.mbarrier::complete_tx::bytes [%0], [%1, {%3, %4}], [%2];"
               ::"r"(dst), "l"(m), "r"(bar), "r"(c0), "r"(c1) : "memory");
}
__device__ __forceinline__ void tma_3d(uint32_t dst, const CUtensorMap* m, int c0, int c1, int c2, uint32_t bar) {
  asm volatile("cp.async.bulk.tensor.3d.shared::cluster.global.mbarrier::complete_tx::bytes [%0], [%1, {%3, %4, %5}], [%2];"
               ::"r"(dst), "l"(m), "r"(bar), "r"(c0), "r"(c1), "r"(c2) : "memory");
}
__device__ __forceinline__ void bulk_load(uint32_t dst, const void* src, uint32_t bytes, uint32_t bar) {
  asm volatile("cp.async.bulk.shared::cluster.global.mbarrier::complete_tx::bytes [%0], [%1], %2, [%3];" ::"r"(dst), "l"(src), "r"(bytes), "r"(bar) : "memory");
}
__device__ __forceinline__ void l2_prefetch(const void* src, uint32_t bytes) { asm volatile("cp.async.bulk.prefetch.L2.global [%0], %1;" ::"l"(src), "r"(bytes) : "memory"); }
__device__ __forceinline__ void wg_fence() { asm volatile("wgmma.fence.sync.aligned;" ::: "memory"); }
__device__ __forceinline__ void wg_commit() { asm volatile("wgmma.commit_group.sync.aligned;" ::: "memory"); }
template <int N> __device__ __forceinline__ void wg_wait() { asm volatile("wgmma.wait_group.sync.aligned %0;" ::"n"(N) : "memory"); }
__device__ __forceinline__ void bar_sync(int id, int n) { asm volatile("bar.sync %0, %1;" ::"r"(id), "r"(n) : "memory"); }
__device__ __forceinline__ void bar_arrive(int id, int n) { asm volatile("bar.arrive %0, %1;" ::"r"(id), "r"(n) : "memory"); }
__device__ __forceinline__ uint32_t pack_bf16(float lo, float hi) { uint32_t r; asm("cvt.rn.bf16x2.f32 %0, %1, %2;" : "=r"(r) : "f"(hi), "f"(lo)); return r; }
__device__ __forceinline__ float bf_lo(uint32_t w) { return __uint_as_float(w << 16); }
__device__ __forceinline__ float bf_hi(uint32_t w) { return __uint_as_float(w & 0xffff0000u); }
__device__ __forceinline__ float bf_round(float x) { return bf_lo(pack_bf16(x, 0.f)); }
__device__ __forceinline__ uint32_t bf2_sub(uint32_t a, uint32_t b) { uint32_t r; asm("sub.rn.bf16x2 %0, %1, %2;" : "=r"(r) : "r"(a), "r"(b)); return r; }
__device__ __forceinline__ uint32_t bf2_add(uint32_t a, uint32_t b) { uint32_t r; asm("add.rn.bf16x2 %0, %1, %2;" : "=r"(r) : "r"(a), "r"(b)); return r; }
#define GADDR(B, O, I) "cvt.u64.u32 ad, " O ";\nadd.u64 ad, ad, " B ";\nadd.u64 ad, ad, " I ";\n"
__device__ __forceinline__ void ld16(uint32_t* v, const uint8_t* ub, uint32_t off, uint32_t imm) {
  asm volatile("{\n.reg .b128 z;\n.reg .b64 x, y, ad;\n" GADDR("%4", "%5", "%6") "ld.relaxed.gpu.global.b128 z, [ad];\n"
               "mov.b128 {x, y}, z;\nmov.b64 {%0,%1}, x;\nmov.b64 {%2,%3}, y;\n}"
               : "=r"(v[0]), "=r"(v[1]), "=r"(v[2]), "=r"(v[3]) : "l"(ub), "r"(off), "l"((uint64_t)imm) : "memory");
}
__device__ __forceinline__ void ld8(uint32_t* v, const uint8_t* ub, uint32_t off, uint32_t imm) {
  asm volatile("{\n.reg .b64 x, ad;\n" GADDR("%2", "%3", "%4") "ld.relaxed.gpu.global.b64 x, [ad];\nmov.b64 {%0,%1}, x;\n}"
               : "=r"(v[0]), "=r"(v[1]) : "l"(ub), "r"(off), "l"((uint64_t)imm) : "memory");
}
__device__ __forceinline__ void st16(uint8_t* ub, uint32_t off, uint32_t imm, uint32_t a, uint32_t b, uint32_t c, uint32_t d) {
  asm volatile("{\n.reg .b128 z;\n.reg .b64 x, y, ad;\n" GADDR("%0", "%1", "%2") "mov.b64 x, {%3,%4};\nmov.b64 y, {%5,%6};\nmov.b128 z, {x, y};\n"
               "st.relaxed.gpu.global.b128 [ad], z;\n}" ::"l"(ub), "r"(off), "l"((uint64_t)imm), "r"(a), "r"(b), "r"(c), "r"(d) : "memory");
}
__device__ __forceinline__ void st8(uint8_t* ub, uint32_t off, uint32_t imm, uint32_t a, uint32_t b) {
  asm volatile("{\n.reg .b64 x, ad;\n" GADDR("%0", "%1", "%2") "mov.b64 x, {%3,%4};\nst.relaxed.gpu.global.b64 [ad], x;\n}"
               ::"l"(ub), "r"(off), "l"((uint64_t)imm), "r"(a), "r"(b) : "memory");
}
__device__ __forceinline__ void send8(uint8_t* ub, uint32_t off, uint32_t imm, uint32_t sm, int i, int j, uint32_t a, uint32_t b) {
  asm volatile("{\n.reg .pred p, q, e;\n.reg .b64 x, ad;\n" SA("%3", "%8") GADDR("%0", "%1", "%2")
               "setp.lt.s32 p, %4, %5;\nsetp.gt.s32 q, %4, %5;\nsetp.eq.s32 e, %4, %5;\nmov.b64 x, {%6,%7};\n"
               "@p st.relaxed.gpu.global.b64 [ad+-1024], x;\n@q st.relaxed.gpu.global.b64 [ad], x;\n@e st.shared.v2.u32 [sa], {%6,%7};\n}"
               ::"l"(ub), "r"(off), "l"((uint64_t)imm), "r"(sm), "r"(i), "r"(j), "r"(a), "r"(b), "r"(win()) : "memory");
}
__device__ __forceinline__ uint4 ldg_line(const void* p) {
  uint4 v; asm volatile("ld.global.nc.L2::128B.v4.u32 {%0,%1,%2,%3}, [%4];" : "=r"(v.x), "=r"(v.y), "=r"(v.z), "=r"(v.w) : "l"(p)); return v;
}
__device__ __forceinline__ void stg4(void* ub, uint32_t off, uint32_t imm, uint32_t v) {
  asm volatile("{\n.reg .b64 ad;\n" GADDR("%0", "%1", "%2") "st.global.u32 [ad], %3;\n}" ::"l"(ub), "r"(off), "l"((uint64_t)imm), "r"(v) : "memory");
}
__device__ __forceinline__ uint32_t tid_() { uint32_t t; asm volatile("mov.u32 %0, %%tid.x;" : "=r"(t)); return t & 127; }
__device__ __forceinline__ uint32_t nz(uint32_t w) { return max(w, 1u); }
__device__ __forceinline__ void mma16816(float (&c)[4], uint32_t a0, uint32_t a1, uint32_t a2, uint32_t a3, uint32_t b0, uint32_t b1) {
  asm("mma.sync.aligned.m16n8k16.row.col.f32.bf16.bf16.f32 {%0,%1,%2,%3}, {%4,%5,%6,%7}, {%8,%9}, {%0,%1,%2,%3};"
               : "+f"(c[0]), "+f"(c[1]), "+f"(c[2]), "+f"(c[3]) : "r"(a0), "r"(a1), "r"(a2), "r"(a3), "r"(b0), "r"(b1));
}
__device__ __forceinline__ void mma1688(float (&c)[4], uint32_t a0, uint32_t a1, uint32_t b0) {
  asm("mma.sync.aligned.m16n8k8.row.col.f32.bf16.bf16.f32 {%0,%1,%2,%3}, {%4,%5}, {%6}, {%0,%1,%2,%3};"
               : "+f"(c[0]), "+f"(c[1]), "+f"(c[2]), "+f"(c[3]) : "r"(a0), "r"(a1), "r"(b0));
}
__device__ __forceinline__ float ex2(float x) { float r; asm("ex2.approx.ftz.f32 %0, %1;" : "=f"(r) : "f"(x)); return r; }
__device__ __forceinline__ float quad_sum(float v) { v += __shfl_xor_sync(0xffffffffu, v, 1); v += __shfl_xor_sync(0xffffffffu, v, 2); return v; }
__device__ __forceinline__ float quad_max(float v) { v = fmaxf(v, __shfl_xor_sync(0xffffffffu, v, 1)); v = fmaxf(v, __shfl_xor_sync(0xffffffffu, v, 2)); return v; }

__device__ __forceinline__ void wgmma_rs_n64(float (&d)[32], uint32_t a0, uint32_t a1, uint32_t a2, uint32_t a3, uint64_t desc, int scale_d) {
  asm volatile("{\n.reg .pred p;\nsetp.ne.b32 p, %37, 0;\n"
    "wgmma.mma_async.sync.aligned.m64n64k16.f32.bf16.bf16 "
    "{%0, %1, %2, %3, %4, %5, %6, %7, %8, %9, %10, %11, %12, %13, %14, %15, %16, %17, %18, %19, %20, %21, %22, %23, %24, %25, %26, %27, %28, %29, %30, %31}, "
    "{%32, %33, %34, %35}, %36, p, 1, 1, 1;\n}\n"
    : "+f"(d[0]), "+f"(d[1]), "+f"(d[2]), "+f"(d[3]), "+f"(d[4]), "+f"(d[5]), "+f"(d[6]), "+f"(d[7]), "+f"(d[8]), "+f"(d[9]), "+f"(d[10]), "+f"(d[11]), "+f"(d[12]), "+f"(d[13]), "+f"(d[14]), "+f"(d[15]), "+f"(d[16]), "+f"(d[17]), "+f"(d[18]), "+f"(d[19]), "+f"(d[20]), "+f"(d[21]), "+f"(d[22]), "+f"(d[23]), "+f"(d[24]), "+f"(d[25]), "+f"(d[26]), "+f"(d[27]), "+f"(d[28]), "+f"(d[29]), "+f"(d[30]), "+f"(d[31])
    : "r"(a0), "r"(a1), "r"(a2), "r"(a3), "l"(desc), "r"(scale_d));
}

__device__ __forceinline__ void wgmma_rs_n72(float (&d)[36], uint32_t a0, uint32_t a1, uint32_t a2, uint32_t a3, uint64_t desc, int scale_d) {
  asm volatile("{\n.reg .pred p;\nsetp.ne.b32 p, %41, 0;\n"
    "wgmma.mma_async.sync.aligned.m64n72k16.f32.bf16.bf16 "
    "{%0, %1, %2, %3, %4, %5, %6, %7, %8, %9, %10, %11, %12, %13, %14, %15, %16, %17, %18, %19, %20, %21, %22, %23, %24, %25, %26, %27, %28, %29, %30, %31, %32, %33, %34, %35}, "
    "{%36, %37, %38, %39}, %40, p, 1, 1, 1;\n}\n"
    : "+f"(d[0]), "+f"(d[1]), "+f"(d[2]), "+f"(d[3]), "+f"(d[4]), "+f"(d[5]), "+f"(d[6]), "+f"(d[7]), "+f"(d[8]), "+f"(d[9]), "+f"(d[10]), "+f"(d[11]), "+f"(d[12]), "+f"(d[13]), "+f"(d[14]), "+f"(d[15]), "+f"(d[16]), "+f"(d[17]), "+f"(d[18]), "+f"(d[19]), "+f"(d[20]), "+f"(d[21]), "+f"(d[22]), "+f"(d[23]), "+f"(d[24]), "+f"(d[25]), "+f"(d[26]), "+f"(d[27]), "+f"(d[28]), "+f"(d[29]), "+f"(d[30]), "+f"(d[31]), "+f"(d[32]), "+f"(d[33]), "+f"(d[34]), "+f"(d[35])
    : "r"(a0), "r"(a1), "r"(a2), "r"(a3), "l"(desc), "r"(scale_d));
}

__device__ __forceinline__ void wgmma_rs_n128(float (&d)[64], uint32_t a0, uint32_t a1, uint32_t a2, uint32_t a3, uint64_t desc, int scale_d) {
  asm volatile("{\n.reg .pred p;\nsetp.ne.b32 p, %69, 0;\n"
    "wgmma.mma_async.sync.aligned.m64n128k16.f32.bf16.bf16 "
    "{%0, %1, %2, %3, %4, %5, %6, %7, %8, %9, %10, %11, %12, %13, %14, %15, %16, %17, %18, %19, %20, %21, %22, %23, %24, %25, %26, %27, %28, %29, %30, %31, %32, %33, %34, %35, %36, %37, %38, %39, %40, %41, %42, %43, %44, %45, %46, %47, %48, %49, %50, %51, %52, %53, %54, %55, %56, %57, %58, %59, %60, %61, %62, %63}, "
    "{%64, %65, %66, %67}, %68, p, 1, 1, 1;\n}\n"
    : "+f"(d[0]), "+f"(d[1]), "+f"(d[2]), "+f"(d[3]), "+f"(d[4]), "+f"(d[5]), "+f"(d[6]), "+f"(d[7]), "+f"(d[8]), "+f"(d[9]), "+f"(d[10]), "+f"(d[11]), "+f"(d[12]), "+f"(d[13]), "+f"(d[14]), "+f"(d[15]), "+f"(d[16]), "+f"(d[17]), "+f"(d[18]), "+f"(d[19]), "+f"(d[20]), "+f"(d[21]), "+f"(d[22]), "+f"(d[23]), "+f"(d[24]), "+f"(d[25]), "+f"(d[26]), "+f"(d[27]), "+f"(d[28]), "+f"(d[29]), "+f"(d[30]), "+f"(d[31]), "+f"(d[32]), "+f"(d[33]), "+f"(d[34]), "+f"(d[35]), "+f"(d[36]), "+f"(d[37]), "+f"(d[38]), "+f"(d[39]), "+f"(d[40]), "+f"(d[41]), "+f"(d[42]), "+f"(d[43]), "+f"(d[44]), "+f"(d[45]), "+f"(d[46]), "+f"(d[47]), "+f"(d[48]), "+f"(d[49]), "+f"(d[50]), "+f"(d[51]), "+f"(d[52]), "+f"(d[53]), "+f"(d[54]), "+f"(d[55]), "+f"(d[56]), "+f"(d[57]), "+f"(d[58]), "+f"(d[59]), "+f"(d[60]), "+f"(d[61]), "+f"(d[62]), "+f"(d[63])
    : "r"(a0), "r"(a1), "r"(a2), "r"(a3), "l"(desc), "r"(scale_d));
}

__device__ __forceinline__ void wgmma_rs_n144(float (&d)[72], uint32_t a0, uint32_t a1, uint32_t a2, uint32_t a3, uint64_t desc, int scale_d) {
  asm volatile("{\n.reg .pred p;\nsetp.ne.b32 p, %77, 0;\n"
    "wgmma.mma_async.sync.aligned.m64n144k16.f32.bf16.bf16 "
    "{%0, %1, %2, %3, %4, %5, %6, %7, %8, %9, %10, %11, %12, %13, %14, %15, %16, %17, %18, %19, %20, %21, %22, %23, %24, %25, %26, %27, %28, %29, %30, %31, %32, %33, %34, %35, %36, %37, %38, %39, %40, %41, %42, %43, %44, %45, %46, %47, %48, %49, %50, %51, %52, %53, %54, %55, %56, %57, %58, %59, %60, %61, %62, %63, %64, %65, %66, %67, %68, %69, %70, %71}, "
    "{%72, %73, %74, %75}, %76, p, 1, 1, 1;\n}\n"
    : "+f"(d[0]), "+f"(d[1]), "+f"(d[2]), "+f"(d[3]), "+f"(d[4]), "+f"(d[5]), "+f"(d[6]), "+f"(d[7]), "+f"(d[8]), "+f"(d[9]), "+f"(d[10]), "+f"(d[11]), "+f"(d[12]), "+f"(d[13]), "+f"(d[14]), "+f"(d[15]), "+f"(d[16]), "+f"(d[17]), "+f"(d[18]), "+f"(d[19]), "+f"(d[20]), "+f"(d[21]), "+f"(d[22]), "+f"(d[23]), "+f"(d[24]), "+f"(d[25]), "+f"(d[26]), "+f"(d[27]), "+f"(d[28]), "+f"(d[29]), "+f"(d[30]), "+f"(d[31]), "+f"(d[32]), "+f"(d[33]), "+f"(d[34]), "+f"(d[35]), "+f"(d[36]), "+f"(d[37]), "+f"(d[38]), "+f"(d[39]), "+f"(d[40]), "+f"(d[41]), "+f"(d[42]), "+f"(d[43]), "+f"(d[44]), "+f"(d[45]), "+f"(d[46]), "+f"(d[47]), "+f"(d[48]), "+f"(d[49]), "+f"(d[50]), "+f"(d[51]), "+f"(d[52]), "+f"(d[53]), "+f"(d[54]), "+f"(d[55]), "+f"(d[56]), "+f"(d[57]), "+f"(d[58]), "+f"(d[59]), "+f"(d[60]), "+f"(d[61]), "+f"(d[62]), "+f"(d[63]), "+f"(d[64]), "+f"(d[65]), "+f"(d[66]), "+f"(d[67]), "+f"(d[68]), "+f"(d[69]), "+f"(d[70]), "+f"(d[71])
    : "r"(a0), "r"(a1), "r"(a2), "r"(a3), "l"(desc), "r"(scale_d));
}

template <int N> struct WG;
template <> struct WG<64>  { static __device__ __forceinline__ void f(float (&d)[32], const uint32_t* a, uint64_t ds, int s) { wgmma_rs_n64(d, a[0], a[1], a[2], a[3], ds, s); } };
template <> struct WG<72>  { static __device__ __forceinline__ void f(float (&d)[36], const uint32_t* a, uint64_t ds, int s) { wgmma_rs_n72(d, a[0], a[1], a[2], a[3], ds, s); } };
template <> struct WG<128> { static __device__ __forceinline__ void f(float (&d)[64], const uint32_t* a, uint64_t ds, int s) { wgmma_rs_n128(d, a[0], a[1], a[2], a[3], ds, s); } };
template <> struct WG<144> { static __device__ __forceinline__ void f(float (&d)[72], const uint32_t* a, uint64_t ds, int s) { wgmma_rs_n144(d, a[0], a[1], a[2], a[3], ds, s); } };

constexpr uint64_t DESC_SW128 = ((uint64_t)(8192 >> 4) << 16) | ((uint64_t)(1024 >> 4) << 32) | (1ull << 62);
constexpr uint64_t DESC_KV = ((uint64_t)(128 >> 4) << 16) | ((uint64_t)(768 >> 4) << 32);
constexpr uint64_t DESC_Q = ((uint64_t)(128 >> 4) << 16) | ((uint64_t)(1536 >> 4) << 32);

template <int V> struct IntC { static constexpr int value = V; };
enum { PS_KV, PS_Q, PS_WO, PS_FF, PS_FFA   };
template <int PS> __host__ __device__ constexpr int pass_slot(int i) {
  return PS == PS_KV ? (i < 3 ? 9 + i : i - 3) : PS == PS_WO ? 6 + i : i;
}

__device__ __forceinline__ void load_frag(uint32_t (&a)[144], int i, const uint8_t* sb, uint32_t uo, uint32_t t) {
  if (i < 32) ld16(&a[4 * i], sb, uo + t * 16, i * 2048);
  else { ld8(&a[4 * i], sb, uo + t * 8, i * 2048); ld8(&a[4 * i + 2], sb, uo + t * 8, i * 2048 + 1024); }
}
__device__ __forceinline__ void store_own(const uint32_t (&y)[18], uint8_t* sb, uint32_t uo, int j, uint32_t t) {
#pragma unroll
  for (int i = 0; i < 4; i++) st16(sb, uo + j * 8192 + t * 16, i * 2048, nz(y[4 * i]), y[4 * i + 1], y[4 * i + 2], y[4 * i + 3]);
  st8(sb, uo + j * 1024 + t * 8, 65536, nz(y[16]), y[17]);
}
__device__ __forceinline__ void load_own(uint32_t* y, const uint8_t* sb, uint32_t uo, int j) {
  const uint32_t t = tid_();
#pragma unroll
  for (int i = 0; i < 4; i++) ld16(&y[4 * i], sb, uo + j * 8192 + t * 16, i * 2048);
  ld8(&y[16], sb, uo + j * 1024 + t * 8, 65536);
}

struct NoTail { __device__ __forceinline__ void operator()() const {} };
template <int N, int PS, int KPS, int KSTEP, int CHK, bool SUB, bool HREL = false, class Tail = NoTail>
__device__ __forceinline__ void mma_pass(float (&acc)[N / 2], uint32_t (&a)[144], uint64_t desc, uint32_t par, const Rel& rel, int bar_id,
                                         const uint8_t* sb = nullptr, uint32_t uo = 0, uint32_t flag = 0, uint32_t m0 = 0, uint32_t m1 = 0, uint32_t park = 0, Tail tail = Tail()) {
  constexpr int NS = 36 / KPS;
  auto check = [&](int lo, int hi, uint32_t m0_) {
    while (true) {
      uint32_t m = m0_;
#pragma unroll
      for (int i = hi - 1; i >= lo; i--) m = min(m, i < 32 ? a[4 * i] : min(a[4 * i], a[4 * i + 2]));
      if (!__any_sync(0xffffffffu, (m | flag) == 0)) break;
      const uint32_t t = tid_();
#pragma unroll
      for (int i = lo; i < hi; i++) load_frag(a, i, sb, uo, t);
    }
  };
#pragma unroll
  for (int s = 0; s < NS; s++) {
    const int sl = pass_slot<PS>(s);
    if (CHK && s == 0 && !SUB) check(0, CHK * KPS, ~0u);
    if (CHK && s == CHK) check(CHK * KPS, 36, lds32(SM_EPOCH) | 1);
    if (SUB) {
#pragma unroll
      for (int i = s * KPS * 4; i < (s + 1) * KPS * 4; i += 2) { a[i] = bf2_sub(a[i], m0); a[i + 1] = bf2_sub(a[i + 1], m1); }
    }
    if (PS == PS_Q && s == Q_SPLIT && flag) bar_sync(NB_ORD2, 256);
    if (PS == PS_KV && s == 0) sts128(park + tid_() * 16, a[0], a[1], a[2], a[3]);
    mbar_wait(bar_full(sl), sl < 9 ? par : par ^ 1);
    wg_fence();
#pragma unroll
    for (int kk = 0; kk < KPS; kk++)
      WG<N>::f(acc, &a[(s * KPS + kk) * 4], desc + ((slot_addr(sl) + kk * KSTEP) >> 4), (s | kk) || PS == PS_FFA);
    wg_commit();
    if (CHK && s < 2 && N_UP < 36 && !flag) {
      const uint32_t t = tid_();
#pragma unroll
      for (int i = s ? (N_UP + 36) / 2 : N_UP; i < (s ? 36 : (N_UP + 36) / 2); i++) load_frag(a, i, sb, uo, t);
    }
    if (s == (PS == PS_KV ? KV_LEAD : NS - 1) && bar_id >= 0) bar_arrive(bar_id, 256);
    if (s > 0) {
      wg_wait<1>();
      if (!(PS == PS_WO && s > 3)) rel(pass_slot<PS>(s - 1));
    }
    if (HREL && s == 3 && flag) {
#pragma unroll
      for (int i = 0; i < 12; i++) ld16(&a[4 * i], sb, uo, (i >> 2) * TILE + (i & 3) * 2048);
    }
  }
  tail();
  wg_wait<0>();
  if (PS != PS_WO) rel(pass_slot<PS>(NS - 1));
}

template <int NF, int N0 = 0> __device__ __forceinline__ void load_frags(uint32_t (&a)[144], const uint8_t* sb, uint32_t uo, uint32_t t) {
#pragma unroll
  for (int i = N0; i < NF; i++) load_frag(a, i, sb, uo, t);
}
__device__ __forceinline__ void ln_scalars(float s1, float s2, uint32_t& m, float& var, uint32_t zero) {
  const float mean = s1 * (1.f / DM);
  var = s2 * (1.f / DM) - mean * mean;
  m = pack_bf16(mean, mean) ^ (__float_as_uint(var) & zero);
}
__device__ __forceinline__ float ln_rstd(float var, float after, uint32_t zero) {
  var = __uint_as_float(__float_as_uint(var) ^ (__float_as_uint(after) & zero));
  float sd, r;
  asm("sqrt.approx.ftz.f32 %0, %1;" : "=f"(sd) : "f"(bf_round(bf_round(fmaxf(var, 0.f)) + 1e-5f)));
  asm("rcp.approx.ftz.f32 %0, %1;" : "=f"(r) : "f"(bf_round(sd)));
  return r;
}
template <int NF> __device__ __forceinline__ void gather_ln(uint32_t (&a)[144], const uint8_t* sb, uint32_t uo, uint32_t sto,
                                          uint32_t& m0, uint32_t& m1, float& r0, float& r1, uint32_t zero) {
  uint32_t u[32];
  const uint32_t t = tid_(), so = sto + (t >> 5) * 1024 + (t & 28) * 4;
#pragma unroll
  for (int i = 0; i < 8; i++) ld16(&u[4 * i], sb, so, OFF_ST + i * 128);
  load_frags<N_UP>(a, sb, uo, t);
  while (true) {
    uint32_t m = a[4 * NF - 4];
#pragma unroll
    for (int i = NF - 2; i >= 0; i--) m = min(m, a[4 * i]);
#pragma unroll
    for (int i = 0; i < 8; i++) m = min(m, u[4 * i]);
    if (!__any_sync(0xffffffffu, m == 0)) break;
#pragma unroll
    for (int i = 0; i < 8; i++) ld16(&u[4 * i], sb, so, OFF_ST + i * 128);
    load_frags<NF>(a, sb, uo, t);
  }
  float v[4];
#pragma unroll
  for (int k = 0; k < 4; k++)
    v[k] = ((__uint_as_float(u[k]) + __uint_as_float(u[4 + k])) + (__uint_as_float(u[8 + k]) + __uint_as_float(u[12 + k]))) +
           ((__uint_as_float(u[16 + k]) + __uint_as_float(u[20 + k])) + (__uint_as_float(u[24 + k]) + __uint_as_float(u[28 + k])));
  ln_scalars(v[1], v[0], m0, r0, zero); ln_scalars(v[3], v[2], m1, r1, zero);
}
struct Stats {
  float s[4] = {0, 0, 0, 0}, d0[4] = {0, 0, 0, 0}, d1[4] = {0, 0, 0, 0};
  __device__ __forceinline__ void add16(const uint32_t* f) {
    mma16816(s, f[0], f[1], f[2], f[3], 0x3f803f80u, 0x3f803f80u);
    mma1688(d0, f[0], f[1], f[0]); mma1688(d1, f[0], f[1], f[1]);
    mma1688(d0, f[2], f[3], f[2]); mma1688(d1, f[2], f[3], f[3]);
  }
  __device__ __forceinline__ float sq0(int g) const { return (g & 1) ? d0[1] : d0[0]; }
  __device__ __forceinline__ float sq1(int g) const { return (g & 1) ? d1[3] : d1[2]; }
};
struct RowStats {
  float s[4] = {0, 0, 0, 0}, u[4] = {0, 0, 0, 0};
  template <int N> __device__ __forceinline__ void add(const uint32_t* y) {
#pragma unroll
    for (int i = 0; i < N; i++) {
      const float lo = bf_lo(y[i]), hi = bf_hi(y[i]);
      const int r = (i & 1) * 2;
      s[r] = fmaf(lo, lo, s[r]); u[r] = fmaf(hi, hi, u[r]); s[r + 1] += lo; u[r + 1] += hi;
    }
  }
  __device__ __forceinline__ uint32_t fold() {
    uint32_t x = 0;
#pragma unroll
    for (int i = 0; i < 4; i++) { s[i] += u[i]; u[i] = 0; x |= __float_as_uint(s[i]); }
    return x;
  }
  __device__ __forceinline__ void store(uint8_t* sb, uint32_t sto, uint32_t t) {
    fold();
#pragma unroll
    for (int i = 0; i < 4; i++) s[i] += __shfl_xor_sync(0xffffffffu, s[i], 1);
#pragma unroll
    for (int i = 0; i < 4; i++) s[i] += __shfl_xor_sync(0xffffffffu, s[i], 2);
    if ((t & 3) == 0) st16(sb, sto + (t >> 5) * 1024 + (t & 28) * 4, OFF_ST, __float_as_uint(s[0]) | 1u, __float_as_uint(s[1]), __float_as_uint(s[2]), __float_as_uint(s[3]));
  }
};
template <bool SET> __device__ __forceinline__ void add_piece(float* acc, uint32_t sm) {
#pragma unroll
  for (int i = 0; i < 4; i++) {
    uint32_t v[4];
    lds128(v, sm + i * 2048);
#pragma unroll
    for (int k = 0; k < 4; k++) {
      acc[8 * i + 2 * k] = SET ? bf_lo(v[k]) : acc[8 * i + 2 * k] + bf_lo(v[k]);
      acc[8 * i + 2 * k + 1] = SET ? bf_hi(v[k]) : acc[8 * i + 2 * k + 1] + bf_hi(v[k]);
    }
  }
}

#define TS(i) do {} while (0)
#define TSP(i) do {} while (0)
#define TSH(i) do {} while (0)

__host__ __device__ constexpr int cl_grp(int c) { return c < 4 ? 8 + SMALLPOS : c < 36 ? (c - 4) & 7 : 8 + (c - 36) % 7 + ((c - 36) % 7 >= SMALLPOS); }
__host__ __device__ constexpr int cl_mem(int c) { return c < 4 ? c : c < 36 ? (c - 4) >> 3 : (c - 36) / 7; }
__host__ __device__ constexpr int role_j(int c) {
  return MAP == 0 ? (MC ? (c >> 1) & 7 : c & 7) : MAP == 1 ? c >> 4 : MAP == 2 ? ((c >> 6) << 2) | ((c >> 1) & 3)
       : MAP == 3 ? ((c >> 5) << 1) | ((c >> 2) & 1) : MAP == 4 ? ((c >> 3) & 3) * 2 + ((c >> 2) & 1)
       : MAP == 5 ? (cl_grp(c >> 1) >> 3) * 4 + cl_mem(c >> 1) : MAP == 6 ? (cl_grp(c >> 1) >> 2) * 2 + (cl_mem(c >> 1) & 1)
       : ((cl_grp(c >> 1) >> 1) & 3) * 2 + (cl_mem(c >> 1) & 1);
}
__host__ __device__ constexpr int role_rb(int c) {
  return MAP == 0 ? (MC ? (c >> 4) * 2 + (c & 1) : c >> 3) : MAP == 1 ? c & 15 : MAP == 2 ? ((c >> 3) & 7) * 2 + (c & 1)
       : MAP == 3 ? ((c >> 3) & 3) * 4 + (c & 3) : MAP == 4 ? (c >> 5) * 4 + (c & 3)
       : MAP == 5 ? (cl_grp(c >> 1) & 7) * 2 + (c & 1) : MAP == 6 ? (cl_grp(c >> 1) & 3) * 4 + (cl_mem(c >> 1) >> 1) * 2 + (c & 1)
       : ((cl_grp(c >> 1) >> 3) * 2 + (cl_grp(c >> 1) & 1)) * 4 + (cl_mem(c >> 1) >> 1) * 2 + (c & 1);
}

__device__ __forceinline__ uint32_t row_off(int rb, int wg, uint32_t t) { return (rb * 128 + wg + ((t >> 5) * 16 + (t & 15)) * 2) * (2 * DM); }

__device__ __forceinline__ const __nv_bfloat16* wo_src(const __nv_bfloat16* wo, int k, int u, int j) {
  const int ko = k < 512 ? (k >> 6) * 72 + (k & 63) : ((k >> 3) & 7) * 72 + 64 + (k & 7);
  return wo + ko * 576 + (u < 8 ? j * 64 + u * 8 : 512 + j * 8);
}

struct Params {
  const __nv_bfloat16 *x, *wqkv, *wo, *wg, *wu, *wd;
  __nv_bfloat16* out;
  uint8_t* scr;
  uint8_t* times;
  unsigned zero;
};

__device__ __forceinline__ void tma_prefetch(const CUtensorMap* m, int c0, int c1) {
  asm volatile("cp.async.bulk.prefetch.tensor.2d.L2.global [%0, {%1, %2}];" ::"l"(m), "r"(c0), "r"(c1) : "memory");
}
__device__ __forceinline__ void fill_packed(int sl, uint32_t par, const uint8_t* src, uint32_t rank, uint32_t own) {
  mbar_wait(bar_empty(sl), par);
  mbar_expect_tx(bar_full(sl), PSLOT);
  if (MC) bulk_load_mc(own + slot_addr(sl) + rank * (PSLOT / 2), src + rank * (PSLOT / 2), PSLOT / 2, own + bar_full(sl));
  else bulk_load(slot_addr(sl), src, PSLOT, bar_full(sl));
}

__cluster_dims__(2, 1, 1)
__global__ void __launch_bounds__(384, 1)
fused_kernel(const __grid_constant__ CUtensorMap map_x, const __grid_constant__ CUtensorMap map_wg,
             const __grid_constant__ CUtensorMap map_wu, const __grid_constant__ CUtensorMap map_wd, const Params P) {
  const int wg = __shfl_sync(0xffffffffu, threadIdx.x >> 7, 0);
  const int cta = blockIdx.x, rank = MC ? cta & 1 : 0, j = role_j(cta), rb = role_rb(cta);
  const uint32_t own = win();
  unsigned* const flags = (unsigned*)(P.scr + OFF_FLAGS);
  if (__shfl_sync(0xffffffffu, threadIdx.x >> 5, 0) == 11) {
    if (threadIdx.x == 352) {
#pragma unroll
      for (int i = 0; i < 14; i++) { mbar_init(bar_full(i), 1); mbar_init(bar_empty(i), MC && i < 12 ? 4 : 2); }
      mbar_init(bar_full(14), 1); mbar_init(bar_empty(14), 1);
      asm volatile("fence.mbarrier_init.release.cluster;" ::: "memory");
      if (smem_u32(smem_raw) != own + SB) asm volatile("trap;");
    }
    __syncwarp();
    bar_arrive(0, 384);
    if (MC) asm volatile("barrier.cluster.arrive.relaxed.aligned;" ::: "memory");
    if (threadIdx.x == 352) {
#pragma unroll 1
      for (int c = 0; c < 9; c++) {
        mbar_expect_tx(bar_full(c), SLOT);
        tma_3d(own + slot_addr(c), &map_x, c * 64, rb * 64, 0, own + bar_full(c));
      }
    }
  } else {
    const bool on = threadIdx.x < 324;
    const int k = rb * 36 + (on ? threadIdx.x / 36 : 0) * 4 + (threadIdx.x & 3), u = (threadIdx.x % 36) >> 2;
    const uint4* s = (const uint4*)(P.wqkv + k * 1728 + j * 72 + u * 8);
    const uint4 vk = ldg_line(s + 72), vv = ldg_line(s + 144);
    const unsigned ep0 = *(volatile unsigned*)&flags[(72 + cta) * 8];
    if (MC) asm volatile("barrier.cluster.arrive.relaxed.aligned;" ::: "memory");
    bar_sync(0, 384);
    uint8_t* d = P.scr + OFF_WPACK + j * 24 * PSLOT;
    if (on) {
      const uint32_t dkv = (k / 48) * PSLOT + u * 768 + (k % 48) * 16;
      st16(d, dkv, 0, vk.x, vk.y, vk.z, vk.w);
      st16(d, dkv, 9 * 768, vv.x, vv.y, vv.z, vv.w);
    }
    asm volatile("fence.proxy.async.global;" ::: "memory");
    bar_arrive(NB_PUB + 3, 384);
    if (threadIdx.x == 351) sts32(SM_EPOCH, ep0);
    if (wg == 2) bar_sync(NB_PUB + 1, 96);
  }
  __syncwarp();
  if (MC) asm volatile("barrier.cluster.wait.acquire.aligned;" ::: "memory");

  if (wg == 2) {
    asm volatile("setmaxnreg.dec.sync.aligned.u32 24;");
    const int pw = __shfl_sync(0xffffffffu, (threadIdx.x >> 5) & 3, 0), lane = threadIdx.x & 31;
    auto tile_col = [](int t, int h, int j) { return t < 9 ? j * 576 + t * 64 : (t == 9 && h) ? 512 : ((j + ((h ? 0x05760 : 0x04123) >> (4 * (t - 9)))) & 7) * 64; };
    auto prefetch_tile = [&](int t) {
#pragma unroll 1
      for (int b = rb; b < 18; b += 16) {
        const int h = b & 1, k = b >> 1;
        if (t < 9) tma_prefetch(h ? &map_wu : &map_wg, tile_col(t, h, j), k * 64);
        else if (t != 13 || !h) tma_prefetch(&map_wd, tile_col(t, h, j), j * 576 + k * 64);
      }
    };
    if (pw == 0) {
      if (lane == 0) {
        flag_wait(&flags[j * 8], (lds32(SM_EPOCH) + 1) * 16);
        TSP(7);
        asm volatile("fence.proxy.async.global;" ::: "memory");
        const uint8_t* wp = P.scr + OFF_WPACK + j * 24 * PSLOT;
#pragma unroll 1
        for (int s = 0; s < 3; s++) fill_packed(9 + s, 1, wp + s * PSLOT, rank, own);
#pragma unroll 1
        for (int L = 0; L < 2; L++) {
#pragma unroll 1
          for (int s = 0; s < 21; s++) {
            if (s == 9 && L == 0) { flag_wait(&flags[(56 + j) * 8], (lds32(SM_EPOCH) + 1) * 16); asm volatile("fence.proxy.async.global;" ::: "memory"); }
            fill_packed(s < 9 ? s : s - 9, s >= 9 && s < 18, wp + (s + 3) * PSLOT, rank, own);
          }
#pragma unroll 1
          for (int t = 0; t < 14; t++) {
            const int p = t - 9;
            const CUtensorMap* ma = p < 0 ? &map_wg : &map_wd;
            const CUtensorMap* mb = p < 0 ? &map_wu : &map_wd;
            const int ca = tile_col(t, 0, j), cb = tile_col(t, 1, j), r0 = p < 0 ? 0 : j * 576;
            if (L * 14 + t + PF_AHEAD < 28) prefetch_tile((t + PF_AHEAD) % 14);
#pragma unroll 1
            for (int k = 0; k < 9; k++) {
              if (TH && t == 0 && k >= TH && k < 6) { mbar_wait(bar_full(k - TH), 1); for (int i = 0; i < THD; i++) __nanosleep(0); }
              mbar_wait(bar_empty(k), t & 1);
              mbar_expect_tx(bar_full(k), p == 4 ? 8192 : SLOT);
              const int r = r0 + (p < 0 || k == 8 ? k : k < 3 ? k + 5 : k - 3) * 64;
              if (MC) {
                if (p != 4) tma_2d_mc(own + slot_addr(k) + rank * 8192, rank ? mb : ma, rank ? cb : ca, r, own + bar_full(k));
                else if ((k & 1) == rank) tma_2d_mc(own + slot_addr(k), ma, ca, r, own + bar_full(k));
              } else {
                tma_2d(slot_addr(k), ma, ca, r, bar_full(k));
                if (p != 4) tma_2d(slot_addr(k) + 8192, mb, cb, r, bar_full(k));
              }
            }
            if (p == 1 && L == 0) {
              l2_prefetch(wp + rb * (24 * PSLOT / 16), 24 * PSLOT / 16);
#pragma unroll 1
              for (int s = 0; s < 3; s++) fill_packed(9 + s, 1, wp + s * PSLOT, rank, own);
            }
          }
        }
        flags[(72 + cta) * 8] = lds32(SM_EPOCH) + 1;
      }
    } else if (pw < 3) {
      const int hw = pw - 1;
      const uint32_t ep = __shfl_sync(0xffffffffu, lds32(SM_EPOCH), 0);
      uint8_t* const sb = P.scr + (rb * 2 + hw) * STRM;
      const uint32_t xs = slot_addr(12) + hw * SLOT, fb = bar_full(12) + hw * 8;
      uint32_t hph = 0;
#pragma unroll 1
      for (int L = 0; L < 2; L++) {
        const uint32_t tag = ep * 2 + L + 1;
        bar_sync(NB_FREE + hw, 160);
        if (rb > 0) hint_wait(sb + OFF_HINT + 512 + j * 128, tag);
        uint32_t bad;
        do {
          if (rb > 0) {
            if (lane == 0) {
              mbar_expect_tx(bar_full(14) + hw * 128, 3072);
              bulk_load(own + ytail(hw * 2), sb + OFF_HALO + (L * 8 + j) * 3072, 1536, own + bar_full(14) + hw * 128);
              bulk_load(own + ytail(hw * 2 + 1), sb + OFF_HALO + (L * 8 + j) * 3072 + 1536, 1536, own + bar_full(14) + hw * 128);
            }
            mbar_wait(bar_full(14) + hw * 128, hph);
            hph ^= 1;
          }
          bad = 0;
#pragma unroll 1
          for (int c = 0; c < 3; c++) {
            uint32_t u[4] = {tag, 0, 0, 0}, v[4] = {tag, 0, 0, 0};
            if (rb > 0) { lds128(u, ytail(hw * 2) + c * 512 + lane * 16); lds128(v, ytail(hw * 2 + 1) + c * 512 + lane * 16); }
            bad |= (u[0] ^ tag) | (v[0] ^ tag);
#pragma unroll
            for (int i = 0; i < 3; i++) { sts32(xs + KSTG + (c * 3 + i) * 128 + lane * 4, u[i + 1]); sts32(xs + (c * 3 + i) * 128 + lane * 4, v[i + 1]); }
          }
        } while (__any_sync(0xffffffffu, bad != 0));
        bar_arrive(NB_HALO + hw, 160);
#pragma unroll 1
        for (int p = 0; p < 4; p++) {
          if (L == 0 && p == 3) flag_wait(flags + (40 + rb) * 8, (ep + 1) * 8);
          bar_sync(NB_FREE + hw, 160);
          TSH(L * 12 + p * 3);
          hint_wait(sb + OFF_HINT + (lane & 3) * 128, (ep * 13 + L * 7 + p + 3) * 8);
          TSH(L * 12 + p * 3 + 1);
          if (lane == 0) {
            mbar_expect_tx(fb, p ? 16384 : 15360);
            bulk_load(own + xs, sb + OFF_P + j * PSRC + (p & 1) * 16384, p ? 16384 : 8192, own + fb);
            if (p == 0) bulk_load(own + xs + 8192, sb + OFF_P + j * PSRC + 32768, 7168, own + fb);
          }
          TSH(L * 12 + p * 3 + 2);
        }
      }
    } else {
      auto clear = [&](int t) {
        const uint32_t so = rb * 2 * STRM + (threadIdx.x & 31) * 16;
#pragma unroll 1
        for (int i = 0; i < 18; i++) {
          st16(P.scr, so + t * TILE + j * 9216 + i * 512, 0, 0, 0, 0, 0);
          st16(P.scr, so + t * TILE + j * 9216 + i * 512, STRM, 0, 0, 0, 0);
          __nanosleep(0);
        }
        if (t != 1) {
          st16(P.scr, so + (t ? t - 1 : 0) * 4096 + j * 512, OFF_ST, 0, 0, 0, 0);
          st16(P.scr, so + (t ? t - 1 : 0) * 4096 + j * 512, OFF_ST + STRM, 0, 0, 0, 0);
        }
      };
      bar_sync(NB_PUB + 3, 384);
      if (lane == 0) flag_signal(&flags[j * 8]);
      TSP(5);
      bar_sync(NB_PUB + 2, 288);
      if (lane == 0) flag_signal(&flags[(56 + j) * 8]);
      TSP(4);
      if (lane == 0) {
#pragma unroll 1
        for (int t = 0; t < PF_AHEAD; t++) prefetch_tile(t);
      }
      __syncwarp();
#pragma unroll 1
      for (int L = 0; L < 2; L++) {
        timed_wait(bar_empty(13), L);
#pragma unroll 1
        for (int t = L ^ 1; t < 4 - 2 * L; t++) clear(t);
        __syncwarp();
        if (lane == 0 && L == 0) flag_signal(flags + (40 + rb) * 8);
      }
      timed_wait(bar_empty(12), 0);
      if (MC) asm volatile("barrier.cluster.arrive.relaxed.aligned;\nbarrier.cluster.wait.aligned;" ::: "memory");
    }
  } else {
    asm volatile("setmaxnreg.inc.sync.aligned.u32 240;");
    const int w = __shfl_sync(0xffffffffu, (threadIdx.x >> 5) & 3, 0);
    const bool leader = (threadIdx.x & 127) == 0;
    const Rel rel{MC ? (threadIdx.x & 95) == 0 : leader, MC ? cta_window(w & 1) : 0};
    uint8_t* const sb = P.scr + (rb * 2 + wg) * STRM;
    uint8_t* const hint = sb + OFF_HINT + w * 128;
    auto hint_target = [](int e) { return (lds32(SM_EPOCH) * 13 + e + 1) * 8; };
    TS(0);
    uint32_t a[144];
#pragma unroll 1
    for (int L = 0; L < 2; L++) {
      uint32_t m0, m1; float r0, r1;
      if (L == 0) {
        Stats st;
        const int lane = tid_() & 31, g = lane >> 2;
        const int row = w * 16 + (lane & 15);
        const uint32_t ra = SB + wg * 8192 + row * 128;
        const uint32_t pt = tid_(), pu = (pt % 36) >> 2, pk = rb * 36 + (pt < 108 ? pt / 36 : 0) * 4 + (pt & 3);
        uint4 pv[3];
#pragma unroll
        for (int i = 0; i < 3; i++) pv[i] = ldg_line(wg ? wo_src(P.wo, pk + i * 12, pu, j) : P.wqkv + (pk + i * 12) * 1728 + j * 72 + pu * 8);
#pragma unroll
        for (int c = 0; c < 9; c++) {
          mbar_wait(bar_full(c), 0);
          if (c == 0) TS(60); if (c == 8) TS(62);
#pragma unroll
          for (int kk = 0; kk < 4; kk++) ldsm4(&a[c * 16 + kk * 4], ra + (((kk * 2 + (lane >> 4)) ^ (row & 7)) << 4) + c * SLOT);
          if (c == 8) {
            uint32_t y[18], z[4];
#pragma unroll
            for (int i = 0; i < 4; i++) ldsm4(&y[4 * i], ra + (((i * 2 + (lane >> 4)) ^ (row & 7)) << 4) + j * SLOT);
            ldsm4(z, ra + ((j ^ (row & 7)) << 4) + 8 * SLOT);
            y[16] = z[0]; y[17] = z[1];
            bar_sync(NB_WG + wg, 128);
#pragma unroll
            for (int i = 0; i < 9; i++) rel(i);
            if (pt < 108) {
#pragma unroll
              for (int i = 0; i < 3; i++) {
                const uint32_t k = pk + i * 12;
                st16(P.scr, (j * 24 + wg * 6 + k / 96) * PSLOT + pu * 1536 + (k % 96) * 16, OFF_WPACK + 12 * PSLOT, pv[i].x, pv[i].y, pv[i].z, pv[i].w);
              }
            }
            asm volatile("fence.proxy.async.global;" ::: "memory");
            bar_arrive(NB_PUB + 2, 288);
            store_own(y, sb, OFF_X2, j, tid_());
          }
#pragma unroll
          for (int kk = 0; kk < 4; kk++) st.add16(&a[c * 16 + kk * 4]);
        }
        const int dl = (lane & ~3) | (g >> 1);
        ln_scalars(st.s[0], __shfl_sync(0xffffffffu, st.sq0(g), dl), m0, r0, P.zero);
        ln_scalars(st.s[2], __shfl_sync(0xffffffffu, st.sq1(g), dl), m1, r1, P.zero);
      } else {
#pragma unroll
        for (int i = 4 * N_UP; i < 144; i++) a[i] = 0;
        hint_wait(hint, hint_target(6));
        TS(61);
        gather_ln<3 * D_KV>(a, sb, OFF_X2, 8192, m0, m1, r0, r1, P.zero);
      }
      TS(1 + L * 20);
      uint32_t kf[18], qf[18];
      {
        float acc[72];
        if (wg == 1) bar_sync(NB_ORD1, 256);
        mma_pass<144, PS_KV, 3, 256, D_KV, true>(acc, a, DESC_KV, 1, rel, wg == 0 ? NB_ORD1 : -1, sb, OFF_X2, L ^ 1, m0, m1, ytail(wg * 2));
        r0 = ln_rstd(r0, acc[0], P.zero); r1 = ln_rstd(r1, acc[0], P.zero);
        uint32_t vf[18];
#pragma unroll
        for (int c = 0; c < 9; c++) {
          kf[2 * c] = pack_bf16(acc[4 * c] * r0, acc[4 * c + 1] * r0);
          kf[2 * c + 1] = pack_bf16(acc[4 * c + 2] * r1, acc[4 * c + 3] * r1);
          vf[c] = pack_bf16(acc[36 + 4 * c] * r0, acc[36 + 4 * c + 1] * r0);
          vf[9 + c] = pack_bf16(acc[36 + 4 * c + 2] * r1, acc[36 + 4 * c + 3] * r1);
        }
        TS(2 + L * 20);
        const uint32_t l16 = (tid_() & 31) * 16, xs = slot_addr(12) + wg * SLOT + w * 1152;
#pragma unroll
        for (int i = 0; i < 4; i++) stsm4(xs + w * 1152 + 1152 + i * 512 + l16, vf[4 * i], vf[4 * i + 1], vf[4 * i + 2], vf[4 * i + 3]);
        sts32(xs + w * 1152 + 1152 + 2048 + l16 / 4, vf[16]); sts32(xs + w * 1152 + 1152 + 2176 + l16 / 4, vf[17]);
        if (w < 3) {
          stsm4(xs + KSTG + 1152 + l16, kf[1], kf[3], kf[5], kf[7]);
          stsm4(xs + KSTG + 1152 + 512 + l16, kf[9], kf[11], kf[13], kf[15]);
          sts32(xs + KSTG + 1152 + 1024 + l16 / 4, kf[17]);
        } else if (rb < 15) {
          const uint32_t tag = lds32(SM_EPOCH) * 2 + L + 1;
          const uint32_t ho = l16 + (L * 8 + j) * 3072;
#pragma unroll
          for (int c = 0; c < 3; c++) {
            st16(sb, ho, 2 * STRM + OFF_HALO + c * 512, tag, kf[6 * c + 1], kf[6 * c + 3], kf[6 * c + 5]);
            st16(sb, ho, 2 * STRM + OFF_HALO + 1536 + c * 512, tag, vf[9 + 3 * c], vf[10 + 3 * c], vf[11 + 3 * c]);
          }
          hint_post(sb + 2 * STRM + OFF_HINT + 512 + j * 128);
        }
      }
      lds128(a, ytail(wg * 2) + tid_() * 16);
      bar_arrive(NB_FREE + wg, 160);
      uint32_t kh[12];
      {
        float acc[36];
        if (wg == 1) bar_sync(NB_ORD1, 256);
        mma_pass<72, PS_Q, 6, 256, 0, false, false>(acc, a, DESC_Q, 0, rel, -1, nullptr, 0, wg, 0, 0, 0, [&]() {
          bar_sync(NB_HALO + wg, 160);
#pragma unroll
          for (int i = 0; i < 3; i++) ldsm4(&kh[4 * i], slot_addr(12) + wg * SLOT + w * 640 + tid_() * 16 + KSTG + i * 512);
        });
#pragma unroll
        for (int i = 0; i < 18; i++) qf[i] = pack_bf16(acc[2 * i], acc[2 * i + 1]);
      }
      TS(3 + L * 20);
      uint32_t xr[18];
      {
        const int tid = tid_(), g = (tid >> 2) & 7, q = tid & 3;
        uint32_t vt[28];
#pragma unroll
        for (int i = 0; i < 7; i++) ldsm4t(&vt[4 * i], slot_addr(12) + wg * SLOT + w * 1792 + tid * 16 + i * 512);
        const bool nohalo = (rb == 0 && w == 0);
        const bool le0 = 2 * q <= g, le1 = 2 * q + 1 <= g;
        const uint32_t M = (le0 ? 0xffffu : 0u) | (le1 ? 0xffff0000u : 0u);
        const float sc0 = r0 * (0.23570226039551584f * 1.4426950408889634f), sc1 = r1 * (0.23570226039551584f * 1.4426950408889634f);
        float l[16], t[8];
#pragma unroll
        for (int h = 0; h < 4; h++) {
          const uint32_t qa0 = q >= h ? qf[4 * h] : 0u, qa1 = q >= h ? qf[4 * h + 1] : 0u;
          const uint32_t qc0 = q <= h ? qf[4 * h + 4] : 0u, qc1 = q <= h ? qf[4 * h + 5] : 0u;
          float sm[4] = {0, 0, 0, 0}, s0[4] = {0, 0, 0, 0}, s1[4] = {0, 0, 0, 0};
          mma16816(s0, qa0, qa1, qf[4 * h + 2], qf[4 * h + 3], kf[4 * h], kf[4 * h + 2]);
          mma16816(s1, qa0, qa1, qf[4 * h + 2], qf[4 * h + 3], kf[4 * h + 1], kf[4 * h + 3]);
          mma16816(sm, qa0, qa1, qf[4 * h + 2], qf[4 * h + 3], kh[2 * h], kh[2 * h + 1]);
          mma1688(s0, qc0, qc1, kf[4 * h + 4]);
          mma1688(s1, qc0, qc1, kf[4 * h + 5]);
          mma1688(sm, qc0, qc1, kh[2 * h + 2]);
          if (nohalo) sm[0] = sm[1] = -3e38f;
          l[4 * h] = le0 ? s0[0] : sm[0]; l[4 * h + 1] = le1 ? s0[1] : sm[1];
          l[4 * h + 2] = le0 ? s1[2] : s0[2]; l[4 * h + 3] = le1 ? s1[3] : s0[3];
        }
#pragma unroll
        for (int i = 0; i < 8; i++) t[i] = fmaxf(l[2 * i], l[2 * i + 1]);
        if (wg == 0) {
          uint32_t x = 0;
#pragma unroll
          for (int i = 0; i < 8; i++) x |= __float_as_uint(t[i]);
          bar_arrive(NB_ORD1 + (x & P.zero), 256);
        }
        TS(14 + L * 20);
#pragma unroll
        for (int i = 0; i < 8; i++) t[i] = fmaxf(t[i], __shfl_xor_sync(0xffffffffu, t[i], 1));
#pragma unroll
        for (int i = 0; i < 8; i++) t[i] = fmaxf(t[i], __shfl_xor_sync(0xffffffffu, t[i], 2)) * ((i & 1) ? sc1 : sc0);
#pragma unroll
        for (int i = 0; i < 8; i++) {
          const float sc = (i & 1) ? sc1 : sc0;
          l[2 * i] = ex2(fmaf(l[2 * i], sc, -t[i])); l[2 * i + 1] = ex2(fmaf(l[2 * i + 1], sc, -t[i])); t[i] = l[2 * i] + l[2 * i + 1];
        }
#pragma unroll
        for (int i = 0; i < 8; i++) t[i] += __shfl_xor_sync(0xffffffffu, t[i], 1);
#pragma unroll
        for (int i = 0; i < 8; i++) t[i] += __shfl_xor_sync(0xffffffffu, t[i], 2);
        uint32_t pf[16];
#pragma unroll
        for (int i = 0; i < 8; i++) {
          float r; asm("rcp.approx.ftz.f32 %0, %1;" : "=f"(r) : "f"(t[i]));
          const uint32_t p = pack_bf16(l[2 * i] * r, l[2 * i + 1] * r);
          pf[2 * i] = p & ~M; pf[2 * i + 1] = p & M;
        }
#pragma unroll
        for (int c = 0; c < 9; c++) {
          const int h = c == 8 ? 3 : c >> 1;
          float o[4] = {0, 0, 0, 0};
          mma16816(o, pf[4 * h], 0u, pf[4 * h + 1], pf[4 * h + 2], vt[c], vt[9 + c]);
          mma1688(o, 0u, pf[4 * h + 3], vt[18 + c]);
          if (c == 2 || c == 4 || c == 6) {
            float e[4] = {0, 0, 0, 0};
            mma16816(e, pf[4 * h - 4], 0u, pf[4 * h - 3], pf[4 * h - 2], vt[c], vt[9 + c]);
            mma1688(e, 0u, pf[4 * h - 1], vt[18 + c]);
            if (q < h) { o[0] = e[0]; o[1] = e[1]; o[2] = e[2]; o[3] = e[3]; }
          }
          qf[2 * c] = pack_bf16(o[0], o[1]); qf[2 * c + 1] = pack_bf16(o[2], o[3]);
        }
        {
          uint32_t x = 0;
#pragma unroll
          for (int i = 0; i < 18; i += 2) x |= qf[i];
          bar_arrive((wg ? NB_ORD0 : NB_ORD2) + (x & P.zero), 256);
        }
        store_own(qf, sb, OFF_O, j, tid);
        hint_post(hint);
        load_own(xr, sb, OFF_X2, j);
      }
      TS(4 + L * 20);
      {
        hint_wait(hint, hint_target(L * 7));
        TS(5 + L * 20);
        load_frags<N_WO>(a, sb, OFF_O, tid_());
        float acc[36];
        if (wg == 0) bar_sync(NB_ORD0, 256);
        load_frags<N_UP, N_WO>(a, sb, OFF_O, tid_());
        TS(19 + L * 20);
        mma_pass<72, PS_WO, 6, 256, D_WO, false>(acc, a, DESC_Q, 0, rel, -1, sb, OFF_O);
        TS(6 + L * 20);
#pragma unroll
        for (int c = 0; c < 9; c++) {
          xr[2 * c] = bf2_add(xr[2 * c], pack_bf16(acc[4 * c], acc[4 * c + 1]));
          xr[2 * c + 1] = bf2_add(xr[2 * c + 1], pack_bf16(acc[4 * c + 2], acc[4 * c + 3]));
        }
        store_own(xr, sb, L * 3 * TILE, j, tid_());
        RowStats rs;
        rs.add<18>(xr);
        rs.store(sb, L * 4096 + j * 128, tid_());
        hint_post(hint);
      }
      TS(16 + L * 20);
      hint_wait(hint, hint_target(L * 7 + 1));
      TS(15 + L * 20);
      gather_ln<4 * D_T0>(a, sb, L * 3 * TILE, L * 4096, m0, m1, r0, r1, P.zero);
      TS(7 + L * 20);
      const uint32_t hb = (L ^ 1) * TILE + j * 9216;
      {
        float ka0, kb0, kc0, ka1, kb1, kc1;
        float acc[64];
        uint32_t hf[16];
        auto geglu = [&](auto chains, uint32_t hsm) {
          constexpr int CH = decltype(chains)::value & 15;
          float r[32];
#pragma unroll
          for (int e = 0; e < 32; e++) {
            float x = acc[e];
            if (e >= CH) x = __uint_as_float(__float_as_uint(x) ^ (__float_as_uint(r[e - CH]) & P.zero));
            if (decltype(chains)::value > 15 && e < 20) {
              const uint32_t ad = (e < 8 ? slot_addr(12) + e * 2048 + wg * 8192 : slot_addr(7 + (e >> 2)) + (e & 3) * 2048) + hsm;
              lds128(&a[48 + 4 * e], e >= CH ? ad ^ (__float_as_uint(r[e - CH]) & P.zero) : ad);
            }
            const bool hi = e & 2;
            float t = x * fmaf(x * x, hi ? kb1 : kb0, hi ? ka1 : ka0);
            asm("tanh.approx.f32 %0, %0;" : "+f"(t));
            const float u = x * acc[32 + e] * (hi ? kc1 : kc0);
            r[e] = fmaf(u, t, u);
            if (e & 1) hf[e >> 1] = pack_bf16(r[e - 1], r[e]);
          }
        };
        if (wg == 1) bar_sync(NB_ORD1, 256);
        mma_pass<128, PS_FF, 4, 2048, D_T0, true>(acc, a, DESC_SW128, 1, rel, NB_ORD1 - wg, sb, L * 3 * TILE, 0, m0, m1);
        TS(8 + L * 20);
        r0 = ln_rstd(r0, acc[0], P.zero); r1 = ln_rstd(r1, acc[0], P.zero);
        ka0 = 0.7978845608028654f * r0; kb0 = 0.035677408136300125f * r0 * r0 * r0; kc0 = 0.5f * r0 * r0;
        ka1 = 0.7978845608028654f * r1; kb1 = 0.035677408136300125f * r1 * r1 * r1; kc1 = 0.5f * r1 * r1;
#pragma unroll 1
        for (int t = 0; t < 8; t++) {
          geglu(IntC<2>(), 0);
          const uint32_t t16 = tid_() * 16;
          if (t < 5) {
            const uint32_t d = (t < 2 ? slot_addr(12) + wg * SLOT + t * 8192 : slot_addr(7) + t * SLOT + wg * 8192) + t16;
#pragma unroll
            for (int i = 0; i < 4; i++)
              sts128(d + i * 2048, hf[4 * i], hf[4 * i + 1], hf[4 * i + 2], hf[4 * i + 3]);
            if (t == 4) asm volatile("fence.proxy.async.shared::cta;" ::: "memory");
          } else {
#pragma unroll
            for (int i = 0; i < 4; i++) st16(sb, hb + (t - 5) * TILE + t16, i * 2048, hf[4 * i], hf[4 * i + 1], hf[4 * i + 2], hf[4 * i + 3]);
          }
          bar_sync(NB_ORD0 + wg, 256);
          mma_pass<128, PS_FF, 4, 2048, 0, false, true>(acc, a, DESC_SW128, t & 1, rel, NB_ORD1 - wg, sb, hb + t16, t == 7);
        }
        TS(9 + L * 20);
        const uint32_t hsm = wg * 8192 + tid_() * 16;
        geglu(IntC<16 + CH_LAST>(), hsm);
#pragma unroll
        for (int i = 0; i < 16; i++) a[128 + i] = hf[i];
      }
      TS(10 + L * 20);
      {
        const uint32_t xs = slot_addr(12) + wg * SLOT;
        auto verify = [&](int p, uint32_t t16) {
          mbar_wait(bar_full(12) + wg * 8, p & 1);
          TS(71 + L * 32 + p * 5);
          const uint32_t ta = p < 2, tb = (p & 1) ? ta : L ^ 1, nb = p ? 4 : 7, sh = p == 0;
          uint32_t m = 0;
#pragma unroll
          for (int s = 0; s < 4; s++) m |= (lds32(xs + s * 2048 + t16) ^ ta) | (lds32(xs + 8192 + ((s * 2048 + t16) >> sh)) ^ tb);
          if (p == 0) {
#pragma unroll
            for (int s = 4; s < 7; s++) m |= lds32(xs + 8192 + s * 1024 + t16 / 2) ^ tb;
          }
          if (__any_sync(0xffffffffu, m & 1)) {
#pragma unroll 1
            for (int s = 0; s < 4 + nb; s++) {
              const bool nar = sh && s >= 4;
              const uint32_t o = nar ? 4096 + s * 1024 + t16 / 2 : s * 2048 + t16;
              uint32_t v[4] = {0, 0, 0, 0};
              do {
                if (nar) ld8(v, sb, j * PSRC + o, OFF_P + 32768 - 8192);
                else ld16(v, sb, j * PSRC + (p & 1) * 16384 + o, OFF_P);
              } while (__any_sync(0xffffffffu, (v[0] ^ (s < 4 ? ta : tb)) & 1));
              sts64(xs + o, v[0], v[1]);
              if (!nar) sts64(xs + o + 8, v[2], v[3]);
            }
            asm volatile("fence.proxy.async.shared::cta;" ::: "memory");
          }
        };
        uint32_t t16 = (a[142] | a[143]) & P.zero;
#pragma unroll 1
        for (int p = 0; p < 4; p++) {
          float acc[64];
          bar_sync(NB_ORD0 + wg + (p ? 0 : t16), 256);
          TS(64 + L * 32 + p * 5);
          if (p == 0) { rel(9); rel(10); rel(11); }
          mma_pass<128, PS_FF, 4, 2048, 0, false, false>(acc, a, DESC_SW128, p & 1, rel, NB_ORD1 - wg, nullptr, 0, 0, 0, 0, 0, [&]() {
            t16 = tid_() * 16;
            if (p) verify(p - 1, t16);
          });
          TS(65 + L * 32 + p * 5);
          if (p == 1 || p == 2) add_piece<false>(acc, xs + t16);
          const uint32_t oa = ((j + (p < 3 ? 1 : 4)) & 7) * PSRC + (p & 1) * 16384 + t16;
#pragma unroll
          for (int i = 0; i < 4; i++)
            st16(sb, oa, OFF_P + i * 2048, (pack_bf16(acc[8 * i], acc[8 * i + 1]) & ~1u) | (p < 2), pack_bf16(acc[8 * i + 2], acc[8 * i + 3]),
                 pack_bf16(acc[8 * i + 4], acc[8 * i + 5]), pack_bf16(acc[8 * i + 6], acc[8 * i + 7]));
          if (p == 0) {
#pragma unroll
            for (int i = 0; i < 8; i++)
              send8(sb, j * 1024 + t16 / 2, OFF_P + 32768 + i * PSRC, xs + 15360 + t16 / 2, i, j,
                    (pack_bf16(acc[32 + 4 * i], acc[33 + 4 * i]) & ~1u) | (L ^ 1), pack_bf16(acc[34 + 4 * i], acc[35 + 4 * i]));
            if (t16 == 0) mbar_arrive(bar_empty(13));
          } else {
            if (p == 2) add_piece<false>(acc + 32, xs + 8192 + t16);
            const uint32_t ob = ((j + (p < 3 ? 7 : 5)) & 7) * PSRC + (p & 1) * 16384 + t16, tb = p == 2 ? L ^ 1 : p < 2;
#pragma unroll
            for (int i = 4; i < 8; i++)
              st16(sb, ob, OFF_P + i * 2048, (pack_bf16(acc[8 * i], acc[8 * i + 1]) & ~1u) | tb, pack_bf16(acc[8 * i + 2], acc[8 * i + 3]),
                   pack_bf16(acc[8 * i + 4], acc[8 * i + 5]), pack_bf16(acc[8 * i + 6], acc[8 * i + 7]));
          }
          hint_post(hint);
          TS(68 + L * 32 + p * 5);
          if (p == 1) {
            float s0 = 0.f, s1 = 0.f, s2 = 0.f, s3 = 0.f;
#pragma unroll
            for (int s = 0; s < 8; s++) {
              uint32_t u, v;
              lds64(u, v, xs + 8192 + s * 1024 + t16 / 2);
              s0 += bf_lo(u); s1 += bf_hi(u); s2 += bf_lo(v); s3 += bf_hi(v);
            }
            sts64(ytail(wg * 2) + t16 / 2, pack_bf16(s0, s1), pack_bf16(s2, s3));
          }
          if (p < 3) bar_arrive(NB_FREE + wg, 160);
          TS(67 + L * 32 + p * 5);
        }
        float acc[32];
        add_piece<true>(acc, xs + t16);
        add_piece<false>(acc, xs + 8192 + t16);
        bar_arrive(NB_FREE + wg, 160);
        load_own(xr, sb, L * 3 * TILE, j);
        bar_sync(NB_ORD0 + wg, 256);
        TS(84 + L * 32);
        uint32_t t, yn[2];
        mma_pass<64, PS_FFA, 4, 2048, 0, false, false>(acc, a, DESC_SW128, 0, rel, wg ? -1 : NB_ORD1, nullptr, 0, 0, 0, 0, 0, [&]() {
          t = tid_();
          lds64(yn[0], yn[1], ytail(wg * 2) + t * 8);
          mbar_wait(bar_full(12) + wg * 8, 1);
#pragma unroll
          for (int i = 0; i < 8; i++) lds128(&a[4 * i], xs + i * 2048 + t * 16);
        });
        TS(11 + L * 20);
        while (true) {
          uint32_t m = 0;
#pragma unroll
          for (int i = 0; i < 8; i++) m |= a[4 * i];
          if (!__any_sync(0xffffffffu, m & 1)) break;
#pragma unroll
          for (int i = 0; i < 8; i++) ld16(&a[4 * i], sb, j * PSRC + t * 16, OFF_P + 16384 + i * 2048);
        }
        TS(12 + L * 20);
#pragma unroll
        for (int i = 0; i < 18; i++)
          xr[i] = bf2_add(xr[i], i < 16 ? pack_bf16(acc[2 * i] + (bf_lo(a[i]) + bf_lo(a[16 + i])), acc[2 * i + 1] + (bf_hi(a[i]) + bf_hi(a[16 + i]))) : yn[i - 16]);
        TS(18 + L * 20);
        if (L == 0) {
          store_own(xr, sb, OFF_X2, j, t);
          RowStats rs;
          rs.add<18>(xr);
          rs.store(sb, 8192 + j * 128, t);
          hint_post(hint);
        } else {
          __syncwarp();
#pragma unroll
          for (int i = 0; i < 4; i++) stsm4(xs + i * 2048 + t * 16, xr[4 * i], xr[4 * i + 1], xr[4 * i + 2], xr[4 * i + 3]);
          stsm4(xs + 8192 + t * 16, xr[16], xr[17], 0, 0);
          __syncwarp();
          uint8_t* op = (uint8_t*)P.out + row_off(rb, wg, t);
#pragma unroll
          for (int i = 0; i < 5; i++) {
            uint32_t r[4];
            lds128(r, xs + i * 2048 + t * 16);
            if (i < 4) *(uint4*)(op + i * 32 + j * 128 + (t & 16)) = make_uint4(r[0], r[1], r[2], r[3]);
            else if (!(t & 16)) *(uint4*)(op + 1024 + j * 16) = make_uint4(r[0], r[1], r[2], r[3]);
          }
        }
      }
      TS(13 + L * 20);
    }
    bar_sync(NB_WG + wg, 128);
    if (tid_() == 0) mbar_arrive(bar_empty(12));
  }
}

typedef CUresult (*EncodeFn)(CUtensorMap*, CUtensorMapDataType, cuuint32_t, void*, const cuuint64_t*, const cuuint64_t*, const cuuint32_t*,
                             const cuuint32_t*, CUtensorMapInterleave, CUtensorMapSwizzle, CUtensorMapL2promotion, CUtensorMapFloatOOBfill);

void encode(EncodeFn fn, CUtensorMap* m, const void* p, int rank, const cuuint64_t* dims, const cuuint64_t* str, const cuuint32_t* box) {
  const cuuint32_t es[3] = {1, 1, 1};
  fn(m, CU_TENSOR_MAP_DATA_TYPE_BFLOAT16, rank, const_cast<void*>(p), dims, str, box, es, CU_TENSOR_MAP_INTERLEAVE_NONE,
     CU_TENSOR_MAP_SWIZZLE_128B, CU_TENSOR_MAP_L2_PROMOTION_L2_256B, CU_TENSOR_MAP_FLOAT_OOB_FILL_NONE);
}

}

extern "C" void kernel_launch(void* const* d_in, const int* in_sizes, int n_in, void* d_out, int out_size) {
  (void)in_sizes; (void)n_in; (void)out_size;
  Params P;
  P.x = (const __nv_bfloat16*)d_in[0]; P.wqkv = (const __nv_bfloat16*)d_in[1]; P.wo = (const __nv_bfloat16*)d_in[2];
  P.wg = (const __nv_bfloat16*)d_in[4]; P.wu = (const __nv_bfloat16*)d_in[5]; P.wd = (const __nv_bfloat16*)d_in[6];
  P.out = (__nv_bfloat16*)d_out; P.zero = 0;
  cudaGetSymbolAddress((void**)&P.scr, g_scr);
  void* fnp = nullptr; cudaDriverEntryPointQueryResult qr;
  cudaGetDriverEntryPoint("cuTensorMapEncodeTiled", &fnp, cudaEnableDefault, &qr);
  EncodeFn fn = (EncodeFn)fnp;
  CUtensorMap mx, mg, mu, md;
  { const cuuint64_t dims[3] = {DM, SEQ / 2, 2}, str[2] = {DM * 4, DM * 2}; const cuuint32_t box[3] = {64, 64, 2}; encode(fn, &mx, P.x, 3, dims, str, box); }
  { const cuuint64_t dims[2] = {DFF, DM}, str[1] = {DFF * 2}; const cuuint32_t box[2] = {64, 64}; encode(fn, &mg, P.wg, 2, dims, str, box); encode(fn, &mu, P.wu, 2, dims, str, box); }
  { const cuuint64_t dims[2] = {DM, DFF}, str[1] = {DM * 2}; const cuuint32_t box[2] = {64, 64}; encode(fn, &md, P.wd, 2, dims, str, box); }
  cudaFuncSetAttribute(fused_kernel, cudaFuncAttributeMaxDynamicSharedMemorySize, SMEM_BYTES);
  fused_kernel<<<128, 384, SMEM_BYTES, cudaStreamPerThread>>>(mx, mg, mu, md, P);
}
```

```cpp
#include <cuda_runtime.h>
#include <cuda_bf16.h>
#include <cuda.h>
#include <stdint.h>

#define KV_LEAD 5
#define D_KV 6
#define D_WO 3
#define D_T0 5
#define PF_AHEAD 3
#define CH_LAST 3
#define MC 1
#define MAP 5
#define N_WO 12
#define TH 0
#define THD 0
#define DBG_PS 2
#define SMALLPOS 1
#define Q_SPLIT 2
#define N_UP 26
#define CLR_NS 200
#define TIMING 0

namespace {

constexpr int SEQ = 2048, DM = 576, DFF = 4608;
constexpr uint32_t SB = 1024;
constexpr uint32_t SLOT = 16384;
constexpr uint32_t PSLOT = 13824;
constexpr uint32_t BARS = SB + 14 * SLOT;
constexpr int SMEM_BYTES = 14 * SLOT + 256 + 2560;
__host__ __device__ constexpr uint32_t slot_addr(int s) { return SB + s * SLOT; }
__host__ __device__ constexpr uint32_t bar_full(int s) { return BARS + 8 * s; }
__host__ __device__ constexpr uint32_t bar_empty(int s) { return BARS + 128 + 8 * s; }
enum { NB_ORD0 = 1, NB_ORD1 = 2, NB_WG = 3  , NB_HALO = 5  , NB_FREE = 7  , NB_PUB = 9  , NB_ORD2 = 13 };
constexpr uint32_t SM_EPOCH = BARS + 120;
__host__ __device__ constexpr uint32_t ytail(uint32_t k) { return k < 3 ? slot_addr(9) + PSLOT + k * SLOT : BARS + 256; }
constexpr uint32_t KSTG = 9 * 1152;

constexpr uint32_t TILE = 36 * 2048;
constexpr uint32_t OFF_X1 = 0  , OFF_O = TILE, OFF_X2 = 2 * TILE, OFF_ST = 4 * TILE  ;
constexpr uint32_t PSRC = 2 * 16384 + 7 * 1024;
constexpr uint32_t OFF_P = OFF_ST + 3 * 4096, OFF_HALO = OFF_P + 8 * PSRC  , OFF_HINT = OFF_HALO + 2 * 8 * 3072  ,
                   OFF_H = OFF_HINT + 16 * 128  , STRM = OFF_H + 8 * 24576;
constexpr uint32_t OFF_WPACK = 32 * STRM, OFF_FLAGS = OFF_WPACK + 8 * 24 * PSLOT;
__device__ __align__(1024) uint8_t g_scr[OFF_FLAGS + (8 + 64 + 128) * 32];

__device__ __forceinline__ uint32_t smem_u32(const void* p) { return (uint32_t)__cvta_generic_to_shared(p); }
extern __shared__ __align__(1024) uint8_t smem_raw[];
__device__ __forceinline__ uint32_t win() { return MC ? (blockIdx.x & 1) << 24 : 0; }
#define SA(A, W) ".reg .u32 sa;\nadd.u32 sa, " A ", " W ";\n"
__device__ __forceinline__ void mbar_init(uint32_t bar, uint32_t cnt) { asm volatile("{\n" SA("%0", "%2") "mbarrier.init.shared::cta.b64 [sa], %1;\n}" ::"r"(bar), "r"(cnt), "r"(win())); }
__device__ __forceinline__ void mbar_expect_tx(uint32_t bar, uint32_t bytes) { asm volatile("{\n" SA("%0", "%2") "mbarrier.arrive.expect_tx.shared::cta.b64 _, [sa], %1;\n}" ::"r"(bar), "r"(bytes), "r"(win()) : "memory"); }
__device__ __forceinline__ void mbar_arrive(uint32_t bar) { asm volatile("{\n" SA("%0", "%1") "mbarrier.arrive.shared::cta.b64 _, [sa];\n}" ::"r"(bar), "r"(win()) : "memory"); }
__device__ __forceinline__ uint32_t lds32(uint32_t a) { uint32_t v; asm volatile("{\n" SA("%1", "%2") "ld.shared.u32 %0, [sa];\n}" : "=r"(v) : "r"(a), "r"(win()) : "memory"); return v; }
__device__ __forceinline__ void lds64(uint32_t& x, uint32_t& y, uint32_t a) { asm volatile("{\n" SA("%2", "%3") "ld.shared.v2.u32 {%0,%1}, [sa];\n}" : "=r"(x), "=r"(y) : "r"(a), "r"(win()) : "memory"); }
__device__ __forceinline__ void lds128(uint32_t* v, uint32_t a) {
  asm volatile("{\n" SA("%4", "%5") "ld.shared.v4.u32 {%0,%1,%2,%3}, [sa];\n}" : "=r"(v[0]), "=r"(v[1]), "=r"(v[2]), "=r"(v[3]) : "r"(a), "r"(win()) : "memory");
}
__device__ __forceinline__ void stsm4(uint32_t a, uint32_t x, uint32_t y, uint32_t z, uint32_t w) {
  asm volatile("{\n" SA("%0", "%5") "stmatrix.sync.aligned.m8n8.x4.shared.b16 [sa], {%1,%2,%3,%4};\n}" ::"r"(a), "r"(x), "r"(y), "r"(z), "r"(w), "r"(win()) : "memory");
}
__device__ __forceinline__ void ldsm4(uint32_t* v, uint32_t a) {
  asm volatile("{\n" SA("%4", "%5") "ldmatrix.sync.aligned.m8n8.x4.shared.b16 {%0,%1,%2,%3}, [sa];\n}" : "=r"(v[0]), "=r"(v[1]), "=r"(v[2]), "=r"(v[3]) : "r"(a), "r"(win()) : "memory");
}
__device__ __forceinline__ void ldsm4t(uint32_t* v, uint32_t a) {
  asm volatile("{\n" SA("%4", "%5") "ldmatrix.sync.aligned.m8n8.x4.trans.shared.b16 {%0,%1,%2,%3}, [sa];\n}" : "=r"(v[0]), "=r"(v[1]), "=r"(v[2]), "=r"(v[3]) : "r"(a), "r"(win()) : "memory");
}
__device__ __forceinline__ void sts32(uint32_t a, uint32_t x) { asm volatile("{\n" SA("%0", "%2") "st.shared.u32 [sa], %1;\n}" ::"r"(a), "r"(x), "r"(win()) : "memory"); }
__device__ __forceinline__ void sts64(uint32_t a, uint32_t x, uint32_t y) { asm volatile("{\n" SA("%0", "%3") "st.shared.v2.u32 [sa], {%1,%2};\n}" ::"r"(a), "r"(x), "r"(y), "r"(win()) : "memory"); }
__device__ __forceinline__ void sts128(uint32_t a, uint32_t x, uint32_t y, uint32_t z, uint32_t w) {
  asm volatile("{\n" SA("%0", "%5") "st.shared.v4.u32 [sa], {%1,%2,%3,%4};\n}" ::"r"(a), "r"(x), "r"(y), "r"(z), "r"(w), "r"(win()) : "memory");
}
__device__ __forceinline__ void mbar_wait(uint32_t bar, uint32_t parity) {
  asm volatile("{\n.reg .pred p;\n" SA("%0", "%2") "LAB_WAIT:\nmbarrier.try_wait.parity.shared::cta.b64 p, [sa], %1;\n@!p bra LAB_WAIT;\n}" ::"r"(bar), "r"(parity), "r"(win()) : "memory");
}
__device__ __forceinline__ void timed_wait(uint32_t bar, uint32_t par) {
  asm volatile("{\n.reg .pred p;\n.reg .u64 t0, t1;\nmov.u64 t0, %%globaltimer;\nLAB_WD:\n"
               "mbarrier.try_wait.parity.shared::cta.b64 p, [%0], %1, 100000;\n@p bra LAB_OK;\n"
               "mov.u64 t1, %%globaltimer;\nsub.u64 t1, t1, t0;\nsetp.lt.u64 p, t1, 2000000000;\n@p bra LAB_WD;\ntrap;\nLAB_OK:\n}" ::"r"(bar + win()), "r"(par) : "memory");
}
__device__ __forceinline__ void flag_wait(const unsigned* flag, unsigned target) {
  asm volatile("{\n.reg .pred p;\n.reg .u32 v;\nLAB_WAIT:\nld.acquire.gpu.global.u32 v, [%0];\nsub.u32 v, v, %1;\n"
               "setp.lt.s32 p, v, 0;\n@p nanosleep.u32 100;\n@p bra LAB_WAIT;\n}" ::"l"(flag), "r"(target) : "memory");
}
__device__ __forceinline__ void hint_post(uint8_t* p) {
  __syncwarp();
  asm volatile("{\n.reg .pred p;\nelect.sync _|p, 0xffffffff;\n@p red.relaxed.gpu.global.add.u32 [%0], 1;\n}" ::"l"(p) : "memory");
}
__device__ __forceinline__ void hint_wait(const uint8_t* p, uint32_t target) {
  asm volatile("{\n.reg .pred p;\n.reg .u32 v;\nLAB_WAIT:\nld.relaxed.gpu.global.u32 v, [%0];\nsub.u32 v, v, %1;\n"
               "setp.lt.s32 p, v, 0;\nvote.sync.any.pred p, p, 0xffffffff;\n@p bra LAB_WAIT;\n}" ::"l"(p), "r"(target) : "memory");
}
__device__ __forceinline__ void flag_signal(unsigned* flag) { asm volatile("red.release.gpu.global.add.u32 [%0], 1;" ::"l"(flag) : "memory"); }
struct Rel {
  bool on; uint32_t base;
  __device__ __forceinline__ void operator()(int s) const {
    if (on) {
      if (MC) asm volatile("{\n" SA("%0", "%1") "mbarrier.arrive.shared::cluster.b64 _, [sa];\n}" ::"r"(bar_empty(s)), "r"(base) : "memory");
      else mbar_arrive(bar_empty(s));
    }
  }
};
__device__ __forceinline__ uint32_t cta_window(uint32_t rank) { uint32_t a; asm("mapa.shared::cluster.u32 %0, %1, %2;" : "=r"(a) : "r"(0), "r"(rank)); return a; }
__device__ __forceinline__ void tma_2d_mc(uint32_t dst, const CUtensorMap* m, int c0, int c1, uint32_t bar) {
  asm volatile("cp.async.bulk.tensor.2d.shared::cluster.global.mbarrier::complete_tx::bytes.multicast::cluster [%0], [%1, {%3, %4}], [%2], %5;"
               ::"r"(dst), "l"(m), "r"(bar), "r"(c0), "r"(c1), "h"((uint16_t)3) : "memory");
}
__device__ __forceinline__ void bulk_load_mc(uint32_t dst, const void* src, uint32_t bytes, uint32_t bar) {
  asm volatile("cp.async.bulk.shared::cluster.global.mbarrier::complete_tx::bytes.multicast::cluster [%0], [%1], %2, [%3], %4;"
               ::"r"(dst), "l"(src), "r"(bytes), "r"(bar), "h"((uint16_t)3) : "memory");
}
__device__ __forceinline__ void tma_2d(uint32_t dst, const CUtensorMap* m, int c0, int c1, uint32_t bar) {
  asm volatile("cp.async.bulk.tensor.2d.shared::cluster.global.mbarrier::complete_tx::bytes [%0], [%1, {%3, %4}], [%2];"
               ::"r"(dst), "l"(m), "r"(bar), "r"(c0), "r"(c1) : "memory");
}
__device__ __forceinline__ void tma_3d(uint32_t dst, const CUtensorMap* m, int c0, int c1, int c2, uint32_t bar) {
  asm volatile("cp.async.bulk.tensor.3d.shared::cluster.global.mbarrier::complete_tx::bytes [%0], [%1, {%3, %4, %5}], [%2];"
               ::"r"(dst), "l"(m), "r"(bar), "r"(c0), "r"(c1), "r"(c2) : "memory");
}
__device__ __forceinline__ void bulk_load(uint32_t dst, const void* src, uint32_t bytes, uint32_t bar) {
  asm volatile("cp.async.bulk.shared::cluster.global.mbarrier::complete_tx::bytes [%0], [%1], %2, [%3];" ::"r"(dst), "l"(src), "r"(bytes), "r"(bar) : "memory");
}
__device__ __forceinline__ void l2_prefetch(const void* src, uint32_t bytes) { asm volatile("cp.async.bulk.prefetch.L2.global [%0], %1;" ::"l"(src), "r"(bytes) : "memory"); }
__device__ __forceinline__ void wg_fence() { asm volatile("wgmma.fence.sync.aligned;" ::: "memory"); }
__device__ __forceinline__ void wg_commit() { asm volatile("wgmma.commit_group.sync.aligned;" ::: "memory"); }
template <int N> __device__ __forceinline__ void wg_wait() { asm volatile("wgmma.wait_group.sync.aligned %0;" ::"n"(N) : "memory"); }
__device__ __forceinline__ void bar_sync(int id, int n) { asm volatile("bar.sync %0, %1;" ::"r"(id), "r"(n) : "memory"); }
__device__ __forceinline__ void bar_arrive(int id, int n) { asm volatile("bar.arrive %0, %1;" ::"r"(id), "r"(n) : "memory"); }
__device__ __forceinline__ uint32_t pack_bf16(float lo, float hi) { uint32_t r; asm("cvt.rn.bf16x2.f32 %0, %1, %2;" : "=r"(r) : "f"(hi), "f"(lo)); return r; }
__device__ __forceinline__ float bf_lo(uint32_t w) { return __uint_as_float(w << 16); }
__device__ __forceinline__ float bf_hi(uint32_t w) { return __uint_as_float(w & 0xffff0000u); }
__device__ __forceinline__ float bf_round(float x) { return bf_lo(pack_bf16(x, 0.f)); }
__device__ __forceinline__ uint32_t bf2_sub(uint32_t a, uint32_t b) { uint32_t r; asm("sub.rn.bf16x2 %0, %1, %2;" : "=r"(r) : "r"(a), "r"(b)); return r; }
__device__ __forceinline__ uint32_t bf2_add(uint32_t a, uint32_t b) { uint32_t r; asm("add.rn.bf16x2 %0, %1, %2;" : "=r"(r) : "r"(a), "r"(b)); return r; }
#define GADDR(B, O, I) "cvt.u64.u32 ad, " O ";\nadd.u64 ad, ad, " B ";\nadd.u64 ad, ad, " I ";\n"
__device__ __forceinline__ void ld16(uint32_t* v, const uint8_t* ub, uint32_t off, uint32_t imm) {
  asm volatile("{\n.reg .b128 z;\n.reg .b64 x, y, ad;\n" GADDR("%4", "%5", "%6") "ld.relaxed.gpu.global.b128 z, [ad];\n"
               "mov.b128 {x, y}, z;\nmov.b64 {%0,%1}, x;\nmov.b64 {%2,%3}, y;\n}"
               : "=r"(v[0]), "=r"(v[1]), "=r"(v[2]), "=r"(v[3]) : "l"(ub), "r"(off), "l"((uint64_t)imm) : "memory");
}
__device__ __forceinline__ void ld8(uint32_t* v, const uint8_t* ub, uint32_t off, uint32_t imm) {
  asm volatile("{\n.reg .b64 x, ad;\n" GADDR("%2", "%3", "%4") "ld.relaxed.gpu.global.b64 x, [ad];\nmov.b64 {%0,%1}, x;\n}"
               : "=r"(v[0]), "=r"(v[1]) : "l"(ub), "r"(off), "l"((uint64_t)imm) : "memory");
}
__device__ __forceinline__ void st16(uint8_t* ub, uint32_t off, uint32_t imm, uint32_t a, uint32_t b, uint32_t c, uint32_t d) {
  asm volatile("{\n.reg .b128 z;\n.reg .b64 x, y, ad;\n" GADDR("%0", "%1", "%2") "mov.b64 x, {%3,%4};\nmov.b64 y, {%5,%6};\nmov.b128 z, {x, y};\n"
               "st.relaxed.gpu.global.b128 [ad], z;\n}" ::"l"(ub), "r"(off), "l"((uint64_t)imm), "r"(a), "r"(b), "r"(c), "r"(d) : "memory");
}
__device__ __forceinline__ void st8(uint8_t* ub, uint32_t off, uint32_t imm, uint32_t a, uint32_t b) {
  asm volatile("{\n.reg .b64 x, ad;\n" GADDR("%0", "%1", "%2") "mov.b64 x, {%3,%4};\nst.relaxed.gpu.global.b64 [ad], x;\n}"
               ::"l"(ub), "r"(off), "l"((uint64_t)imm), "r"(a), "r"(b) : "memory");
}
__device__ __forceinline__ void send8(uint8_t* ub, uint32_t off, uint32_t imm, uint32_t sm, int i, int j, uint32_t a, uint32_t b) {
  asm volatile("{\n.reg .pred p, q, e;\n.reg .b64 x, ad;\n" SA("%3", "%8") GADDR("%0", "%1", "%2")
               "setp.lt.s32 p, %4, %5;\nsetp.gt.s32 q, %4, %5;\nsetp.eq.s32 e, %4, %5;\nmov.b64 x, {%6,%7};\n"
               "@p st.relaxed.gpu.global.b64 [ad+-1024], x;\n@q st.relaxed.gpu.global.b64 [ad], x;\n@e st.shared.v2.u32 [sa], {%6,%7};\n}"
               ::"l"(ub), "r"(off), "l"((uint64_t)imm), "r"(sm), "r"(i), "r"(j), "r"(a), "r"(b), "r"(win()) : "memory");
}
__device__ __forceinline__ uint4 ldg_line(const void* p) {
  uint4 v; asm volatile("ld.global.nc.L2::128B.v4.u32 {%0,%1,%2,%3}, [%4];" : "=r"(v.x), "=r"(v.y), "=r"(v.z), "=r"(v.w) : "l"(p)); return v;
}
__device__ __forceinline__ void stg4(void* ub, uint32_t off, uint32_t imm, uint32_t v) {
  asm volatile("{\n.reg .b64 ad;\n" GADDR("%0", "%1", "%2") "st.global.u32 [ad], %3;\n}" ::"l"(ub), "r"(off), "l"((uint64_t)imm), "r"(v) : "memory");
}
__device__ __forceinline__ uint32_t tid_() { uint32_t t; asm volatile("mov.u32 %0, %%tid.x;" : "=r"(t)); return t & 127; }
__device__ __forceinline__ uint32_t nz(uint32_t w) { return max(w, 1u); }
__device__ __forceinline__ void mma16816(float (&c)[4], uint32_t a0, uint32_t a1, uint32_t a2, uint32_t a3, uint32_t b0, uint32_t b1) {
  asm("mma.sync.aligned.m16n8k16.row.col.f32.bf16.bf16.f32 {%0,%1,%2,%3}, {%4,%5,%6,%7}, {%8,%9}, {%0,%1,%2,%3};"
               : "+f"(c[0]), "+f"(c[1]), "+f"(c[2]), "+f"(c[3]) : "r"(a0), "r"(a1), "r"(a2), "r"(a3), "r"(b0), "r"(b1));
}
__device__ __forceinline__ void mma1688(float (&c)[4], uint32_t a0, uint32_t a1, uint32_t b0) {
  asm("mma.sync.aligned.m16n8k8.row.col.f32.bf16.bf16.f32 {%0,%1,%2,%3}, {%4,%5}, {%6}, {%0,%1,%2,%3};"
               : "+f"(c[0]), "+f"(c[1]), "+f"(c[2]), "+f"(c[3]) : "r"(a0), "r"(a1), "r"(b0));
}
__device__ __forceinline__ float ex2(float x) { float r; asm("ex2.approx.ftz.f32 %0, %1;" : "=f"(r) : "f"(x)); return r; }
__device__ __forceinline__ float quad_sum(float v) { v += __shfl_xor_sync(0xffffffffu, v, 1); v += __shfl_xor_sync(0xffffffffu, v, 2); return v; }
__device__ __forceinline__ float quad_max(float v) { v = fmaxf(v, __shfl_xor_sync(0xffffffffu, v, 1)); v = fmaxf(v, __shfl_xor_sync(0xffffffffu, v, 2)); return v; }

__device__ __forceinline__ void wgmma_rs_n64(float (&d)[32], uint32_t a0, uint32_t a1, uint32_t a2, uint32_t a3, uint64_t desc, int scale_d) {
  asm volatile("{\n.reg .pred p;\nsetp.ne.b32 p, %37, 0;\n"
    "wgmma.mma_async.sync.aligned.m64n64k16.f32.bf16.bf16 "
    "{%0, %1, %2, %3, %4, %5, %6, %7, %8, %9, %10, %11, %12, %13, %14, %15, %16, %17, %18, %19, %20, %21, %22, %23, %24, %25, %26, %27, %28, %29, %30, %31}, "
    "{%32, %33, %34, %35}, %36, p, 1, 1, 1;\n}\n"
    : "+f"(d[0]), "+f"(d[1]), "+f"(d[2]), "+f"(d[3]), "+f"(d[4]), "+f"(d[5]), "+f"(d[6]), "+f"(d[7]), "+f"(d[8]), "+f"(d[9]), "+f"(d[10]), "+f"(d[11]), "+f"(d[12]), "+f"(d[13]), "+f"(d[14]), "+f"(d[15]), "+f"(d[16]), "+f"(d[17]), "+f"(d[18]), "+f"(d[19]), "+f"(d[20]), "+f"(d[21]), "+f"(d[22]), "+f"(d[23]), "+f"(d[24]), "+f"(d[25]), "+f"(d[26]), "+f"(d[27]), "+f"(d[28]), "+f"(d[29]), "+f"(d[30]), "+f"(d[31])
    : "r"(a0), "r"(a1), "r"(a2), "r"(a3), "l"(desc), "r"(scale_d));
}

__device__ __forceinline__ void wgmma_rs_n72(float (&d)[36], uint32_t a0, uint32_t a1, uint32_t a2, uint32_t a3, uint64_t desc, int scale_d) {
  asm volatile("{\n.reg .pred p;\nsetp.ne.b32 p, %41, 0;\n"
    "wgmma.mma_async.sync.aligned.m64n72k16.f32.bf16.bf16 "
    "{%0, %1, %2, %3, %4, %5, %6, %7, %8, %9, %10, %11, %12, %13, %14, %15, %16, %17, %18, %19, %20, %21, %22, %23, %24, %25, %26, %27, %28, %29, %30, %31, %32, %33, %34, %35}, "
    "{%36, %37, %38, %39}, %40, p, 1, 1, 1;\n}\n"
    : "+f"(d[0]), "+f"(d[1]), "+f"(d[2]), "+f"(d[3]), "+f"(d[4]), "+f"(d[5]), "+f"(d[6]), "+f"(d[7]), "+f"(d[8]), "+f"(d[9]), "+f"(d[10]), "+f"(d[11]), "+f"(d[12]), "+f"(d[13]), "+f"(d[14]), "+f"(d[15]), "+f"(d[16]), "+f"(d[17]), "+f"(d[18]), "+f"(d[19]), "+f"(d[20]), "+f"(d[21]), "+f"(d[22]), "+f"(d[23]), "+f"(d[24]), "+f"(d[25]), "+f"(d[26]), "+f"(d[27]), "+f"(d[28]), "+f"(d[29]), "+f"(d[30]), "+f"(d[31]), "+f"(d[32]), "+f"(d[33]), "+f"(d[34]), "+f"(d[35])
    : "r"(a0), "r"(a1), "r"(a2), "r"(a3), "l"(desc), "r"(scale_d));
}

__device__ __forceinline__ void wgmma_rs_n128(float (&d)[64], uint32_t a0, uint32_t a1, uint32_t a2, uint32_t a3, uint64_t desc, int scale_d) {
  asm volatile("{\n.reg .pred p;\nsetp.ne.b32 p, %69, 0;\n"
    "wgmma.mma_async.sync.aligned.m64n128k16.f32.bf16.bf16 "
    "{%0, %1, %2, %3, %4, %5, %6, %7, %8, %9, %10, %11, %12, %13, %14, %15, %16, %17, %18, %19, %20, %21, %22, %23, %24, %25, %26, %27, %28, %29, %30, %31, %32, %33, %34, %35, %36, %37, %38, %39, %40, %41, %42, %43, %44, %45, %46, %47, %48, %49, %50, %51, %52, %53, %54, %55, %56, %57, %58, %59, %60, %61, %62, %63}, "
    "{%64, %65, %66, %67}, %68, p, 1, 1, 1;\n}\n"
    : "+f"(d[0]), "+f"(d[1]), "+f"(d[2]), "+f"(d[3]), "+f"(d[4]), "+f"(d[5]), "+f"(d[6]), "+f"(d[7]), "+f"(d[8]), "+f"(d[9]), "+f"(d[10]), "+f"(d[11]), "+f"(d[12]), "+f"(d[13]), "+f"(d[14]), "+f"(d[15]), "+f"(d[16]), "+f"(d[17]), "+f"(d[18]), "+f"(d[19]), "+f"(d[20]), "+f"(d[21]), "+f"(d[22]), "+f"(d[23]), "+f"(d[24]), "+f"(d[25]), "+f"(d[26]), "+f"(d[27]), "+f"(d[28]), "+f"(d[29]), "+f"(d[30]), "+f"(d[31]), "+f"(d[32]), "+f"(d[33]), "+f"(d[34]), "+f"(d[35]), "+f"(d[36]), "+f"(d[37]), "+f"(d[38]), "+f"(d[39]), "+f"(d[40]), "+f"(d[41]), "+f"(d[42]), "+f"(d[43]), "+f"(d[44]), "+f"(d[45]), "+f"(d[46]), "+f"(d[47]), "+f"(d[48]), "+f"(d[49]), "+f"(d[50]), "+f"(d[51]), "+f"(d[52]), "+f"(d[53]), "+f"(d[54]), "+f"(d[55]), "+f"(d[56]), "+f"(d[57]), "+f"(d[58]), "+f"(d[59]), "+f"(d[60]), "+f"(d[61]), "+f"(d[62]), "+f"(d[63])
    : "r"(a0), "r"(a1), "r"(a2), "r"(a3), "l"(desc), "r"(scale_d));
}

__device__ __forceinline__ void wgmma_rs_n144(float (&d)[72], uint32_t a0, uint32_t a1, uint32_t a2, uint32_t a3, uint64_t desc, int scale_d) {
  asm volatile("{\n.reg .pred p;\nsetp.ne.b32 p, %77, 0;\n"
    "wgmma.mma_async.sync.aligned.m64n144k16.f32.bf16.bf16 "
    "{%0, %1, %2, %3, %4, %5, %6, %7, %8, %9, %10, %11, %12, %13, %14, %15, %16, %17, %18, %19, %20, %21, %22, %23, %24, %25, %26, %27, %28, %29, %30, %31, %32, %33, %34, %35, %36, %37, %38, %39, %40, %41, %42, %43, %44, %45, %46, %47, %48, %49, %50, %51, %52, %53, %54, %55, %56, %57, %58, %59, %60, %61, %62, %63, %64, %65, %66, %67, %68, %69, %70, %71}, "
    "{%72, %73, %74, %75}, %76, p, 1, 1, 1;\n}\n"
    : "+f"(d[0]), "+f"(d[1]), "+f"(d[2]), "+f"(d[3]), "+f"(d[4]), "+f"(d[5]), "+f"(d[6]), "+f"(d[7]), "+f"(d[8]), "+f"(d[9]), "+f"(d[10]), "+f"(d[11]), "+f"(d[12]), "+f"(d[13]), "+f"(d[14]), "+f"(d[15]), "+f"(d[16]), "+f"(d[17]), "+f"(d[18]), "+f"(d[19]), "+f"(d[20]), "+f"(d[21]), "+f"(d[22]), "+f"(d[23]), "+f"(d[24]), "+f"(d[25]), "+f"(d[26]), "+f"(d[27]), "+f"(d[28]), "+f"(d[29]), "+f"(d[30]), "+f"(d[31]), "+f"(d[32]), "+f"(d[33]), "+f"(d[34]), "+f"(d[35]), "+f"(d[36]), "+f"(d[37]), "+f"(d[38]), "+f"(d[39]), "+f"(d[40]), "+f"(d[41]), "+f"(d[42]), "+f"(d[43]), "+f"(d[44]), "+f"(d[45]), "+f"(d[46]), "+f"(d[47]), "+f"(d[48]), "+f"(d[49]), "+f"(d[50]), "+f"(d[51]), "+f"(d[52]), "+f"(d[53]), "+f"(d[54]), "+f"(d[55]), "+f"(d[56]), "+f"(d[57]), "+f"(d[58]), "+f"(d[59]), "+f"(d[60]), "+f"(d[61]), "+f"(d[62]), "+f"(d[63]), "+f"(d[64]), "+f"(d[65]), "+f"(d[66]), "+f"(d[67]), "+f"(d[68]), "+f"(d[69]), "+f"(d[70]), "+f"(d[71])
    : "r"(a0), "r"(a1), "r"(a2), "r"(a3), "l"(desc), "r"(scale_d));
}

template <int N> struct WG;
template <> struct WG<64>  { static __device__ __forceinline__ void f(float (&d)[32], const uint32_t* a, uint64_t ds, int s) { wgmma_rs_n64(d, a[0], a[1], a[2], a[3], ds, s); } };
template <> struct WG<72>  { static __device__ __forceinline__ void f(float (&d)[36], const uint32_t* a, uint64_t ds, int s) { wgmma_rs_n72(d, a[0], a[1], a[2], a[3], ds, s); } };
template <> struct WG<128> { static __device__ __forceinline__ void f(float (&d)[64], const uint32_t* a, uint64_t ds, int s) { wgmma_rs_n128(d, a[0], a[1], a[2], a[3], ds, s); } };
template <> struct WG<144> { static __device__ __forceinline__ void f(float (&d)[72], const uint32_t* a, uint64_t ds, int s) { wgmma_rs_n144(d, a[0], a[1], a[2], a[3], ds, s); } };

constexpr uint64_t DESC_SW128 = ((uint64_t)(8192 >> 4) << 16) | ((uint64_t)(1024 >> 4) << 32) | (1ull << 62);
constexpr uint64_t DESC_KV = ((uint64_t)(128 >> 4) << 16) | ((uint64_t)(768 >> 4) << 32);
constexpr uint64_t DESC_Q = ((uint64_t)(128 >> 4) << 16) | ((uint64_t)(1536 >> 4) << 32);

template <int V> struct IntC { static constexpr int value = V; };
enum { PS_KV, PS_Q, PS_WO, PS_FF, PS_FFA   };
template <int PS> __host__ __device__ constexpr int pass_slot(int i) {
  return PS == PS_KV ? (i < 3 ? 9 + i : i - 3) : PS == PS_WO ? 6 + i : i;
}

__device__ __forceinline__ void load_frag(uint32_t (&a)[144], int i, const uint8_t* sb, uint32_t uo, uint32_t t) {
  if (i < 32) ld16(&a[4 * i], sb, uo + t * 16, i * 2048);
  else { ld8(&a[4 * i], sb, uo + t * 8, i * 2048); ld8(&a[4 * i + 2], sb, uo + t * 8, i * 2048 + 1024); }
}
__device__ __forceinline__ void store_own(const uint32_t (&y)[18], uint8_t* sb, uint32_t uo, int j, uint32_t t) {
#pragma unroll
  for (int i = 0; i < 4; i++) st16(sb, uo + j * 8192 + t * 16, i * 2048, nz(y[4 * i]), y[4 * i + 1], y[4 * i + 2], y[4 * i + 3]);
  st8(sb, uo + j * 1024 + t * 8, 65536, nz(y[16]), y[17]);
}
__device__ __forceinline__ void load_own(uint32_t* y, const uint8_t* sb, uint32_t uo, int j) {
  const uint32_t t = tid_();
#pragma unroll
  for (int i = 0; i < 4; i++) ld16(&y[4 * i], sb, uo + j * 8192 + t * 16, i * 2048);
  ld8(&y[16], sb, uo + j * 1024 + t * 8, 65536);
}

struct NoTail { __device__ __forceinline__ void operator()() const {} };
template <int N, int PS, int KPS, int KSTEP, int CHK, bool SUB, bool HREL = false, class Tail = NoTail>
__device__ __forceinline__ void mma_pass(float (&acc)[N / 2], uint32_t (&a)[144], uint64_t desc, uint32_t par, const Rel& rel, int bar_id,
                                         const uint8_t* sb = nullptr, uint32_t uo = 0, uint32_t flag = 0, uint32_t m0 = 0, uint32_t m1 = 0, uint32_t park = 0, Tail tail = Tail()) {
  constexpr int NS = 36 / KPS;
  auto check = [&](int lo, int hi, uint32_t m0_) {
    while (true) {
      uint32_t m = m0_;
#pragma unroll
      for (int i = hi - 1; i >= lo; i--) m = min(m, i < 32 ? a[4 * i] : min(a[4 * i], a[4 * i + 2]));
      if (!__any_sync(0xffffffffu, (m | flag) == 0)) break;
      const uint32_t t = tid_();
#pragma unroll
      for (int i = lo; i < hi; i++) load_frag(a, i, sb, uo, t);
    }
  };
#pragma unroll
  for (int s = 0; s < NS; s++) {
    const int sl = pass_slot<PS>(s);
    if (CHK && s == 0 && !SUB) check(0, CHK * KPS, ~0u);
    if (CHK && s == CHK) check(CHK * KPS, 36, lds32(SM_EPOCH) | 1);
    if (SUB) {
#pragma unroll
      for (int i = s * KPS * 4; i < (s + 1) * KPS * 4; i += 2) { a[i] = bf2_sub(a[i], m0); a[i + 1] = bf2_sub(a[i + 1], m1); }
    }
    if (PS == PS_Q && s == Q_SPLIT && flag) bar_sync(NB_ORD2, 256);
    if (PS == PS_KV && s == 0) sts128(park + tid_() * 16, a[0], a[1], a[2], a[3]);
    mbar_wait(bar_full(sl), sl < 9 ? par : par ^ 1);
    wg_fence();
#pragma unroll
    for (int kk = 0; kk < KPS; kk++)
      WG<N>::f(acc, &a[(s * KPS + kk) * 4], desc + ((slot_addr(sl) + kk * KSTEP) >> 4), (s | kk) || PS == PS_FFA);
    wg_commit();
    if (CHK && s < 2 && N_UP < 36 && !flag) {
      const uint32_t t = tid_();
#pragma unroll
      for (int i = s ? (N_UP + 36) / 2 : N_UP; i < (s ? 36 : (N_UP + 36) / 2); i++) load_frag(a, i, sb, uo, t);
    }
    if (s == (PS == PS_KV ? KV_LEAD : NS - 1) && bar_id >= 0) bar_arrive(bar_id, 256);
    if (s > 0) {
      wg_wait<1>();
      if (!(PS == PS_WO && s > 3)) rel(pass_slot<PS>(s - 1));
    }
    if (HREL && s == 3 && flag) {
#pragma unroll
      for (int i = 0; i < 12; i++) ld16(&a[4 * i], sb, uo, i * 2048);
    }
  }
  tail();
  wg_wait<0>();
  if (PS != PS_WO) rel(pass_slot<PS>(NS - 1));
}

template <int NF, int N0 = 0> __device__ __forceinline__ void load_frags(uint32_t (&a)[144], const uint8_t* sb, uint32_t uo, uint32_t t) {
#pragma unroll
  for (int i = N0; i < NF; i++) load_frag(a, i, sb, uo, t);
}
__device__ __forceinline__ void ln_scalars(float s1, float s2, uint32_t& m, float& var, uint32_t zero) {
  const float mean = s1 * (1.f / DM);
  var = s2 * (1.f / DM) - mean * mean;
  m = pack_bf16(mean, mean) ^ (__float_as_uint(var) & zero);
}
__device__ __forceinline__ float ln_rstd(float var, float after, uint32_t zero) {
  var = __uint_as_float(__float_as_uint(var) ^ (__float_as_uint(after) & zero));
  float sd, r;
  asm("sqrt.approx.ftz.f32 %0, %1;" : "=f"(sd) : "f"(bf_round(bf_round(fmaxf(var, 0.f)) + 1e-5f)));
  asm("rcp.approx.ftz.f32 %0, %1;" : "=f"(r) : "f"(bf_round(sd)));
  return r;
}
template <int NF> __device__ __forceinline__ void gather_ln(uint32_t (&a)[144], const uint8_t* sb, uint32_t uo, uint32_t sto,
                                          uint32_t& m0, uint32_t& m1, float& r0, float& r1, uint32_t zero) {
  uint32_t u[32];
  const uint32_t t = tid_(), so = sto + (t >> 5) * 1024 + (t & 28) * 4;
#pragma unroll
  for (int i = 0; i < 8; i++) ld16(&u[4 * i], sb, so, OFF_ST + i * 128);
  load_frags<N_UP>(a, sb, uo, t);
  while (true) {
    uint32_t m = a[4 * NF - 4];
#pragma unroll
    for (int i = NF - 2; i >= 0; i--) m = min(m, a[4 * i]);
#pragma unroll
    for (int i = 0; i < 8; i++) m = min(m, u[4 * i]);
    if (!__any_sync(0xffffffffu, m == 0)) break;
#pragma unroll
    for (int i = 0; i < 8; i++) ld16(&u[4 * i], sb, so, OFF_ST + i * 128);
    load_frags<NF>(a, sb, uo, t);
  }
  float v[4];
#pragma unroll
  for (int k = 0; k < 4; k++)
    v[k] = ((__uint_as_float(u[k]) + __uint_as_float(u[4 + k])) + (__uint_as_float(u[8 + k]) + __uint_as_float(u[12 + k]))) +
           ((__uint_as_float(u[16 + k]) + __uint_as_float(u[20 + k])) + (__uint_as_float(u[24 + k]) + __uint_as_float(u[28 + k])));
  ln_scalars(v[1], v[0], m0, r0, zero); ln_scalars(v[3], v[2], m1, r1, zero);
}
struct Stats {
  float s[4] = {0, 0, 0, 0}, d0[4] = {0, 0, 0, 0}, d1[4] = {0, 0, 0, 0};
  __device__ __forceinline__ void add16(const uint32_t* f) {
    mma16816(s, f[0], f[1], f[2], f[3], 0x3f803f80u, 0x3f803f80u);
    mma1688(d0, f[0], f[1], f[0]); mma1688(d1, f[0], f[1], f[1]);
    mma1688(d0, f[2], f[3], f[2]); mma1688(d1, f[2], f[3], f[3]);
  }
  __device__ __forceinline__ float sq0(int g) const { return (g & 1) ? d0[1] : d0[0]; }
  __device__ __forceinline__ float sq1(int g) const { return (g & 1) ? d1[3] : d1[2]; }
};
struct RowStats {
  float s[4] = {0, 0, 0, 0}, u[4] = {0, 0, 0, 0};
  template <int N> __device__ __forceinline__ void add(const uint32_t* y) {
#pragma unroll
    for (int i = 0; i < N; i++) {
      const float lo = bf_lo(y[i]), hi = bf_hi(y[i]);
      const int r = (i & 1) * 2;
      s[r] = fmaf(lo, lo, s[r]); u[r] = fmaf(hi, hi, u[r]); s[r + 1] += lo; u[r + 1] += hi;
    }
  }
  __device__ __forceinline__ uint32_t fold() {
    uint32_t x = 0;
#pragma unroll
    for (int i = 0; i < 4; i++) { s[i] += u[i]; u[i] = 0; x |= __float_as_uint(s[i]); }
    return x;
  }
  __device__ __forceinline__ void store(uint8_t* sb, uint32_t sto, uint32_t t) {
    fold();
#pragma unroll
    for (int i = 0; i < 4; i++) s[i] += __shfl_xor_sync(0xffffffffu, s[i], 1);
#pragma unroll
    for (int i = 0; i < 4; i++) s[i] += __shfl_xor_sync(0xffffffffu, s[i], 2);
    if ((t & 3) == 0) st16(sb, sto + (t >> 5) * 1024 + (t & 28) * 4, OFF_ST, __float_as_uint(s[0]) | 1u, __float_as_uint(s[1]), __float_as_uint(s[2]), __float_as_uint(s[3]));
  }
};
template <bool SET> __device__ __forceinline__ void add_piece(float* acc, uint32_t sm) {
#pragma unroll
  for (int i = 0; i < 4; i++) {
    uint32_t v[4];
    lds128(v, sm + i * 2048);
#pragma unroll
    for (int k = 0; k < 4; k++) {
      acc[8 * i + 2 * k] = SET ? bf_lo(v[k]) : acc[8 * i + 2 * k] + bf_lo(v[k]);
      acc[8 * i + 2 * k + 1] = SET ? bf_hi(v[k]) : acc[8 * i + 2 * k + 1] + bf_hi(v[k]);
    }
  }
}

#define TS(i) do {} while (0)
#define TSP(i) do {} while (0)
#define TSH(i) do {} while (0)

__host__ __device__ constexpr int cl_grp(int c) { return c < 4 ? 8 + SMALLPOS : c < 36 ? (c - 4) & 7 : 8 + (c - 36) % 7 + ((c - 36) % 7 >= SMALLPOS); }
__host__ __device__ constexpr int cl_mem(int c) { return c < 4 ? c : c < 36 ? (c - 4) >> 3 : (c - 36) / 7; }
__host__ __device__ constexpr int role_j(int c) {
  return MAP == 0 ? (MC ? (c >> 1) & 7 : c & 7) : MAP == 1 ? c >> 4 : MAP == 2 ? ((c >> 6) << 2) | ((c >> 1) & 3)
       : MAP == 3 ? ((c >> 5) << 1) | ((c >> 2) & 1) : MAP == 4 ? ((c >> 3) & 3) * 2 + ((c >> 2) & 1)
       : MAP == 5 ? (cl_grp(c >> 1) >> 3) * 4 + cl_mem(c >> 1) : MAP == 6 ? (cl_grp(c >> 1) >> 2) * 2 + (cl_mem(c >> 1) & 1)
       : ((cl_grp(c >> 1) >> 1) & 3) * 2 + (cl_mem(c >> 1) & 1);
}
__host__ __device__ constexpr int role_rb(int c) {
  return MAP == 0 ? (MC ? (c >> 4) * 2 + (c & 1) : c >> 3) : MAP == 1 ? c & 15 : MAP == 2 ? ((c >> 3) & 7) * 2 + (c & 1)
       : MAP == 3 ? ((c >> 3) & 3) * 4 + (c & 3) : MAP == 4 ? (c >> 5) * 4 + (c & 3)
       : MAP == 5 ? (cl_grp(c >> 1) & 7) * 2 + (c & 1) : MAP == 6 ? (cl_grp(c >> 1) & 3) * 4 + (cl_mem(c >> 1) >> 1) * 2 + (c & 1)
       : ((cl_grp(c >> 1) >> 3) * 2 + (cl_grp(c >> 1) & 1)) * 4 + (cl_mem(c >> 1) >> 1) * 2 + (c & 1);
}

__device__ __forceinline__ uint32_t row_off(int rb, int wg, uint32_t t) { return (rb * 128 + wg + ((t >> 5) * 16 + (t & 15)) * 2) * (2 * DM); }

__device__ __forceinline__ const __nv_bfloat16* wo_src(const __nv_bfloat16* wo, int k, int u, int j) {
  const int ko = k < 512 ? (k >> 6) * 72 + (k & 63) : ((k >> 3) & 7) * 72 + 64 + (k & 7);
  return wo + ko * 576 + (u < 8 ? j * 64 + u * 8 : 512 + j * 8);
}

struct Params {
  const __nv_bfloat16 *x, *wqkv, *wo, *wg, *wu, *wd;
  __nv_bfloat16* out;
  uint8_t* scr;
  uint8_t* times;
  unsigned zero;
};

__device__ __forceinline__ void tma_prefetch(const CUtensorMap* m, int c0, int c1) {
  asm volatile("cp.async.bulk.prefetch.tensor.2d.L2.global [%0, {%1, %2}];" ::"l"(m), "r"(c0), "r"(c1) : "memory");
}
__device__ __forceinline__ void fill_packed(int sl, uint32_t par, const uint8_t* src, uint32_t rank, uint32_t own) {
  mbar_wait(bar_empty(sl), par);
  mbar_expect_tx(bar_full(sl), PSLOT);
  if (MC) bulk_load_mc(own + slot_addr(sl) + rank * (PSLOT / 2), src + rank * (PSLOT / 2), PSLOT / 2, own + bar_full(sl));
  else bulk_load(slot_addr(sl), src, PSLOT, bar_full(sl));
}

__cluster_dims__(2, 1, 1)
__global__ void __launch_bounds__(384, 1)
fused_kernel(const __grid_constant__ CUtensorMap map_x, const __grid_constant__ CUtensorMap map_wg,
             const __grid_constant__ CUtensorMap map_wu, const __grid_constant__ CUtensorMap map_wd, const Params P) {
  const int wg = __shfl_sync(0xffffffffu, threadIdx.x >> 7, 0);
  const int cta = blockIdx.x, rank = MC ? cta & 1 : 0, j = role_j(cta), rb = role_rb(cta);
  const uint32_t own = win();
  unsigned* const flags = (unsigned*)(P.scr + OFF_FLAGS);
  if (__shfl_sync(0xffffffffu, threadIdx.x >> 5, 0) == 11) {
    if (threadIdx.x == 352) {
#pragma unroll
      for (int i = 0; i < 14; i++) { mbar_init(bar_full(i), 1); mbar_init(bar_empty(i), MC && i < 12 ? 4 : 2); }
      mbar_init(bar_full(14), 1); mbar_init(bar_empty(14), 1);
      asm volatile("fence.mbarrier_init.release.cluster;" ::: "memory");
      if (smem_u32(smem_raw) != own + SB) asm volatile("trap;");
    }
    __syncwarp();
    bar_arrive(0, 384);
    if (MC) asm volatile("barrier.cluster.arrive.relaxed.aligned;" ::: "memory");
    if (threadIdx.x == 352) {
#pragma unroll 1
      for (int c = 0; c < 9; c++) {
        mbar_expect_tx(bar_full(c), SLOT);
        tma_3d(own + slot_addr(c), &map_x, c * 64, rb * 64, 0, own + bar_full(c));
      }
    }
  } else {
    const bool on = threadIdx.x < 324;
    const int k = rb * 36 + (on ? threadIdx.x / 36 : 0) * 4 + (threadIdx.x & 3), u = (threadIdx.x % 36) >> 2;
    const uint4* s = (const uint4*)(P.wqkv + k * 1728 + j * 72 + u * 8);
    const uint4 vk = ldg_line(s + 72), vv = ldg_line(s + 144);
    const unsigned ep0 = *(volatile unsigned*)&flags[(72 + cta) * 8];
    if (MC) asm volatile("barrier.cluster.arrive.relaxed.aligned;" ::: "memory");
    bar_sync(0, 384);
    uint8_t* d = P.scr + OFF_WPACK + j * 24 * PSLOT;
    if (on) {
      const uint32_t dkv = (k / 48) * PSLOT + u * 768 + (k % 48) * 16;
      st16(d, dkv, 0, vk.x, vk.y, vk.z, vk.w);
      st16(d, dkv, 9 * 768, vv.x, vv.y, vv.z, vv.w);
    }
    asm volatile("fence.proxy.async.global;" ::: "memory");
    bar_arrive(NB_PUB + 3, 384);
    if (threadIdx.x == 351) sts32(SM_EPOCH, ep0);
    if (wg == 2) bar_sync(NB_PUB + 1, 96);
  }
  __syncwarp();
  if (MC) asm volatile("barrier.cluster.wait.acquire.aligned;" ::: "memory");

  if (wg == 2) {
    asm volatile("setmaxnreg.dec.sync.aligned.u32 24;");
    const int pw = __shfl_sync(0xffffffffu, (threadIdx.x >> 5) & 3, 0), lane = threadIdx.x & 31;
    auto tile_col = [](int t, int h, int j) { return t < 9 ? j * 576 + t * 64 : (t == 9 && h) ? 512 : ((j + ((h ? 0x05760 : 0x04123) >> (4 * (t - 9)))) & 7) * 64; };
    auto prefetch_tile = [&](int t) {
#pragma unroll 1
      for (int b = rb; b < 18; b += 16) {
        const int h = b & 1, k = b >> 1;
        if (t < 9) tma_prefetch(h ? &map_wu : &map_wg, tile_col(t, h, j), k * 64);
        else if (t != 13 || !h) tma_prefetch(&map_wd, tile_col(t, h, j), j * 576 + k * 64);
      }
    };
    if (pw == 0) {
      if (lane == 0) {
        flag_wait(&flags[j * 8], (lds32(SM_EPOCH) + 1) * 16);
        TSP(7);
        asm volatile("fence.proxy.async.global;" ::: "memory");
        const uint8_t* wp = P.scr + OFF_WPACK + j * 24 * PSLOT;
#pragma unroll 1
        for (int s = 0; s < 3; s++) fill_packed(9 + s, 1, wp + s * PSLOT, rank, own);
#pragma unroll 1
        for (int L = 0; L < 2; L++) {
#pragma unroll 1
          for (int s = 0; s < 21; s++) {
            if (s == 9 && L == 0) { flag_wait(&flags[(56 + j) * 8], (lds32(SM_EPOCH) + 1) * 16); asm volatile("fence.proxy.async.global;" ::: "memory"); }
            fill_packed(s < 9 ? s : s - 9, s >= 9 && s < 18, wp + (s + 3) * PSLOT, rank, own);
          }
#pragma unroll 1
          for (int t = 0; t < 14; t++) {
            const int p = t - 9;
            const CUtensorMap* ma = p < 0 ? &map_wg : &map_wd;
            const CUtensorMap* mb = p < 0 ? &map_wu : &map_wd;
            const int ca = tile_col(t, 0, j), cb = tile_col(t, 1, j), r0 = p < 0 ? 0 : j * 576;
            if (L * 14 + t + PF_AHEAD < 28) prefetch_tile((t + PF_AHEAD) % 14);
#pragma unroll 1
            for (int k = 0; k < 9; k++) {
              if (TH && t == 0 && k >= TH && k < 6) { mbar_wait(bar_full(k - TH), 1); for (int i = 0; i < THD; i++) __nanosleep(0); }
              mbar_wait(bar_empty(k), t & 1);
              mbar_expect_tx(bar_full(k), p == 4 ? 8192 : SLOT);
              const int r = r0 + (p < 0 || k == 8 ? k : k < 3 ? k + 5 : k - 3) * 64;
              if (MC) {
                if (p != 4) tma_2d_mc(own + slot_addr(k) + rank * 8192, rank ? mb : ma, rank ? cb : ca, r, own + bar_full(k));
                else if ((k & 1) == rank) tma_2d_mc(own + slot_addr(k), ma, ca, r, own + bar_full(k));
              } else {
                tma_2d(slot_addr(k), ma, ca, r, bar_full(k));
                if (p != 4) tma_2d(slot_addr(k) + 8192, mb, cb, r, bar_full(k));
              }
            }
            if (p == 1 && L == 0) {
              l2_prefetch(wp + rb * (24 * PSLOT / 16), 24 * PSLOT / 16);
#pragma unroll 1
              for (int s = 0; s < 3; s++) fill_packed(9 + s, 1, wp + s * PSLOT, rank, own);
            }
          }
        }
        flags[(72 + cta) * 8] = lds32(SM_EPOCH) + 1;
      }
    } else if (pw < 3) {
      const int hw = pw - 1;
      const uint32_t ep = __shfl_sync(0xffffffffu, lds32(SM_EPOCH), 0);
      uint8_t* const sb = P.scr + (rb * 2 + hw) * STRM;
      const uint32_t xs = slot_addr(12) + hw * SLOT, fb = bar_full(12) + hw * 8;
      uint32_t hph = 0;
#pragma unroll 1
      for (int L = 0; L < 2; L++) {
        const uint32_t tag = ep * 2 + L + 1;
        bar_sync(NB_FREE + hw, 160);
        if (rb > 0) hint_wait(sb + OFF_HINT + 512 + j * 128, tag);
        uint32_t bad;
        do {
          if (rb > 0) {
            if (lane == 0) {
              mbar_expect_tx(bar_full(14) + hw * 128, 3072);
              bulk_load(own + ytail(hw * 2), sb + OFF_HALO + (L * 8 + j) * 3072, 1536, own + bar_full(14) + hw * 128);
              bulk_load(own + ytail(hw * 2 + 1), sb + OFF_HALO + (L * 8 + j) * 3072 + 1536, 1536, own + bar_full(14) + hw * 128);
            }
            mbar_wait(bar_full(14) + hw * 128, hph);
            hph ^= 1;
          }
          bad = 0;
#pragma unroll 1
          for (int c = 0; c < 3; c++) {
            uint32_t u[4] = {tag, 0, 0, 0}, v[4] = {tag, 0, 0, 0};
            if (rb > 0) { lds128(u, ytail(hw * 2) + c * 512 + lane * 16); lds128(v, ytail(hw * 2 + 1) + c * 512 + lane * 16); }
            bad |= (u[0] ^ tag) | (v[0] ^ tag);
#pragma unroll
            for (int i = 0; i < 3; i++) { sts32(xs + KSTG + (c * 3 + i) * 128 + lane * 4, u[i + 1]); sts32(xs + (c * 3 + i) * 128 + lane * 4, v[i + 1]); }
          }
        } while (__any_sync(0xffffffffu, bad != 0));
        bar_arrive(NB_HALO + hw, 160);
#pragma unroll 1
        for (int p = 0; p < 4; p++) {
          if (L == 0 && p == 3) flag_wait(flags + (40 + rb) * 8, (ep + 1) * 8);
          bar_sync(NB_FREE + hw, 160);
          TSH(L * 12 + p * 3);
          hint_wait(sb + OFF_HINT + (lane & 3) * 128, (ep * 13 + L * 7 + p + 3) * 8);
          TSH(L * 12 + p * 3 + 1);
          if (lane == 0) {
            mbar_expect_tx(fb, p ? 16384 : 15360);
            bulk_load(own + xs, sb + OFF_P + j * PSRC + (p & 1) * 16384, p ? 16384 : 8192, own + fb);
            if (p == 0) bulk_load(own + xs + 8192, sb + OFF_P + j * PSRC + 32768, 7168, own + fb);
          }
          TSH(L * 12 + p * 3 + 2);
        }
      }
    } else {
      auto clear = [&](int t) {
        const uint32_t so = rb * 2 * STRM + (threadIdx.x & 31) * 16;
#pragma unroll 1
        for (int i = 0; i < 18; i++) {
          st16(P.scr, so + t * TILE + j * 9216 + i * 512, 0, 0, 0, 0, 0);
          st16(P.scr, so + t * TILE + j * 9216 + i * 512, STRM, 0, 0, 0, 0);
          __nanosleep(CLR_NS);
        }
        if (t != 1) {
          st16(P.scr, so + (t ? t - 1 : 0) * 4096 + j * 512, OFF_ST, 0, 0, 0, 0);
          st16(P.scr, so + (t ? t - 1 : 0) * 4096 + j * 512, OFF_ST + STRM, 0, 0, 0, 0);
        }
      };
      bar_sync(NB_PUB + 3, 384);
      if (lane == 0) flag_signal(&flags[j * 8]);
      TSP(5);
      bar_sync(NB_PUB + 2, 288);
      if (lane == 0) flag_signal(&flags[(56 + j) * 8]);
      TSP(4);
      if (lane == 0) {
#pragma unroll 1
        for (int t = 0; t < PF_AHEAD; t++) prefetch_tile(t);
      }
      __syncwarp();
#pragma unroll 1
      for (int L = 0; L < 2; L++) {
        timed_wait(bar_empty(13), L);
#pragma unroll 1
        for (int t = L ^ 1; t < 4 - 2 * L; t++) clear(t);
        __syncwarp();
        if (lane == 0 && L == 0) flag_signal(flags + (40 + rb) * 8);
      }
      timed_wait(bar_empty(12), 0);
      if (MC) asm volatile("barrier.cluster.arrive.relaxed.aligned;\nbarrier.cluster.wait.aligned;" ::: "memory");
    }
  } else {
    asm volatile("setmaxnreg.inc.sync.aligned.u32 240;");
    const int w = __shfl_sync(0xffffffffu, (threadIdx.x >> 5) & 3, 0);
    const bool leader = (threadIdx.x & 127) == 0;
    const Rel rel{MC ? (threadIdx.x & 95) == 0 : leader, MC ? cta_window(w & 1) : 0};
    uint8_t* const sb = P.scr + (rb * 2 + wg) * STRM;
    uint8_t* const hint = sb + OFF_HINT + w * 128;
    auto hint_target = [](int e) { return (lds32(SM_EPOCH) * 13 + e + 1) * 8; };
    TS(0);
    uint32_t a[144];
#pragma unroll 1
    for (int L = 0; L < 2; L++) {
      uint32_t m0, m1; float r0, r1;
      if (L == 0) {
        Stats st;
        const int lane = tid_() & 31, g = lane >> 2;
        const int row = w * 16 + (lane & 15);
        const uint32_t ra = SB + wg * 8192 + row * 128;
        const uint32_t pt = tid_(), pu = (pt % 36) >> 2, pk = rb * 36 + (pt < 108 ? pt / 36 : 0) * 4 + (pt & 3);
        uint4 pv[3];
#pragma unroll
        for (int i = 0; i < 3; i++) pv[i] = ldg_line(wg ? wo_src(P.wo, pk + i * 12, pu, j) : P.wqkv + (pk + i * 12) * 1728 + j * 72 + pu * 8);
#pragma unroll
        for (int c = 0; c < 9; c++) {
          mbar_wait(bar_full(c), 0);
          if (c == 0) TS(60); if (c == 8) TS(62);
#pragma unroll
          for (int kk = 0; kk < 4; kk++) ldsm4(&a[c * 16 + kk * 4], ra + (((kk * 2 + (lane >> 4)) ^ (row & 7)) << 4) + c * SLOT);
          if (c == 8) {
            uint32_t y[18], z[4];
#pragma unroll
            for (int i = 0; i < 4; i++) ldsm4(&y[4 * i], ra + (((i * 2 + (lane >> 4)) ^ (row & 7)) << 4) + j * SLOT);
            ldsm4(z, ra + ((j ^ (row & 7)) << 4) + 8 * SLOT);
            y[16] = z[0]; y[17] = z[1];
            bar_sync(NB_WG + wg, 128);
#pragma unroll
            for (int i = 0; i < 9; i++) rel(i);
            if (pt < 108) {
#pragma unroll
              for (int i = 0; i < 3; i++) {
                const uint32_t k = pk + i * 12;
                st16(P.scr, (j * 24 + wg * 6 + k / 96) * PSLOT + pu * 1536 + (k % 96) * 16, OFF_WPACK + 12 * PSLOT, pv[i].x, pv[i].y, pv[i].z, pv[i].w);
              }
            }
            asm volatile("fence.proxy.async.global;" ::: "memory");
            bar_arrive(NB_PUB + 2, 288);
            store_own(y, sb, OFF_X2, j, tid_());
          }
#pragma unroll
          for (int kk = 0; kk < 4; kk++) st.add16(&a[c * 16 + kk * 4]);
        }
        const int dl = (lane & ~3) | (g >> 1);
        ln_scalars(st.s[0], __shfl_sync(0xffffffffu, st.sq0(g), dl), m0, r0, P.zero);
        ln_scalars(st.s[2], __shfl_sync(0xffffffffu, st.sq1(g), dl), m1, r1, P.zero);
      } else {
#pragma unroll
        for (int i = 4 * N_UP; i < 144; i++) a[i] = 0;
        hint_wait(hint, hint_target(6));
        TS(61);
        gather_ln<3 * D_KV>(a, sb, OFF_X2, 8192, m0, m1, r0, r1, P.zero);
      }
      TS(1 + L * 20);
      uint32_t kf[18], qf[18];
      {
        float acc[72];
        if (wg == 1) bar_sync(NB_ORD1, 256);
        mma_pass<144, PS_KV, 3, 256, D_KV, true>(acc, a, DESC_KV, 1, rel, wg == 0 ? NB_ORD1 : -1, sb, OFF_X2, L ^ 1, m0, m1, ytail(wg * 2));
        r0 = ln_rstd(r0, acc[0], P.zero); r1 = ln_rstd(r1, acc[0], P.zero);
        uint32_t vf[18];
#pragma unroll
        for (int c = 0; c < 9; c++) {
          kf[2 * c] = pack_bf16(acc[4 * c] * r0, acc[4 * c + 1] * r0);
          kf[2 * c + 1] = pack_bf16(acc[4 * c + 2] * r1, acc[4 * c + 3] * r1);
          vf[c] = pack_bf16(acc[36 + 4 * c] * r0, acc[36 + 4 * c + 1] * r0);
          vf[9 + c] = pack_bf16(acc[36 + 4 * c + 2] * r1, acc[36 + 4 * c + 3] * r1);
        }
        TS(2 + L * 20);
        const uint32_t l16 = (tid_() & 31) * 16, xs = slot_addr(12) + wg * SLOT + w * 1152;
#pragma unroll
        for (int i = 0; i < 4; i++) stsm4(xs + w * 1152 + 1152 + i * 512 + l16, vf[4 * i], vf[4 * i + 1], vf[4 * i + 2], vf[4 * i + 3]);
        sts32(xs + w * 1152 + 1152 + 2048 + l16 / 4, vf[16]); sts32(xs + w * 1152 + 1152 + 2176 + l16 / 4, vf[17]);
        if (w < 3) {
          stsm4(xs + KSTG + 1152 + l16, kf[1], kf[3], kf[5], kf[7]);
          stsm4(xs + KSTG + 1152 + 512 + l16, kf[9], kf[11], kf[13], kf[15]);
          sts32(xs + KSTG + 1152 + 1024 + l16 / 4, kf[17]);
        } else if (rb < 15) {
          const uint32_t tag = lds32(SM_EPOCH) * 2 + L + 1;
          const uint32_t ho = l16 + (L * 8 + j) * 3072;
#pragma unroll
          for (int c = 0; c < 3; c++) {
            st16(sb, ho, 2 * STRM + OFF_HALO + c * 512, tag, kf[6 * c + 1], kf[6 * c + 3], kf[6 * c + 5]);
            st16(sb, ho, 2 * STRM + OFF_HALO + 1536 + c * 512, tag, vf[9 + 3 * c], vf[10 + 3 * c], vf[11 + 3 * c]);
          }
          hint_post(sb + 2 * STRM + OFF_HINT + 512 + j * 128);
        }
      }
      lds128(a, ytail(wg * 2) + tid_() * 16);
      bar_arrive(NB_FREE + wg, 160);
      uint32_t kh[12];
      {
        float acc[36];
        if (wg == 1) bar_sync(NB_ORD1, 256);
        mma_pass<72, PS_Q, 6, 256, 0, false, false>(acc, a, DESC_Q, 0, rel, -1, nullptr, 0, wg, 0, 0, 0, [&]() {
          bar_sync(NB_HALO + wg, 160);
#pragma unroll
          for (int i = 0; i < 3; i++) ldsm4(&kh[4 * i], slot_addr(12) + wg * SLOT + w * 640 + tid_() * 16 + KSTG + i * 512);
        });
#pragma unroll
        for (int i = 0; i < 18; i++) qf[i] = pack_bf16(acc[2 * i], acc[2 * i + 1]);
      }
      TS(3 + L * 20);
      uint32_t xr[18];
      {
        const int tid = tid_(), g = (tid >> 2) & 7, q = tid & 3;
        uint32_t vt[28];
#pragma unroll
        for (int i = 0; i < 7; i++) ldsm4t(&vt[4 * i], slot_addr(12) + wg * SLOT + w * 1792 + tid * 16 + i * 512);
        const bool nohalo = (rb == 0 && w == 0);
        const bool le0 = 2 * q <= g, le1 = 2 * q + 1 <= g;
        const uint32_t M = (le0 ? 0xffffu : 0u) | (le1 ? 0xffff0000u : 0u);
        const float sc0 = r0 * (0.23570226039551584f * 1.4426950408889634f), sc1 = r1 * (0.23570226039551584f * 1.4426950408889634f);
        float l[16], t[8];
#pragma unroll
        for (int h = 0; h < 4; h++) {
          const uint32_t qa0 = q >= h ? qf[4 * h] : 0u, qa1 = q >= h ? qf[4 * h + 1] : 0u;
          const uint32_t qc0 = q <= h ? qf[4 * h + 4] : 0u, qc1 = q <= h ? qf[4 * h + 5] : 0u;
          float sm[4] = {0, 0, 0, 0}, s0[4] = {0, 0, 0, 0}, s1[4] = {0, 0, 0, 0};
          mma16816(s0, qa0, qa1, qf[4 * h + 2], qf[4 * h + 3], kf[4 * h], kf[4 * h + 2]);
          mma16816(s1, qa0, qa1, qf[4 * h + 2], qf[4 * h + 3], kf[4 * h + 1], kf[4 * h + 3]);
          mma16816(sm, qa0, qa1, qf[4 * h + 2], qf[4 * h + 3], kh[2 * h], kh[2 * h + 1]);
          mma1688(s0, qc0, qc1, kf[4 * h + 4]);
          mma1688(s1, qc0, qc1, kf[4 * h + 5]);
          mma1688(sm, qc0, qc1, kh[2 * h + 2]);
          if (nohalo) sm[0] = sm[1] = -3e38f;
          l[4 * h] = le0 ? s0[0] : sm[0]; l[4 * h + 1] = le1 ? s0[1] : sm[1];
          l[4 * h + 2] = le0 ? s1[2] : s0[2]; l[4 * h + 3] = le1 ? s1[3] : s0[3];
        }
#pragma unroll
        for (int i = 0; i < 8; i++) t[i] = fmaxf(l[2 * i], l[2 * i + 1]);
        if (wg == 0) {
          uint32_t x = 0;
#pragma unroll
          for (int i = 0; i < 8; i++) x |= __float_as_uint(t[i]);
          bar_arrive(NB_ORD1 + (x & P.zero), 256);
        }
        TS(14 + L * 20);
#pragma unroll
        for (int i = 0; i < 8; i++) t[i] = fmaxf(t[i], __shfl_xor_sync(0xffffffffu, t[i], 1));
#pragma unroll
        for (int i = 0; i < 8; i++) t[i] = fmaxf(t[i], __shfl_xor_sync(0xffffffffu, t[i], 2)) * ((i & 1) ? sc1 : sc0);
#pragma unroll
        for (int i = 0; i < 8; i++) {
          const float sc = (i & 1) ? sc1 : sc0;
          l[2 * i] = ex2(fmaf(l[2 * i], sc, -t[i])); l[2 * i + 1] = ex2(fmaf(l[2 * i + 1], sc, -t[i])); t[i] = l[2 * i] + l[2 * i + 1];
        }
#pragma unroll
        for (int i = 0; i < 8; i++) t[i] += __shfl_xor_sync(0xffffffffu, t[i], 1);
#pragma unroll
        for (int i = 0; i < 8; i++) t[i] += __shfl_xor_sync(0xffffffffu, t[i], 2);
        uint32_t pf[16];
#pragma unroll
        for (int i = 0; i < 8; i++) {
          float r; asm("rcp.approx.ftz.f32 %0, %1;" : "=f"(r) : "f"(t[i]));
          const uint32_t p = pack_bf16(l[2 * i] * r, l[2 * i + 1] * r);
          pf[2 * i] = p & ~M; pf[2 * i + 1] = p & M;
        }
#pragma unroll
        for (int c = 0; c < 9; c++) {
          const int h = c == 8 ? 3 : c >> 1;
          float o[4] = {0, 0, 0, 0};
          mma16816(o, pf[4 * h], 0u, pf[4 * h + 1], pf[4 * h + 2], vt[c], vt[9 + c]);
          mma1688(o, 0u, pf[4 * h + 3], vt[18 + c]);
          if (c == 2 || c == 4 || c == 6) {
            float e[4] = {0, 0, 0, 0};
            mma16816(e, pf[4 * h - 4], 0u, pf[4 * h - 3], pf[4 * h - 2], vt[c], vt[9 + c]);
            mma1688(e, 0u, pf[4 * h - 1], vt[18 + c]);
            if (q < h) { o[0] = e[0]; o[1] = e[1]; o[2] = e[2]; o[3] = e[3]; }
          }
          qf[2 * c] = pack_bf16(o[0], o[1]); qf[2 * c + 1] = pack_bf16(o[2], o[3]);
        }
        {
          uint32_t x = 0;
#pragma unroll
          for (int i = 0; i < 18; i += 2) x |= qf[i];
          bar_arrive((wg ? NB_ORD0 : NB_ORD2) + (x & P.zero), 256);
        }
        store_own(qf, sb, OFF_O, j, tid);
        hint_post(hint);
        load_own(xr, sb, OFF_X2, j);
      }
      TS(4 + L * 20);
      {
        hint_wait(hint, hint_target(L * 7));
        TS(5 + L * 20);
        load_frags<N_WO>(a, sb, OFF_O, tid_());
        float acc[36];
        if (wg == 0) bar_sync(NB_ORD0, 256);
        load_frags<N_UP, N_WO>(a, sb, OFF_O, tid_());
        TS(19 + L * 20);
        mma_pass<72, PS_WO, 6, 256, D_WO, false>(acc, a, DESC_Q, 0, rel, -1, sb, OFF_O);
        TS(6 + L * 20);
#pragma unroll
        for (int c = 0; c < 9; c++) {
          xr[2 * c] = bf2_add(xr[2 * c], pack_bf16(acc[4 * c], acc[4 * c + 1]));
          xr[2 * c + 1] = bf2_add(xr[2 * c + 1], pack_bf16(acc[4 * c + 2], acc[4 * c + 3]));
        }
        store_own(xr, sb, L * 3 * TILE, j, tid_());
        RowStats rs;
        rs.add<18>(xr);
        rs.store(sb, L * 4096 + j * 128, tid_());
        hint_post(hint);
      }
      TS(16 + L * 20);
      hint_wait(hint, hint_target(L * 7 + 1));
      TS(15 + L * 20);
      gather_ln<4 * D_T0>(a, sb, L * 3 * TILE, L * 4096, m0, m1, r0, r1, P.zero);
      TS(7 + L * 20);
      const uint32_t hb = OFF_H + j * 24576;
      {
        float ka0, kb0, kc0, ka1, kb1, kc1;
        float acc[64];
        uint32_t hf[16];
        auto geglu = [&](auto chains, uint32_t hsm) {
          constexpr int CH = decltype(chains)::value & 15;
          float r[32];
#pragma unroll
          for (int e = 0; e < 32; e++) {
            float x = acc[e];
            if (e >= CH) x = __uint_as_float(__float_as_uint(x) ^ (__float_as_uint(r[e - CH]) & P.zero));
            if (decltype(chains)::value > 15 && e < 20) {
              const uint32_t ad = (e < 8 ? slot_addr(12) + e * 2048 + wg * 8192 : slot_addr(7 + (e >> 2)) + (e & 3) * 2048) + hsm;
              lds128(&a[48 + 4 * e], e >= CH ? ad ^ (__float_as_uint(r[e - CH]) & P.zero) : ad);
            }
            const bool hi = e & 2;
            float t = x * fmaf(x * x, hi ? kb1 : kb0, hi ? ka1 : ka0);
            asm("tanh.approx.f32 %0, %0;" : "+f"(t));
            const float u = x * acc[32 + e] * (hi ? kc1 : kc0);
            r[e] = fmaf(u, t, u);
            if (e & 1) hf[e >> 1] = pack_bf16(r[e - 1], r[e]);
          }
        };
        if (wg == 1) bar_sync(NB_ORD1, 256);
        mma_pass<128, PS_FF, 4, 2048, D_T0, true>(acc, a, DESC_SW128, 1, rel, NB_ORD1 - wg, sb, L * 3 * TILE, 0, m0, m1);
        if (tid_() == 0) mbar_arrive(bar_empty(13));
        TS(8 + L * 20);
        r0 = ln_rstd(r0, acc[0], P.zero); r1 = ln_rstd(r1, acc[0], P.zero);
        ka0 = 0.7978845608028654f * r0; kb0 = 0.035677408136300125f * r0 * r0 * r0; kc0 = 0.5f * r0 * r0;
        ka1 = 0.7978845608028654f * r1; kb1 = 0.035677408136300125f * r1 * r1 * r1; kc1 = 0.5f * r1 * r1;
#pragma unroll 1
        for (int t = 0; t < 8; t++) {
          geglu(IntC<2>(), 0);
          const uint32_t t16 = tid_() * 16;
          if (t < 5) {
            const uint32_t d = (t < 2 ? slot_addr(12) + wg * SLOT + t * 8192 : slot_addr(7) + t * SLOT + wg * 8192) + t16;
#pragma unroll
            for (int i = 0; i < 4; i++)
              sts128(d + i * 2048, hf[4 * i], hf[4 * i + 1], hf[4 * i + 2], hf[4 * i + 3]);
            if (t == 4) asm volatile("fence.proxy.async.shared::cta;" ::: "memory");
          } else {
#pragma unroll
            for (int i = 0; i < 4; i++) st16(sb, hb + (t - 5) * 8192 + t16, i * 2048, hf[4 * i], hf[4 * i + 1], hf[4 * i + 2], hf[4 * i + 3]);
          }
          bar_sync(NB_ORD0 + wg, 256);
          mma_pass<128, PS_FF, 4, 2048, 0, false, true>(acc, a, DESC_SW128, t & 1, rel, NB_ORD1 - wg, sb, hb + t16, t == 7);
        }
        TS(9 + L * 20);
        const uint32_t hsm = wg * 8192 + tid_() * 16;
        geglu(IntC<16 + CH_LAST>(), hsm);
#pragma unroll
        for (int i = 0; i < 16; i++) a[128 + i] = hf[i];
      }
      TS(10 + L * 20);
      {
        const uint32_t xs = slot_addr(12) + wg * SLOT;
        auto verify = [&](int p, uint32_t t16) {
          mbar_wait(bar_full(12) + wg * 8, p & 1);
          TS(71 + L * 32 + p * 5);
          const uint32_t ta = p < 2, tb = (p & 1) ? ta : L ^ 1, nb = p ? 4 : 7, sh = p == 0;
          uint32_t m = 0;
#pragma unroll
          for (int s = 0; s < 4; s++) m |= (lds32(xs + s * 2048 + t16) ^ ta) | (lds32(xs + 8192 + ((s * 2048 + t16) >> sh)) ^ tb);
          if (p == 0) {
#pragma unroll
            for (int s = 4; s < 7; s++) m |= lds32(xs + 8192 + s * 1024 + t16 / 2) ^ tb;
          }
          if (__any_sync(0xffffffffu, m & 1)) {
#pragma unroll 1
            for (int s = 0; s < 4 + nb; s++) {
              const bool nar = sh && s >= 4;
              const uint32_t o = nar ? 4096 + s * 1024 + t16 / 2 : s * 2048 + t16;
              uint32_t v[4] = {0, 0, 0, 0};
              do {
                if (nar) ld8(v, sb, j * PSRC + o, OFF_P + 32768 - 8192);
                else ld16(v, sb, j * PSRC + (p & 1) * 16384 + o, OFF_P);
              } while (__any_sync(0xffffffffu, (v[0] ^ (s < 4 ? ta : tb)) & 1));
              sts64(xs + o, v[0], v[1]);
              if (!nar) sts64(xs + o + 8, v[2], v[3]);
            }
            asm volatile("fence.proxy.async.shared::cta;" ::: "memory");
          }
        };
        uint32_t t16 = (a[142] | a[143]) & P.zero;
#pragma unroll 1
        for (int p = 0; p < 4; p++) {
          float acc[64];
          bar_sync(NB_ORD0 + wg + (p ? 0 : t16), 256);
          TS(64 + L * 32 + p * 5);
          if (p == 0) { rel(9); rel(10); rel(11); }
          mma_pass<128, PS_FF, 4, 2048, 0, false, false>(acc, a, DESC_SW128, p & 1, rel, NB_ORD1 - wg, nullptr, 0, 0, 0, 0, 0, [&]() {
            t16 = tid_() * 16;
            if (p) verify(p - 1, t16);
          });
          TS(65 + L * 32 + p * 5);
          if (p == 1 || p == 2) add_piece<false>(acc, xs + t16);
          const uint32_t oa = ((j + (p < 3 ? 1 : 4)) & 7) * PSRC + (p & 1) * 16384 + t16;
#pragma unroll
          for (int i = 0; i < 4; i++)
            st16(sb, oa, OFF_P + i * 2048, (pack_bf16(acc[8 * i], acc[8 * i + 1]) & ~1u) | (p < 2), pack_bf16(acc[8 * i + 2], acc[8 * i + 3]),
                 pack_bf16(acc[8 * i + 4], acc[8 * i + 5]), pack_bf16(acc[8 * i + 6], acc[8 * i + 7]));
          if (p == 0) {
#pragma unroll
            for (int i = 0; i < 8; i++)
              send8(sb, j * 1024 + t16 / 2, OFF_P + 32768 + i * PSRC, xs + 15360 + t16 / 2, i, j,
                    (pack_bf16(acc[32 + 4 * i], acc[33 + 4 * i]) & ~1u) | (L ^ 1), pack_bf16(acc[34 + 4 * i], acc[35 + 4 * i]));
          } else {
            if (p == 2) add_piece<false>(acc + 32, xs + 8192 + t16);
            const uint32_t ob = ((j + (p < 3 ? 7 : 5)) & 7) * PSRC + (p & 1) * 16384 + t16, tb = p == 2 ? L ^ 1 : p < 2;
#pragma unroll
            for (int i = 4; i < 8; i++)
              st16(sb, ob, OFF_P + i * 2048, (pack_bf16(acc[8 * i], acc[8 * i + 1]) & ~1u) | tb, pack_bf16(acc[8 * i + 2], acc[8 * i + 3]),
                   pack_bf16(acc[8 * i + 4], acc[8 * i + 5]), pack_bf16(acc[8 * i + 6], acc[8 * i + 7]));
          }
          hint_post(hint);
          TS(68 + L * 32 + p * 5);
          if (p == 1) {
            float s0 = 0.f, s1 = 0.f, s2 = 0.f, s3 = 0.f;
#pragma unroll
            for (int s = 0; s < 8; s++) {
              uint32_t u, v;
              lds64(u, v, xs + 8192 + s * 1024 + t16 / 2);
              s0 += bf_lo(u); s1 += bf_hi(u); s2 += bf_lo(v); s3 += bf_hi(v);
            }
            sts64(ytail(wg * 2) + t16 / 2, pack_bf16(s0, s1), pack_bf16(s2, s3));
          }
          if (p < 3) bar_arrive(NB_FREE + wg, 160);
          TS(67 + L * 32 + p * 5);
        }
        float acc[32];
        add_piece<true>(acc, xs + t16);
        add_piece<false>(acc, xs + 8192 + t16);
        bar_arrive(NB_FREE + wg, 160);
        load_own(xr, sb, L * 3 * TILE, j);
        bar_sync(NB_ORD0 + wg, 256);
        TS(84 + L * 32);
        uint32_t t, yn[2];
        mma_pass<64, PS_FFA, 4, 2048, 0, false, false>(acc, a, DESC_SW128, 0, rel, wg ? -1 : NB_ORD1, nullptr, 0, 0, 0, 0, 0, [&]() {
          t = tid_();
          lds64(yn[0], yn[1], ytail(wg * 2) + t * 8);
          mbar_wait(bar_full(12) + wg * 8, 1);
#pragma unroll
          for (int i = 0; i < 8; i++) lds128(&a[4 * i], xs + i * 2048 + t * 16);
        });
        TS(11 + L * 20);
        while (true) {
          uint32_t m = 0;
#pragma unroll
          for (int i = 0; i < 8; i++) m |= a[4 * i];
          if (!__any_sync(0xffffffffu, m & 1)) break;
#pragma unroll
          for (int i = 0; i < 8; i++) ld16(&a[4 * i], sb, j * PSRC + t * 16, OFF_P + 16384 + i * 2048);
        }
        TS(12 + L * 20);
#pragma unroll
        for (int i = 0; i < 18; i++)
          xr[i] = bf2_add(xr[i], i < 16 ? pack_bf16(acc[2 * i] + (bf_lo(a[i]) + bf_lo(a[16 + i])), acc[2 * i + 1] + (bf_hi(a[i]) + bf_hi(a[16 + i]))) : yn[i - 16]);
        TS(18 + L * 20);
        if (L == 0) {
          store_own(xr, sb, OFF_X2, j, t);
          RowStats rs;
          rs.add<18>(xr);
          rs.store(sb, 8192 + j * 128, t);
          hint_post(hint);
        } else {
          __syncwarp();
#pragma unroll
          for (int i = 0; i < 4; i++) stsm4(xs + i * 2048 + t * 16, xr[4 * i], xr[4 * i + 1], xr[4 * i + 2], xr[4 * i + 3]);
          stsm4(xs + 8192 + t * 16, xr[16], xr[17], 0, 0);
          __syncwarp();
          uint8_t* op = (uint8_t*)P.out + row_off(rb, wg, t);
#pragma unroll
          for (int i = 0; i < 5; i++) {
            uint32_t r[4];
            lds128(r, xs + i * 2048 + t * 16);
            if (i < 4) *(uint4*)(op + i * 32 + j * 128 + (t & 16)) = make_uint4(r[0], r[1], r[2], r[3]);
            else if (!(t & 16)) *(uint4*)(op + 1024 + j * 16) = make_uint4(r[0], r[1], r[2], r[3]);
          }
        }
      }
      TS(13 + L * 20);
    }
    bar_sync(NB_WG + wg, 128);
    if (tid_() == 0) mbar_arrive(bar_empty(12));
  }
}

typedef CUresult (*EncodeFn)(CUtensorMap*, CUtensorMapDataType, cuuint32_t, void*, const cuuint64_t*, const cuuint64_t*, const cuuint32_t*,
                             const cuuint32_t*, CUtensorMapInterleave, CUtensorMapSwizzle, CUtensorMapL2promotion, CUtensorMapFloatOOBfill);

void encode(EncodeFn fn, CUtensorMap* m, const void* p, int rank, const cuuint64_t* dims, const cuuint64_t* str, const cuuint32_t* box) {
  const cuuint32_t es[3] = {1, 1, 1};
  fn(m, CU_TENSOR_MAP_DATA_TYPE_BFLOAT16, rank, const_cast<void*>(p), dims, str, box, es, CU_TENSOR_MAP_INTERLEAVE_NONE,
     CU_TENSOR_MAP_SWIZZLE_128B, CU_TENSOR_MAP_L2_PROMOTION_L2_256B, CU_TENSOR_MAP_FLOAT_OOB_FILL_NONE);
}

}

extern "C" void kernel_launch(void* const* d_in, const int* in_sizes, int n_in, void* d_out, int out_size) {
  (void)in_sizes; (void)n_in; (void)out_size;
  Params P;
  P.x = (const __nv_bfloat16*)d_in[0]; P.wqkv = (const __nv_bfloat16*)d_in[1]; P.wo = (const __nv_bfloat16*)d_in[2];
  P.wg = (const __nv_bfloat16*)d_in[4]; P.wu = (const __nv_bfloat16*)d_in[5]; P.wd = (const __nv_bfloat16*)d_in[6];
  P.out = (__nv_bfloat16*)d_out; P.zero = 0;
  cudaGetSymbolAddress((void**)&P.scr, g_scr);
  void* fnp = nullptr; cudaDriverEntryPointQueryResult qr;
  cudaGetDriverEntryPoint("cuTensorMapEncodeTiled", &fnp, cudaEnableDefault, &qr);
  EncodeFn fn = (EncodeFn)fnp;
  CUtensorMap mx, mg, mu, md;
  { const cuuint64_t dims[3] = {DM, SEQ / 2, 2}, str[2] = {DM * 4, DM * 2}; const cuuint32_t box[3] = {64, 64, 2}; encode(fn, &mx, P.x, 3, dims, str, box); }
  { const cuuint64_t dims[2] = {DFF, DM}, str[1] = {DFF * 2}; const cuuint32_t box[2] = {64, 64}; encode(fn, &mg, P.wg, 2, dims, str, box); encode(fn, &mu, P.wu, 2, dims, str, box); }
  { const cuuint64_t dims[2] = {DM, DFF}, str[1] = {DM * 2}; const cuuint32_t box[2] = {64, 64}; encode(fn, &md, P.wd, 2, dims, str, box); }
  cudaFuncSetAttribute(fused_kernel, cudaFuncAttributeMaxDynamicSharedMemorySize, SMEM_BYTES);
  fused_kernel<<<128, 384, SMEM_BYTES, cudaStreamPerThread>>>(mx, mg, mu, md, P);
}
```

```cpp
#include <cuda_runtime.h>
#include <cuda_bf16.h>
#include <cuda.h>
#include <stdint.h>

#define KV_LEAD 5
#define D_KV 6
#define D_WO 3
#define D_T0 5
#define PF_AHEAD 3
#define CH_LAST 3
#define MC 1
#define MAP 5
#define N_WO 12
#define DBG_PS 2
#define SMALLPOS 1
#define Q_SPLIT 2
#define N_UP 26
#define CLR_NS 0
#define TIMING 0

namespace {

constexpr int SEQ = 2048, DM = 576, DFF = 4608;
constexpr uint32_t SB = 1024;
constexpr uint32_t SLOT = 16384;
constexpr uint32_t PSLOT = 13824;
constexpr uint32_t BARS = SB + 14 * SLOT;
constexpr int SMEM_BYTES = 14 * SLOT + 256 + 2560;
__host__ __device__ constexpr uint32_t slot_addr(int s) { return SB + s * SLOT; }
__host__ __device__ constexpr uint32_t bar_full(int s) { return BARS + 8 * s; }
__host__ __device__ constexpr uint32_t bar_empty(int s) { return BARS + 128 + 8 * s; }
enum { NB_ORD0 = 1, NB_ORD1 = 2, NB_WG = 3  , NB_HALO = 5  , NB_FREE = 7  , NB_PUB = 9  , NB_ORD2 = 13 };
constexpr uint32_t SM_EPOCH = BARS + 120;
__host__ __device__ constexpr uint32_t ytail(uint32_t k) { return k < 3 ? slot_addr(9) + PSLOT + k * SLOT : BARS + 256; }
constexpr uint32_t KSTG = 9 * 1152;

constexpr uint32_t TILE = 36 * 2048;
constexpr uint32_t OFF_X1 = 0  , OFF_O = TILE, OFF_X2 = 2 * TILE, OFF_ST = 4 * TILE  ;
constexpr uint32_t PSRC = 2 * 16384 + 7 * 1024;
constexpr uint32_t OFF_P = OFF_ST + 3 * 4096, OFF_HALO = OFF_P + 8 * PSRC  , OFF_HINT = OFF_HALO + 2 * 8 * 3072  ,
                   OFF_H = OFF_HINT + 16 * 128  , STRM = OFF_H + 8 * 24576;
constexpr uint32_t OFF_WPACK = 32 * STRM, OFF_FLAGS = OFF_WPACK + 8 * 24 * PSLOT;
__device__ __align__(1024) uint8_t g_scr[OFF_FLAGS + (8 + 64 + 128) * 32];

__device__ __forceinline__ uint32_t smem_u32(const void* p) { return (uint32_t)__cvta_generic_to_shared(p); }
extern __shared__ __align__(1024) uint8_t smem_raw[];
__device__ __forceinline__ uint32_t win() { return MC ? (blockIdx.x & 1) << 24 : 0; }
#define SA(A, W) ".reg .u32 sa;\nadd.u32 sa, " A ", " W ";\n"
__device__ __forceinline__ void mbar_init(uint32_t bar, uint32_t cnt) { asm volatile("{\n" SA("%0", "%2") "mbarrier.init.shared::cta.b64 [sa], %1;\n}" ::"r"(bar), "r"(cnt), "r"(win())); }
__device__ __forceinline__ void mbar_expect_tx(uint32_t bar, uint32_t bytes) { asm volatile("{\n" SA("%0", "%2") "mbarrier.arrive.expect_tx.shared::cta.b64 _, [sa], %1;\n}" ::"r"(bar), "r"(bytes), "r"(win()) : "memory"); }
__device__ __forceinline__ void mbar_arrive(uint32_t bar) { asm volatile("{\n" SA("%0", "%1") "mbarrier.arrive.shared::cta.b64 _, [sa];\n}" ::"r"(bar), "r"(win()) : "memory"); }
__device__ __forceinline__ uint32_t lds32(uint32_t a) { uint32_t v; asm volatile("{\n" SA("%1", "%2") "ld.shared.u32 %0, [sa];\n}" : "=r"(v) : "r"(a), "r"(win()) : "memory"); return v; }
__device__ __forceinline__ void lds64(uint32_t& x, uint32_t& y, uint32_t a) { asm volatile("{\n" SA("%2", "%3") "ld.shared.v2.u32 {%0,%1}, [sa];\n}" : "=r"(x), "=r"(y) : "r"(a), "r"(win()) : "memory"); }
__device__ __forceinline__ void lds128(uint32_t* v, uint32_t a) {
  asm volatile("{\n" SA("%4", "%5") "ld.shared.v4.u32 {%0,%1,%2,%3}, [sa];\n}" : "=r"(v[0]), "=r"(v[1]), "=r"(v[2]), "=r"(v[3]) : "r"(a), "r"(win()) : "memory");
}
__device__ __forceinline__ void stsm4(uint32_t a, uint32_t x, uint32_t y, uint32_t z, uint32_t w) {
  asm volatile("{\n" SA("%0", "%5") "stmatrix.sync.aligned.m8n8.x4.shared.b16 [sa], {%1,%2,%3,%4};\n}" ::"r"(a), "r"(x), "r"(y), "r"(z), "r"(w), "r"(win()) : "memory");
}
__device__ __forceinline__ void ldsm4(uint32_t* v, uint32_t a) {
  asm volatile("{\n" SA("%4", "%5") "ldmatrix.sync.aligned.m8n8.x4.shared.b16 {%0,%1,%2,%3}, [sa];\n}" : "=r"(v[0]), "=r"(v[1]), "=r"(v[2]), "=r"(v[3]) : "r"(a), "r"(win()) : "memory");
}
__device__ __forceinline__ void ldsm4t(uint32_t* v, uint32_t a) {
  asm volatile("{\n" SA("%4", "%5") "ldmatrix.sync.aligned.m8n8.x4.trans.shared.b16 {%0,%1,%2,%3}, [sa];\n}" : "=r"(v[0]), "=r"(v[1]), "=r"(v[2]), "=r"(v[3]) : "r"(a), "r"(win()) : "memory");
}
__device__ __forceinline__ void sts32(uint32_t a, uint32_t x) { asm volatile("{\n" SA("%0", "%2") "st.shared.u32 [sa], %1;\n}" ::"r"(a), "r"(x), "r"(win()) : "memory"); }
__device__ __forceinline__ void sts64(uint32_t a, uint32_t x, uint32_t y) { asm volatile("{\n" SA("%0", "%3") "st.shared.v2.u32 [sa], {%1,%2};\n}" ::"r"(a), "r"(x), "r"(y), "r"(win()) : "memory"); }
__device__ __forceinline__ void sts128(uint32_t a, uint32_t x, uint32_t y, uint32_t z, uint32_t w) {
  asm volatile("{\n" SA("%0", "%5") "st.shared.v4.u32 [sa], {%1,%2,%3,%4};\n}" ::"r"(a), "r"(x), "r"(y), "r"(z), "r"(w), "r"(win()) : "memory");
}
__device__ __forceinline__ void mbar_wait(uint32_t bar, uint32_t parity) {
  asm volatile("{\n.reg .pred p;\n" SA("%0", "%2") "LAB_WAIT:\nmbarrier.try_wait.parity.shared::cta.b64 p, [sa], %1;\n@!p bra LAB_WAIT;\n}" ::"r"(bar), "r"(parity), "r"(win()) : "memory");
}
__device__ __forceinline__ void timed_wait(uint32_t bar, uint32_t par) {
  asm volatile("{\n.reg .pred p;\n.reg .u64 t0, t1;\nmov.u64 t0, %%globaltimer;\nLAB_WD:\n"
               "mbarrier.try_wait.parity.shared::cta.b64 p, [%0], %1, 100000;\n@p bra LAB_OK;\n"
               "mov.u64 t1, %%globaltimer;\nsub.u64 t1, t1, t0;\nsetp.lt.u64 p, t1, 2000000000;\n@p bra LAB_WD;\ntrap;\nLAB_OK:\n}" ::"r"(bar + win()), "r"(par) : "memory");
}
__device__ __forceinline__ void flag_wait(const unsigned* flag, unsigned target) {
  asm volatile("{\n.reg .pred p;\n.reg .u32 v;\nLAB_WAIT:\nld.acquire.gpu.global.u32 v, [%0];\nsub.u32 v, v, %1;\n"
               "setp.lt.s32 p, v, 0;\nvote.sync.any.pred p, p, 0xffffffff;\n@p nanosleep.u32 100;\n@p bra LAB_WAIT;\n}" ::"l"(flag), "r"(target) : "memory");
}
__device__ __forceinline__ void hint_post(uint8_t* p) {
  __syncwarp();
  asm volatile("{\n.reg .pred p;\nelect.sync _|p, 0xffffffff;\n@p red.relaxed.gpu.global.add.u32 [%0], 1;\n}" ::"l"(p) : "memory");
}
__device__ __forceinline__ void hint_wait(const uint8_t* p, uint32_t target) {
  asm volatile("{\n.reg .pred p;\n.reg .u32 v;\nLAB_WAIT:\nld.relaxed.gpu.global.u32 v, [%0];\nsub.u32 v, v, %1;\n"
               "setp.lt.s32 p, v, 0;\nvote.sync.any.pred p, p, 0xffffffff;\n@p bra LAB_WAIT;\n}" ::"l"(p), "r"(target) : "memory");
}
__device__ __forceinline__ void flag_signal(unsigned* flag) { asm volatile("red.release.gpu.global.add.u32 [%0], 1;" ::"l"(flag) : "memory"); }
struct Rel {
  bool on; uint32_t base;
  __device__ __forceinline__ void operator()(int s) const {
    if (on) {
      if (MC) asm volatile("{\n" SA("%0", "%1") "mbarrier.arrive.shared::cluster.b64 _, [sa];\n}" ::"r"(bar_empty(s)), "r"(base) : "memory");
      else mbar_arrive(bar_empty(s));
    }
  }
};
__device__ __forceinline__ uint32_t cta_window(uint32_t rank) { uint32_t a; asm("mapa.shared::cluster.u32 %0, %1, %2;" : "=r"(a) : "r"(0), "r"(rank)); return a; }
#define ELECT ".reg .pred e;\nelect.sync _|e, 0xffffffff;\n"
__device__ __forceinline__ void w_expect_tx(uint32_t bar, uint32_t bytes) {
  asm volatile("{\n" ELECT "@e mbarrier.arrive.expect_tx.shared::cta.b64 _, [%0], %1;\n}" ::"r"(bar), "r"(bytes) : "memory");
}
__device__ __forceinline__ void w_tma_2d_mc(uint32_t dst, const CUtensorMap* m, int c0, int c1, uint32_t bar) {
  asm volatile("{\n" ELECT "@e cp.async.bulk.tensor.2d.shared::cluster.global.mbarrier::complete_tx::bytes.multicast::cluster [%0], [%1, {%3, %4}], [%2], %5;\n}"
               ::"r"(dst), "l"(m), "r"(bar), "r"(c0), "r"(c1), "h"((uint16_t)3) : "memory");
}
__device__ __forceinline__ void w_bulk_load_mc(uint32_t dst, const void* src, uint32_t bytes, uint32_t bar) {
  asm volatile("{\n" ELECT "@e cp.async.bulk.shared::cluster.global.mbarrier::complete_tx::bytes.multicast::cluster [%0], [%1], %2, [%3], %4;\n}"
               ::"r"(dst), "l"(src), "r"(bytes), "r"(bar), "h"((uint16_t)3) : "memory");
}
__device__ __forceinline__ void w_bulk_load(uint32_t dst, const void* src, uint32_t bytes, uint32_t bar) {
  asm volatile("{\n" ELECT "@e cp.async.bulk.shared::cluster.global.mbarrier::complete_tx::bytes [%0], [%1], %2, [%3];\n}" ::"r"(dst), "l"(src), "r"(bytes), "r"(bar) : "memory");
}
__device__ __forceinline__ void w_l2_prefetch(const void* src, uint32_t bytes) { asm volatile("{\n" ELECT "@e cp.async.bulk.prefetch.L2.global [%0], %1;\n}" ::"l"(src), "r"(bytes) : "memory"); }
__device__ __forceinline__ void w_tma_prefetch(const CUtensorMap* m, int c0, int c1) {
  asm volatile("{\n" ELECT "@e cp.async.bulk.prefetch.tensor.2d.L2.global [%0, {%1, %2}];\n}" ::"l"(m), "r"(c0), "r"(c1) : "memory");
}
__device__ __forceinline__ void tma_3d(uint32_t dst, const CUtensorMap* m, int c0, int c1, int c2, uint32_t bar) {
  asm volatile("cp.async.bulk.tensor.3d.shared::cluster.global.mbarrier::complete_tx::bytes [%0], [%1, {%3, %4, %5}], [%2];"
               ::"r"(dst), "l"(m), "r"(bar), "r"(c0), "r"(c1), "r"(c2) : "memory");
}
__device__ __forceinline__ void wg_fence() { asm volatile("wgmma.fence.sync.aligned;" ::: "memory"); }
__device__ __forceinline__ void wg_commit() { asm volatile("wgmma.commit_group.sync.aligned;" ::: "memory"); }
template <int N> __device__ __forceinline__ void wg_wait() { asm volatile("wgmma.wait_group.sync.aligned %0;" ::"n"(N) : "memory"); }
__device__ __forceinline__ void bar_sync(int id, int n) { asm volatile("bar.sync %0, %1;" ::"r"(id), "r"(n) : "memory"); }
__device__ __forceinline__ void bar_arrive(int id, int n) { asm volatile("bar.arrive %0, %1;" ::"r"(id), "r"(n) : "memory"); }
__device__ __forceinline__ uint32_t pack_bf16(float lo, float hi) { uint32_t r; asm("cvt.rn.bf16x2.f32 %0, %1, %2;" : "=r"(r) : "f"(hi), "f"(lo)); return r; }
__device__ __forceinline__ float bf_lo(uint32_t w) { return __uint_as_float(w << 16); }
__device__ __forceinline__ float bf_hi(uint32_t w) { return __uint_as_float(w & 0xffff0000u); }
__device__ __forceinline__ float bf_round(float x) { return bf_lo(pack_bf16(x, 0.f)); }
__device__ __forceinline__ uint32_t bf2_sub(uint32_t a, uint32_t b) { uint32_t r; asm("sub.rn.bf16x2 %0, %1, %2;" : "=r"(r) : "r"(a), "r"(b)); return r; }
__device__ __forceinline__ uint32_t bf2_add(uint32_t a, uint32_t b) { uint32_t r; asm("add.rn.bf16x2 %0, %1, %2;" : "=r"(r) : "r"(a), "r"(b)); return r; }
#define GADDR(B, O, I) "cvt.u64.u32 ad, " O ";\nadd.u64 ad, ad, " B ";\nadd.u64 ad, ad, " I ";\n"
__device__ __forceinline__ void ld16(uint32_t* v, const uint8_t* ub, uint32_t off, uint32_t imm) {
  asm volatile("{\n.reg .b128 z;\n.reg .b64 x, y, ad;\n" GADDR("%4", "%5", "%6") "ld.relaxed.gpu.global.b128 z, [ad];\n"
               "mov.b128 {x, y}, z;\nmov.b64 {%0,%1}, x;\nmov.b64 {%2,%3}, y;\n}"
               : "=r"(v[0]), "=r"(v[1]), "=r"(v[2]), "=r"(v[3]) : "l"(ub), "r"(off), "l"((uint64_t)imm) : "memory");
}
__device__ __forceinline__ void ld8(uint32_t* v, const uint8_t* ub, uint32_t off, uint32_t imm) {
  asm volatile("{\n.reg .b64 x, ad;\n" GADDR("%2", "%3", "%4") "ld.relaxed.gpu.global.b64 x, [ad];\nmov.b64 {%0,%1}, x;\n}"
               : "=r"(v[0]), "=r"(v[1]) : "l"(ub), "r"(off), "l"((uint64_t)imm) : "memory");
}
__device__ __forceinline__ void st16(uint8_t* ub, uint32_t off, uint32_t imm, uint32_t a, uint32_t b, uint32_t c, uint32_t d) {
  asm volatile("{\n.reg .b128 z;\n.reg .b64 x, y, ad;\n" GADDR("%0", "%1", "%2") "mov.b64 x, {%3,%4};\nmov.b64 y, {%5,%6};\nmov.b128 z, {x, y};\n"
               "st.relaxed.gpu.global.b128 [ad], z;\n}" ::"l"(ub), "r"(off), "l"((uint64_t)imm), "r"(a), "r"(b), "r"(c), "r"(d) : "memory");
}
__device__ __forceinline__ void st8(uint8_t* ub, uint32_t off, uint32_t imm, uint32_t a, uint32_t b) {
  asm volatile("{\n.reg .b64 x, ad;\n" GADDR("%0", "%1", "%2") "mov.b64 x, {%3,%4};\nst.relaxed.gpu.global.b64 [ad], x;\n}"
               ::"l"(ub), "r"(off), "l"((uint64_t)imm), "r"(a), "r"(b) : "memory");
}
__device__ __forceinline__ void send8(uint8_t* ub, uint32_t off, uint32_t imm, uint32_t sm, int i, int j, uint32_t a, uint32_t b) {
  asm volatile("{\n.reg .pred p, q, e;\n.reg .b64 x, ad;\n" SA("%3", "%8") GADDR("%0", "%1", "%2")
               "setp.lt.s32 p, %4, %5;\nsetp.gt.s32 q, %4, %5;\nsetp.eq.s32 e, %4, %5;\nmov.b64 x, {%6,%7};\n"
               "@p st.relaxed.gpu.global.b64 [ad+-1024], x;\n@q st.relaxed.gpu.global.b64 [ad], x;\n@e st.shared.v2.u32 [sa], {%6,%7};\n}"
               ::"l"(ub), "r"(off), "l"((uint64_t)imm), "r"(sm), "r"(i), "r"(j), "r"(a), "r"(b), "r"(win()) : "memory");
}
__device__ __forceinline__ uint4 ldg_line(const void* p) {
  uint4 v; asm volatile("ld.global.nc.L2::128B.v4.u32 {%0,%1,%2,%3}, [%4];" : "=r"(v.x), "=r"(v.y), "=r"(v.z), "=r"(v.w) : "l"(p)); return v;
}
__device__ __forceinline__ void stg4(void* ub, uint32_t off, uint32_t imm, uint32_t v) {
  asm volatile("{\n.reg .b64 ad;\n" GADDR("%0", "%1", "%2") "st.global.u32 [ad], %3;\n}" ::"l"(ub), "r"(off), "l"((uint64_t)imm), "r"(v) : "memory");
}
__device__ __forceinline__ uint32_t tid_() { uint32_t t; asm volatile("mov.u32 %0, %%tid.x;" : "=r"(t)); return t & 127; }
__device__ __forceinline__ uint32_t nz(uint32_t w) { return max(w, 1u); }
__device__ __forceinline__ void mma16816(float (&c)[4], uint32_t a0, uint32_t a1, uint32_t a2, uint32_t a3, uint32_t b0, uint32_t b1) {
  asm("mma.sync.aligned.m16n8k16.row.col.f32.bf16.bf16.f32 {%0,%1,%2,%3}, {%4,%5,%6,%7}, {%8,%9}, {%0,%1,%2,%3};"
               : "+f"(c[0]), "+f"(c[1]), "+f"(c[2]), "+f"(c[3]) : "r"(a0), "r"(a1), "r"(a2), "r"(a3), "r"(b0), "r"(b1));
}
__device__ __forceinline__ void mma1688(float (&c)[4], uint32_t a0, uint32_t a1, uint32_t b0) {
  asm("mma.sync.aligned.m16n8k8.row.col.f32.bf16.bf16.f32 {%0,%1,%2,%3}, {%4,%5}, {%6}, {%0,%1,%2,%3};"
               : "+f"(c[0]), "+f"(c[1]), "+f"(c[2]), "+f"(c[3]) : "r"(a0), "r"(a1), "r"(b0));
}
__device__ __forceinline__ float ex2(float x) { float r; asm("ex2.approx.ftz.f32 %0, %1;" : "=f"(r) : "f"(x)); return r; }
__device__ __forceinline__ float quad_sum(float v) { v += __shfl_xor_sync(0xffffffffu, v, 1); v += __shfl_xor_sync(0xffffffffu, v, 2); return v; }
__device__ __forceinline__ float quad_max(float v) { v = fmaxf(v, __shfl_xor_sync(0xffffffffu, v, 1)); v = fmaxf(v, __shfl_xor_sync(0xffffffffu, v, 2)); return v; }

__device__ __forceinline__ void wgmma_rs_n64(float (&d)[32], uint32_t a0, uint32_t a1, uint32_t a2, uint32_t a3, uint64_t desc, int scale_d) {
  asm volatile("{\n.reg .pred p;\nsetp.ne.b32 p, %37, 0;\n"
    "wgmma.mma_async.sync.aligned.m64n64k16.f32.bf16.bf16 "
    "{%0, %1, %2, %3, %4, %5, %6, %7, %8, %9, %10, %11, %12, %13, %14, %15, %16, %17, %18, %19, %20, %21, %22, %23, %24, %25, %26, %27, %28, %29, %30, %31}, "
    "{%32, %33, %34, %35}, %36, p, 1, 1, 1;\n}\n"
    : "+f"(d[0]), "+f"(d[1]), "+f"(d[2]), "+f"(d[3]), "+f"(d[4]), "+f"(d[5]), "+f"(d[6]), "+f"(d[7]), "+f"(d[8]), "+f"(d[9]), "+f"(d[10]), "+f"(d[11]), "+f"(d[12]), "+f"(d[13]), "+f"(d[14]), "+f"(d[15]), "+f"(d[16]), "+f"(d[17]), "+f"(d[18]), "+f"(d[19]), "+f"(d[20]), "+f"(d[21]), "+f"(d[22]), "+f"(d[23]), "+f"(d[24]), "+f"(d[25]), "+f"(d[26]), "+f"(d[27]), "+f"(d[28]), "+f"(d[29]), "+f"(d[30]), "+f"(d[31])
    : "r"(a0), "r"(a1), "r"(a2), "r"(a3), "l"(desc), "r"(scale_d));
}

__device__ __forceinline__ void wgmma_rs_n72(float (&d)[36], uint32_t a0, uint32_t a1, uint32_t a2, uint32_t a3, uint64_t desc, int scale_d) {
  asm volatile("{\n.reg .pred p;\nsetp.ne.b32 p, %41, 0;\n"
    "wgmma.mma_async.sync.aligned.m64n72k16.f32.bf16.bf16 "
    "{%0, %1, %2, %3, %4, %5, %6, %7, %8, %9, %10, %11, %12, %13, %14, %15, %16, %17, %18, %19, %20, %21, %22, %23, %24, %25, %26, %27, %28, %29, %30, %31, %32, %33, %34, %35}, "
    "{%36, %37, %38, %39}, %40, p, 1, 1, 1;\n}\n"
    : "+f"(d[0]), "+f"(d[1]), "+f"(d[2]), "+f"(d[3]), "+f"(d[4]), "+f"(d[5]), "+f"(d[6]), "+f"(d[7]), "+f"(d[8]), "+f"(d[9]), "+f"(d[10]), "+f"(d[11]), "+f"(d[12]), "+f"(d[13]), "+f"(d[14]), "+f"(d[15]), "+f"(d[16]), "+f"(d[17]), "+f"(d[18]), "+f"(d[19]), "+f"(d[20]), "+f"(d[21]), "+f"(d[22]), "+f"(d[23]), "+f"(d[24]), "+f"(d[25]), "+f"(d[26]), "+f"(d[27]), "+f"(d[28]), "+f"(d[29]), "+f"(d[30]), "+f"(d[31]), "+f"(d[32]), "+f"(d[33]), "+f"(d[34]), "+f"(d[35])
    : "r"(a0), "r"(a1), "r"(a2), "r"(a3), "l"(desc), "r"(scale_d));
}

__device__ __forceinline__ void wgmma_rs_n128(float (&d)[64], uint32_t a0, uint32_t a1, uint32_t a2, uint32_t a3, uint64_t desc, int scale_d) {
  asm volatile("{\n.reg .pred p;\nsetp.ne.b32 p, %69, 0;\n"
    "wgmma.mma_async.sync.aligned.m64n128k16.f32.bf16.bf16 "
    "{%0, %1, %2, %3, %4, %5, %6, %7, %8, %9, %10, %11, %12, %13, %14, %15, %16, %17, %18, %19, %20, %21, %22, %23, %24, %25, %26, %27, %28, %29, %30, %31, %32, %33, %34, %35, %36, %37, %38, %39, %40, %41, %42, %43, %44, %45, %46, %47, %48, %49, %50, %51, %52, %53, %54, %55, %56, %57, %58, %59, %60, %61, %62, %63}, "
    "{%64, %65, %66, %67}, %68, p, 1, 1, 1;\n}\n"
    : "+f"(d[0]), "+f"(d[1]), "+f"(d[2]), "+f"(d[3]), "+f"(d[4]), "+f"(d[5]), "+f"(d[6]), "+f"(d[7]), "+f"(d[8]), "+f"(d[9]), "+f"(d[10]), "+f"(d[11]), "+f"(d[12]), "+f"(d[13]), "+f"(d[14]), "+f"(d[15]), "+f"(d[16]), "+f"(d[17]), "+f"(d[18]), "+f"(d[19]), "+f"(d[20]), "+f"(d[21]), "+f"(d[22]), "+f"(d[23]), "+f"(d[24]), "+f"(d[25]), "+f"(d[26]), "+f"(d[27]), "+f"(d[28]), "+f"(d[29]), "+f"(d[30]), "+f"(d[31]), "+f"(d[32]), "+f"(d[33]), "+f"(d[34]), "+f"(d[35]), "+f"(d[36]), "+f"(d[37]), "+f"(d[38]), "+f"(d[39]), "+f"(d[40]), "+f"(d[41]), "+f"(d[42]), "+f"(d[43]), "+f"(d[44]), "+f"(d[45]), "+f"(d[46]), "+f"(d[47]), "+f"(d[48]), "+f"(d[49]), "+f"(d[50]), "+f"(d[51]), "+f"(d[52]), "+f"(d[53]), "+f"(d[54]), "+f"(d[55]), "+f"(d[56]), "+f"(d[57]), "+f"(d[58]), "+f"(d[59]), "+f"(d[60]), "+f"(d[61]), "+f"(d[62]), "+f"(d[63])
    : "r"(a0), "r"(a1), "r"(a2), "r"(a3), "l"(desc), "r"(scale_d));
}

__device__ __forceinline__ void wgmma_rs_n144(float (&d)[72], uint32_t a0, uint32_t a1, uint32_t a2, uint32_t a3, uint64_t desc, int scale_d) {
  asm volatile("{\n.reg .pred p;\nsetp.ne.b32 p, %77, 0;\n"
    "wgmma.mma_async.sync.aligned.m64n144k16.f32.bf16.bf16 "
    "{%0, %1, %2, %3, %4, %5, %6, %7, %8, %9, %10, %11, %12, %13, %14, %15, %16, %17, %18, %19, %20, %21, %22, %23, %24, %25, %26, %27, %28, %29, %30, %31, %32, %33, %34, %35, %36, %37, %38, %39, %40, %41, %42, %43, %44, %45, %46, %47, %48, %49, %50, %51, %52, %53, %54, %55, %56, %57, %58, %59, %60, %61, %62, %63, %64, %65, %66, %67, %68, %69, %70, %71}, "
    "{%72, %73, %74, %75}, %76, p, 1, 1, 1;\n}\n"
    : "+f"(d[0]), "+f"(d[1]), "+f"(d[2]), "+f"(d[3]), "+f"(d[4]), "+f"(d[5]), "+f"(d[6]), "+f"(d[7]), "+f"(d[8]), "+f"(d[9]), "+f"(d[10]), "+f"(d[11]), "+f"(d[12]), "+f"(d[13]), "+f"(d[14]), "+f"(d[15]), "+f"(d[16]), "+f"(d[17]), "+f"(d[18]), "+f"(d[19]), "+f"(d[20]), "+f"(d[21]), "+f"(d[22]), "+f"(d[23]), "+f"(d[24]), "+f"(d[25]), "+f"(d[26]), "+f"(d[27]), "+f"(d[28]), "+f"(d[29]), "+f"(d[30]), "+f"(d[31]), "+f"(d[32]), "+f"(d[33]), "+f"(d[34]), "+f"(d[35]), "+f"(d[36]), "+f"(d[37]), "+f"(d[38]), "+f"(d[39]), "+f"(d[40]), "+f"(d[41]), "+f"(d[42]), "+f"(d[43]), "+f"(d[44]), "+f"(d[45]), "+f"(d[46]), "+f"(d[47]), "+f"(d[48]), "+f"(d[49]), "+f"(d[50]), "+f"(d[51]), "+f"(d[52]), "+f"(d[53]), "+f"(d[54]), "+f"(d[55]), "+f"(d[56]), "+f"(d[57]), "+f"(d[58]), "+f"(d[59]), "+f"(d[60]), "+f"(d[61]), "+f"(d[62]), "+f"(d[63]), "+f"(d[64]), "+f"(d[65]), "+f"(d[66]), "+f"(d[67]), "+f"(d[68]), "+f"(d[69]), "+f"(d[70]), "+f"(d[71])
    : "r"(a0), "r"(a1), "r"(a2), "r"(a3), "l"(desc), "r"(scale_d));
}

template <int N> struct WG;
template <> struct WG<64>  { static __device__ __forceinline__ void f(float (&d)[32], const uint32_t* a, uint64_t ds, int s) { wgmma_rs_n64(d, a[0], a[1], a[2], a[3], ds, s); } };
template <> struct WG<72>  { static __device__ __forceinline__ void f(float (&d)[36], const uint32_t* a, uint64_t ds, int s) { wgmma_rs_n72(d, a[0], a[1], a[2], a[3], ds, s); } };
template <> struct WG<128> { static __device__ __forceinline__ void f(float (&d)[64], const uint32_t* a, uint64_t ds, int s) { wgmma_rs_n128(d, a[0], a[1], a[2], a[3], ds, s); } };
template <> struct WG<144> { static __device__ __forceinline__ void f(float (&d)[72], const uint32_t* a, uint64_t ds, int s) { wgmma_rs_n144(d, a[0], a[1], a[2], a[3], ds, s); } };

constexpr uint64_t DESC_SW128 = ((uint64_t)(8192 >> 4) << 16) | ((uint64_t)(1024 >> 4) << 32) | (1ull << 62);
constexpr uint64_t DESC_KV = ((uint64_t)(128 >> 4) << 16) | ((uint64_t)(768 >> 4) << 32);
constexpr uint64_t DESC_Q = ((uint64_t)(128 >> 4) << 16) | ((uint64_t)(1536 >> 4) << 32);

template <int V> struct IntC { static constexpr int value = V; };
enum { PS_KV, PS_Q, PS_WO, PS_FF, PS_FFA   };
template <int PS> __host__ __device__ constexpr int pass_slot(int i) {
  return PS == PS_KV ? (i < 3 ? 9 + i : i - 3) : PS == PS_WO ? 6 + i : i;
}

__device__ __forceinline__ void load_frag(uint32_t (&a)[144], int i, const uint8_t* sb, uint32_t uo, uint32_t t) {
  if (i < 32) ld16(&a[4 * i], sb, uo + t * 16, i * 2048);
  else { ld8(&a[4 * i], sb, uo + t * 8, i * 2048); ld8(&a[4 * i + 2], sb, uo + t * 8, i * 2048 + 1024); }
}
__device__ __forceinline__ void store_own(const uint32_t (&y)[18], uint8_t* sb, uint32_t uo, int j, uint32_t t) {
#pragma unroll
  for (int i = 0; i < 4; i++) st16(sb, uo + j * 8192 + t * 16, i * 2048, nz(y[4 * i]), y[4 * i + 1], y[4 * i + 2], y[4 * i + 3]);
  st8(sb, uo + j * 1024 + t * 8, 65536, nz(y[16]), y[17]);
}
__device__ __forceinline__ void load_own(uint32_t* y, const uint8_t* sb, uint32_t uo, int j) {
  const uint32_t t = tid_();
#pragma unroll
  for (int i = 0; i < 4; i++) ld16(&y[4 * i], sb, uo + j * 8192 + t * 16, i * 2048);
  ld8(&y[16], sb, uo + j * 1024 + t * 8, 65536);
}

struct NoTail { __device__ __forceinline__ void operator()() const {} };
template <int N, int PS, int KPS, int KSTEP, int CHK, bool SUB, bool HREL = false, class Tail = NoTail>
__device__ __forceinline__ void mma_pass(float (&acc)[N / 2], uint32_t (&a)[144], uint64_t desc, uint32_t par, const Rel& rel, int bar_id,
                                         const uint8_t* sb = nullptr, uint32_t uo = 0, uint32_t flag = 0, uint32_t m0 = 0, uint32_t m1 = 0, uint32_t park = 0, Tail tail = Tail()) {
  constexpr int NS = 36 / KPS;
  auto check = [&](int lo, int hi, uint32_t m0_) {
    while (true) {
      uint32_t m = m0_;
#pragma unroll
      for (int i = hi - 1; i >= lo; i--) m = min(m, i < 32 ? a[4 * i] : min(a[4 * i], a[4 * i + 2]));
      if (!__any_sync(0xffffffffu, (m | flag) == 0)) break;
      const uint32_t t = tid_();
#pragma unroll
      for (int i = lo; i < hi; i++) load_frag(a, i, sb, uo, t);
    }
  };
#pragma unroll
  for (int s = 0; s < NS; s++) {
    const int sl = pass_slot<PS>(s);
    if (CHK && s == 0 && !SUB) check(0, CHK * KPS, ~0u);
    if (CHK && s == CHK) check(CHK * KPS, 36, lds32(SM_EPOCH) | 1);
    if (SUB) {
#pragma unroll
      for (int i = s * KPS * 4; i < (s + 1) * KPS * 4; i += 2) { a[i] = bf2_sub(a[i], m0); a[i + 1] = bf2_sub(a[i + 1], m1); }
    }
    if (PS == PS_Q && s == Q_SPLIT && flag) bar_sync(NB_ORD2, 256);
    if (PS == PS_KV && s == 0) sts128(park + tid_() * 16, a[0], a[1], a[2], a[3]);
    mbar_wait(bar_full(sl), sl < 9 ? par : par ^ 1);
    wg_fence();
#pragma unroll
    for (int kk = 0; kk < KPS; kk++)
      WG<N>::f(acc, &a[(s * KPS + kk) * 4], desc + ((slot_addr(sl) + kk * KSTEP) >> 4), (s | kk) || PS == PS_FFA);
    wg_commit();
    if (CHK && s < 2 && N_UP < 36 && !flag) {
      const uint32_t t = tid_();
#pragma unroll
      for (int i = s ? (N_UP + 36) / 2 : N_UP; i < (s ? 36 : (N_UP + 36) / 2); i++) load_frag(a, i, sb, uo, t);
    }
    if (s == (PS == PS_KV ? KV_LEAD : NS - 1) && bar_id >= 0) bar_arrive(bar_id, 256);
    if (s > 0) {
      wg_wait<1>();
      if (!(PS == PS_WO && s > 3)) rel(pass_slot<PS>(s - 1));
    }
    if (HREL && s == 3 && flag) {
#pragma unroll
      for (int i = 0; i < 12; i++) ld16(&a[4 * i], sb, uo, i * 2048);
    }
  }
  tail();
  wg_wait<0>();
  if (PS != PS_WO) rel(pass_slot<PS>(NS - 1));
}

template <int NF, int N0 = 0> __device__ __forceinline__ void load_frags(uint32_t (&a)[144], const uint8_t* sb, uint32_t uo, uint32_t t) {
#pragma unroll
  for (int i = N0; i < NF; i++) load_frag(a, i, sb, uo, t);
}
__device__ __forceinline__ void ln_scalars(float s1, float s2, uint32_t& m, float& var, uint32_t zero) {
  const float mean = s1 * (1.f / DM);
  var = s2 * (1.f / DM) - mean * mean;
  m = pack_bf16(mean, mean) ^ (__float_as_uint(var) & zero);
}
__device__ __forceinline__ float ln_rstd(float var, float after, uint32_t zero) {
  var = __uint_as_float(__float_as_uint(var) ^ (__float_as_uint(after) & zero));
  float sd, r;
  asm("sqrt.approx.ftz.f32 %0, %1;" : "=f"(sd) : "f"(bf_round(bf_round(fmaxf(var, 0.f)) + 1e-5f)));
  asm("rcp.approx.ftz.f32 %0, %1;" : "=f"(r) : "f"(bf_round(sd)));
  return r;
}
template <int NF> __device__ __forceinline__ void gather_ln(uint32_t (&a)[144], const uint8_t* sb, uint32_t uo, uint32_t sto,
                                          uint32_t& m0, uint32_t& m1, float& r0, float& r1, uint32_t zero) {
  uint32_t u[32];
  const uint32_t t = tid_(), so = sto + (t >> 5) * 1024 + (t & 28) * 4;
#pragma unroll
  for (int i = 0; i < 8; i++) ld16(&u[4 * i], sb, so, OFF_ST + i * 128);
  load_frags<N_UP>(a, sb, uo, t);
  while (true) {
    uint32_t m = a[4 * NF - 4];
#pragma unroll
    for (int i = NF - 2; i >= 0; i--) m = min(m, a[4 * i]);
#pragma unroll
    for (int i = 0; i < 8; i++) m = min(m, u[4 * i]);
    if (!__any_sync(0xffffffffu, m == 0)) break;
#pragma unroll
    for (int i = 0; i < 8; i++) ld16(&u[4 * i], sb, so, OFF_ST + i * 128);
    load_frags<NF>(a, sb, uo, t);
  }
  float v[4];
#pragma unroll
  for (int k = 0; k < 4; k++)
    v[k] = ((__uint_as_float(u[k]) + __uint_as_float(u[4 + k])) + (__uint_as_float(u[8 + k]) + __uint_as_float(u[12 + k]))) +
           ((__uint_as_float(u[16 + k]) + __uint_as_float(u[20 + k])) + (__uint_as_float(u[24 + k]) + __uint_as_float(u[28 + k])));
  ln_scalars(v[1], v[0], m0, r0, zero); ln_scalars(v[3], v[2], m1, r1, zero);
}
struct Stats {
  float s[4] = {0, 0, 0, 0}, d0[4] = {0, 0, 0, 0}, d1[4] = {0, 0, 0, 0};
  __device__ __forceinline__ void add16(const uint32_t* f) {
    mma16816(s, f[0], f[1], f[2], f[3], 0x3f803f80u, 0x3f803f80u);
    mma1688(d0, f[0], f[1], f[0]); mma1688(d1, f[0], f[1], f[1]);
    mma1688(d0, f[2], f[3], f[2]); mma1688(d1, f[2], f[3], f[3]);
  }
  __device__ __forceinline__ float sq0(int g) const { return (g & 1) ? d0[1] : d0[0]; }
  __device__ __forceinline__ float sq1(int g) const { return (g & 1) ? d1[3] : d1[2]; }
};
struct RowStats {
  float s[4] = {0, 0, 0, 0}, u[4] = {0, 0, 0, 0};
  template <int N> __device__ __forceinline__ void add(const uint32_t* y) {
#pragma unroll
    for (int i = 0; i < N; i++) {
      const float lo = bf_lo(y[i]), hi = bf_hi(y[i]);
      const int r = (i & 1) * 2;
      s[r] = fmaf(lo, lo, s[r]); u[r] = fmaf(hi, hi, u[r]); s[r + 1] += lo; u[r + 1] += hi;
    }
  }
  __device__ __forceinline__ uint32_t fold() {
    uint32_t x = 0;
#pragma unroll
    for (int i = 0; i < 4; i++) { s[i] += u[i]; u[i] = 0; x |= __float_as_uint(s[i]); }
    return x;
  }
  __device__ __forceinline__ void store(uint8_t* sb, uint32_t sto, uint32_t t) {
    fold();
#pragma unroll
    for (int i = 0; i < 4; i++) s[i] += __shfl_xor_sync(0xffffffffu, s[i], 1);
#pragma unroll
    for (int i = 0; i < 4; i++) s[i] += __shfl_xor_sync(0xffffffffu, s[i], 2);
    if ((t & 3) == 0) st16(sb, sto + (t >> 5) * 1024 + (t & 28) * 4, OFF_ST, __float_as_uint(s[0]) | 1u, __float_as_uint(s[1]), __float_as_uint(s[2]), __float_as_uint(s[3]));
  }
};
template <bool SET> __device__ __forceinline__ void add_piece(float* acc, uint32_t sm) {
#pragma unroll
  for (int i = 0; i < 4; i++) {
    uint32_t v[4];
    lds128(v, sm + i * 2048);
#pragma unroll
    for (int k = 0; k < 4; k++) {
      acc[8 * i + 2 * k] = SET ? bf_lo(v[k]) : acc[8 * i + 2 * k] + bf_lo(v[k]);
      acc[8 * i + 2 * k + 1] = SET ? bf_hi(v[k]) : acc[8 * i + 2 * k + 1] + bf_hi(v[k]);
    }
  }
}

#define TS(i) do {} while (0)
#define TSP(i) do {} while (0)
#define TSH(i) do {} while (0)

__host__ __device__ constexpr int cl_grp(int c) { return c < 4 ? 8 + SMALLPOS : c < 36 ? (c - 4) & 7 : 8 + (c - 36) % 7 + ((c - 36) % 7 >= SMALLPOS); }
__host__ __device__ constexpr int cl_mem(int c) { return c < 4 ? c : c < 36 ? (c - 4) >> 3 : (c - 36) / 7; }
__host__ __device__ constexpr int role_j(int c) {
  return MAP == 0 ? (MC ? (c >> 1) & 7 : c & 7) : MAP == 1 ? c >> 4 : MAP == 2 ? ((c >> 6) << 2) | ((c >> 1) & 3)
       : MAP == 3 ? ((c >> 5) << 1) | ((c >> 2) & 1) : MAP == 4 ? ((c >> 3) & 3) * 2 + ((c >> 2) & 1)
       : MAP == 5 ? (cl_grp(c >> 1) >> 3) * 4 + cl_mem(c >> 1) : MAP == 6 ? (cl_grp(c >> 1) >> 2) * 2 + (cl_mem(c >> 1) & 1)
       : ((cl_grp(c >> 1) >> 1) & 3) * 2 + (cl_mem(c >> 1) & 1);
}
__host__ __device__ constexpr int role_rb(int c) {
  return MAP == 0 ? (MC ? (c >> 4) * 2 + (c & 1) : c >> 3) : MAP == 1 ? c & 15 : MAP == 2 ? ((c >> 3) & 7) * 2 + (c & 1)
       : MAP == 3 ? ((c >> 3) & 3) * 4 + (c & 3) : MAP == 4 ? (c >> 5) * 4 + (c & 3)
       : MAP == 5 ? (cl_grp(c >> 1) & 7) * 2 + (c & 1) : MAP == 6 ? (cl_grp(c >> 1) & 3) * 4 + (cl_mem(c >> 1) >> 1) * 2 + (c & 1)
       : ((cl_grp(c >> 1) >> 3) * 2 + (cl_grp(c >> 1) & 1)) * 4 + (cl_mem(c >> 1) >> 1) * 2 + (c & 1);
}

__device__ __forceinline__ uint32_t row_off(int rb, int wg, uint32_t t) { return (rb * 128 + wg + ((t >> 5) * 16 + (t & 15)) * 2) * (2 * DM); }

__device__ __forceinline__ const __nv_bfloat16* wo_src(const __nv_bfloat16* wo, int k, int u, int j) {
  const int ko = k < 512 ? (k >> 6) * 72 + (k & 63) : ((k >> 3) & 7) * 72 + 64 + (k & 7);
  return wo + ko * 576 + (u < 8 ? j * 64 + u * 8 : 512 + j * 8);
}

struct Params {
  const __nv_bfloat16 *x, *wqkv, *wo, *wg, *wu, *wd;
  __nv_bfloat16* out;
  uint8_t* scr;
  uint8_t* times;
  unsigned zero;
};

__cluster_dims__(2, 1, 1)
__global__ void __launch_bounds__(384, 1)
fused_kernel(const __grid_constant__ CUtensorMap map_x, const __grid_constant__ CUtensorMap map_wg,
             const __grid_constant__ CUtensorMap map_wu, const __grid_constant__ CUtensorMap map_wd, const Params P) {
  const int wg = __shfl_sync(0xffffffffu, threadIdx.x >> 7, 0);
  const int cta = blockIdx.x, rank = MC ? cta & 1 : 0, j = role_j(cta), rb = role_rb(cta);
  const uint32_t own = win();
  unsigned* const flags = (unsigned*)(P.scr + OFF_FLAGS);
  if (__shfl_sync(0xffffffffu, threadIdx.x >> 5, 0) == 11) {
    if (threadIdx.x == 352) {
#pragma unroll
      for (int i = 0; i < 14; i++) { mbar_init(bar_full(i), 1); mbar_init(bar_empty(i), MC && i < 12 ? 4 : 2); }
      mbar_init(bar_full(14), 1); mbar_init(bar_empty(14), 1);
      asm volatile("fence.mbarrier_init.release.cluster;" ::: "memory");
      if (smem_u32(smem_raw) != own + SB) asm volatile("trap;");
    }
    __syncwarp();
    bar_arrive(0, 384);
    if (MC) asm volatile("barrier.cluster.arrive.relaxed.aligned;" ::: "memory");
    if (threadIdx.x == 352) {
#pragma unroll 1
      for (int c = 0; c < 9; c++) {
        mbar_expect_tx(bar_full(c), SLOT);
        tma_3d(own + slot_addr(c), &map_x, c * 64, rb * 64, 0, own + bar_full(c));
      }
    }
  } else {
    const bool on = threadIdx.x < 324;
    const int k = rb * 36 + (on ? threadIdx.x / 36 : 0) * 4 + (threadIdx.x & 3), u = (threadIdx.x % 36) >> 2;
    const uint4* s = (const uint4*)(P.wqkv + k * 1728 + j * 72 + u * 8);
    const uint4 vk = ldg_line(s + 72), vv = ldg_line(s + 144);
    const unsigned ep0 = *(volatile unsigned*)&flags[(72 + cta) * 8];
    if (MC) asm volatile("barrier.cluster.arrive.relaxed.aligned;" ::: "memory");
    bar_sync(0, 384);
    uint8_t* d = P.scr + OFF_WPACK + j * 24 * PSLOT;
    if (on) {
      const uint32_t dkv = (k / 48) * PSLOT + u * 768 + (k % 48) * 16;
      st16(d, dkv, 0, vk.x, vk.y, vk.z, vk.w);
      st16(d, dkv, 9 * 768, vv.x, vv.y, vv.z, vv.w);
    }
    asm volatile("fence.proxy.async.global;" ::: "memory");
    bar_arrive(NB_PUB + 3, 384);
    if (threadIdx.x == 351) sts32(SM_EPOCH, ep0);
    if (wg == 2) bar_sync(NB_PUB + 1, 96);
  }
  __syncwarp();
  if (MC) asm volatile("barrier.cluster.wait.acquire.aligned;" ::: "memory");

  if (wg == 2) {
    asm volatile("setmaxnreg.dec.sync.aligned.u32 24;");
    const int pw = __shfl_sync(0xffffffffu, (threadIdx.x >> 5) & 3, 0), lane = threadIdx.x & 31;
    auto tile_col = [](int t, int h, int j) { return t < 9 ? j * 576 + t * 64 : (t == 9 && h) ? 512 : ((j + ((h ? 0x05760 : 0x04123) >> (4 * (t - 9)))) & 7) * 64; };
    auto prefetch_tile = [&](int t) {
#pragma unroll 1
      for (int b = rb; b < 18; b += 16) {
        const int h = b & 1, k = b >> 1;
        if (t < 9) w_tma_prefetch(h ? &map_wu : &map_wg, tile_col(t, h, j), k * 64);
        else if (t != 13 || !h) w_tma_prefetch(&map_wd, tile_col(t, h, j), j * 576 + k * 64);
      }
    };
    if (pw == 0) {
      {
        flag_wait(&flags[j * 8], (lds32(SM_EPOCH) + 1) * 16);
        TSP(7);
        asm volatile("fence.proxy.async.global;" ::: "memory");
        const uint8_t* wp = P.scr + OFF_WPACK + j * 24 * PSLOT;
        wp += rank * (PSLOT / 2);
        auto packed = [&](int sl, uint32_t par, int f) {
          mbar_wait(bar_empty(0) + sl * 8, par);
          w_bulk_load_mc(own + SB + rank * (PSLOT / 2) + sl * SLOT, wp + f * PSLOT, PSLOT / 2, own + bar_full(0) + sl * 8);
          w_expect_tx(own + bar_full(0) + sl * 8, PSLOT);
        };
        const uint32_t half = own + SB + rank * 8192;
#pragma unroll 1
        for (int L = 0; L < 2; L++) {
#pragma unroll 1
          for (int s = L ? 0 : -3; s < 21; s++) {
            if (s == 9 && L == 0) { flag_wait(&flags[(56 + j) * 8], (lds32(SM_EPOCH) + 1) * 16); asm volatile("fence.proxy.async.global;" ::: "memory"); }
            packed(s < 0 ? s + 12 : s < 9 ? s : s - 9, s < 0 || (s >= 9 && s < 18), s + 3);
          }
#pragma unroll 1
          for (int t = 0; t < 14; t++) {
            if (L * 14 + t + PF_AHEAD < 28) prefetch_tile((t + PF_AHEAD) % 14);
            const CUtensorMap* mp = t >= 9 ? &map_wd : rank ? &map_wu : &map_wg;
            const bool nar = t == 13;
            const int col = tile_col(t, nar ? 0 : rank, j);
            const uint32_t dst = nar ? own + SB : half, bytes = nar ? 8192 : SLOT;
            const int ra = t < 9 ? 0 : j * 576 + 320, rbs = t < 9 ? 0 : j * 576 - 192, rc = t < 9 ? 0 : j * 576;
#pragma unroll
            for (int k = 0; k < 9; k++) {
              mbar_wait(bar_empty(k), t & 1);
              if (!nar || rank == (k & 1)) w_tma_2d_mc(dst + k * SLOT, mp, col, (k < 3 ? ra : k < 8 ? rbs : rc) + k * 64, own + bar_full(k));
              w_expect_tx(own + bar_full(k), bytes);
            }
            if (t == 10 && L == 0) {
              w_l2_prefetch(P.scr + OFF_WPACK + j * 24 * PSLOT + rb * (24 * PSLOT / 16), 24 * PSLOT / 16);
#pragma unroll 1
              for (int s = 0; s < 3; s++) packed(9 + s, 1, s);
            }
          }
        }
        flags[(72 + cta) * 8] = lds32(SM_EPOCH) + 1;
      }
    } else if (pw < 3) {
      const int hw = pw - 1;
      const uint32_t ep = __shfl_sync(0xffffffffu, lds32(SM_EPOCH), 0);
      uint8_t* const sb = P.scr + (rb * 2 + hw) * STRM;
      const uint32_t xs = slot_addr(12) + hw * SLOT, fb = bar_full(12) + hw * 8;
      uint32_t hph = 0;
#pragma unroll 1
      for (int L = 0; L < 2; L++) {
        const uint32_t tag = ep * 2 + L + 1;
        bar_sync(NB_FREE + hw, 160);
        if (rb > 0) hint_wait(sb + OFF_HINT + 512 + j * 128, tag);
        uint32_t bad;
        do {
          if (rb > 0) {
            w_bulk_load(own + ytail(hw * 2), sb + OFF_HALO + (L * 8 + j) * 3072, 1536, own + bar_full(14) + hw * 128);
            w_bulk_load(own + ytail(hw * 2 + 1), sb + OFF_HALO + (L * 8 + j) * 3072 + 1536, 1536, own + bar_full(14) + hw * 128);
            w_expect_tx(own + bar_full(14) + hw * 128, 3072);
            mbar_wait(bar_full(14) + hw * 128, hph);
            hph ^= 1;
          }
          bad = 0;
#pragma unroll 1
          for (int c = 0; c < 3; c++) {
            uint32_t u[4] = {tag, 0, 0, 0}, v[4] = {tag, 0, 0, 0};
            if (rb > 0) { lds128(u, ytail(hw * 2) + c * 512 + lane * 16); lds128(v, ytail(hw * 2 + 1) + c * 512 + lane * 16); }
            bad |= (u[0] ^ tag) | (v[0] ^ tag);
#pragma unroll
            for (int i = 0; i < 3; i++) { sts32(xs + KSTG + (c * 3 + i) * 128 + lane * 4, u[i + 1]); sts32(xs + (c * 3 + i) * 128 + lane * 4, v[i + 1]); }
          }
        } while (__any_sync(0xffffffffu, bad != 0));
        bar_arrive(NB_HALO + hw, 160);
#pragma unroll 1
        for (int p = 0; p < 4; p++) {
          if (L == 0 && p == 3) flag_wait(flags + (40 + rb) * 8, (ep + 1) * 8);
          bar_sync(NB_FREE + hw, 160);
          TSH(L * 12 + p * 3);
          hint_wait(sb + OFF_HINT + (lane & 3) * 128, (ep * 13 + L * 7 + p + 3) * 8);
          TSH(L * 12 + p * 3 + 1);
          w_bulk_load(own + xs, sb + OFF_P + j * PSRC + (p & 1) * 16384, p ? 16384 : 8192, own + fb);
          if (p == 0) w_bulk_load(own + xs + 8192, sb + OFF_P + j * PSRC + 32768, 7168, own + fb);
          w_expect_tx(own + fb, p ? 16384 : 15360);
          TSH(L * 12 + p * 3 + 2);
        }
      }
    } else {
      auto clear = [&](int t) {
        const uint32_t so = rb * 2 * STRM + (threadIdx.x & 31) * 16;
#pragma unroll 1
        for (int i = 0; i < 18; i++) {
          st16(P.scr, so + t * TILE + j * 9216 + i * 512, 0, 0, 0, 0, 0);
          st16(P.scr, so + t * TILE + j * 9216 + i * 512, STRM, 0, 0, 0, 0);
          __nanosleep(CLR_NS);
        }
        if (t != 1) {
          st16(P.scr, so + (t ? t - 1 : 0) * 4096 + j * 512, OFF_ST, 0, 0, 0, 0);
          st16(P.scr, so + (t ? t - 1 : 0) * 4096 + j * 512, OFF_ST + STRM, 0, 0, 0, 0);
        }
      };
      bar_sync(NB_PUB + 3, 384);
      if (lane == 0) flag_signal(&flags[j * 8]);
      TSP(5);
      bar_sync(NB_PUB + 2, 288);
      if (lane == 0) flag_signal(&flags[(56 + j) * 8]);
      TSP(4);
      __syncwarp();
#pragma unroll 1
      for (int t = 0; t < PF_AHEAD; t++) prefetch_tile(t);
#pragma unroll 1
      for (int L = 0; L < 2; L++) {
        timed_wait(bar_empty(13), L);
#pragma unroll 1
        for (int t = L ^ 1; t < 4 - 2 * L; t++) clear(t);
        __syncwarp();
        if (lane == 0 && L == 0) flag_signal(flags + (40 + rb) * 8);
      }
      timed_wait(bar_empty(12), 0);
      if (MC) asm volatile("barrier.cluster.arrive.relaxed.aligned;\nbarrier.cluster.wait.aligned;" ::: "memory");
    }
  } else {
    asm volatile("setmaxnreg.inc.sync.aligned.u32 240;");
    const int w = __shfl_sync(0xffffffffu, (threadIdx.x >> 5) & 3, 0);
    const bool leader = (threadIdx.x & 127) == 0;
    const Rel rel{MC ? (threadIdx.x & 95) == 0 : leader, MC ? cta_window(w & 1) : 0};
    uint8_t* const sb = P.scr + (rb * 2 + wg) * STRM;
    uint8_t* const hint = sb + OFF_HINT + w * 128;
    auto hint_target = [](int e) { return (lds32(SM_EPOCH) * 13 + e + 1) * 8; };
    TS(0);
    uint32_t a[144];
#pragma unroll 1
    for (int L = 0; L < 2; L++) {
      uint32_t m0, m1; float r0, r1;
      if (L == 0) {
        Stats st;
        const int lane = tid_() & 31, g = lane >> 2;
        const int row = w * 16 + (lane & 15);
        const uint32_t ra = SB + wg * 8192 + row * 128;
        const uint32_t pt = tid_(), pu = (pt % 36) >> 2, pk = rb * 36 + (pt < 108 ? pt / 36 : 0) * 4 + (pt & 3);
        uint4 pv[3];
#pragma unroll
        for (int i = 0; i < 3; i++) pv[i] = ldg_line(wg ? wo_src(P.wo, pk + i * 12, pu, j) : P.wqkv + (pk + i * 12) * 1728 + j * 72 + pu * 8);
#pragma unroll
        for (int c = 0; c < 9; c++) {
          mbar_wait(bar_full(c), 0);
          if (c == 0) TS(60); if (c == 8) TS(62);
#pragma unroll
          for (int kk = 0; kk < 4; kk++) ldsm4(&a[c * 16 + kk * 4], ra + (((kk * 2 + (lane >> 4)) ^ (row & 7)) << 4) + c * SLOT);
          if (c == 8) {
            uint32_t y[18], z[4];
#pragma unroll
            for (int i = 0; i < 4; i++) ldsm4(&y[4 * i], ra + (((i * 2 + (lane >> 4)) ^ (row & 7)) << 4) + j * SLOT);
            ldsm4(z, ra + ((j ^ (row & 7)) << 4) + 8 * SLOT);
            y[16] = z[0]; y[17] = z[1];
            bar_sync(NB_WG + wg, 128);
#pragma unroll
            for (int i = 0; i < 9; i++) rel(i);
            if (pt < 108) {
#pragma unroll
              for (int i = 0; i < 3; i++) {
                const uint32_t k = pk + i * 12;
                st16(P.scr, (j * 24 + wg * 6 + k / 96) * PSLOT + pu * 1536 + (k % 96) * 16, OFF_WPACK + 12 * PSLOT, pv[i].x, pv[i].y, pv[i].z, pv[i].w);
              }
            }
            asm volatile("fence.proxy.async.global;" ::: "memory");
            bar_arrive(NB_PUB + 2, 288);
            store_own(y, sb, OFF_X2, j, tid_());
          }
#pragma unroll
          for (int kk = 0; kk < 4; kk++) st.add16(&a[c * 16 + kk * 4]);
        }
        const int dl = (lane & ~3) | (g >> 1);
        ln_scalars(st.s[0], __shfl_sync(0xffffffffu, st.sq0(g), dl), m0, r0, P.zero);
        ln_scalars(st.s[2], __shfl_sync(0xffffffffu, st.sq1(g), dl), m1, r1, P.zero);
      } else {
#pragma unroll
        for (int i = 4 * N_UP; i < 144; i++) a[i] = 0;
        hint_wait(hint, hint_target(6));
        TS(61);
        gather_ln<3 * D_KV>(a, sb, OFF_X2, 8192, m0, m1, r0, r1, P.zero);
      }
      TS(1 + L * 20);
      uint32_t kf[18], qf[18];
      {
        float acc[72];
        if (wg == 1) bar_sync(NB_ORD1, 256);
        mma_pass<144, PS_KV, 3, 256, D_KV, true>(acc, a, DESC_KV, 1, rel, wg == 0 ? NB_ORD1 : -1, sb, OFF_X2, L ^ 1, m0, m1, ytail(wg * 2));
        r0 = ln_rstd(r0, acc[0], P.zero); r1 = ln_rstd(r1, acc[0], P.zero);
        uint32_t vf[18];
#pragma unroll
        for (int c = 0; c < 9; c++) {
          kf[2 * c] = pack_bf16(acc[4 * c] * r0, acc[4 * c + 1] * r0);
          kf[2 * c + 1] = pack_bf16(acc[4 * c + 2] * r1, acc[4 * c + 3] * r1);
          vf[c] = pack_bf16(acc[36 + 4 * c] * r0, acc[36 + 4 * c + 1] * r0);
          vf[9 + c] = pack_bf16(acc[36 + 4 * c + 2] * r1, acc[36 + 4 * c + 3] * r1);
        }
        TS(2 + L * 20);
        const uint32_t l16 = (tid_() & 31) * 16, xs = slot_addr(12) + wg * SLOT + w * 1152;
#pragma unroll
        for (int i = 0; i < 4; i++) stsm4(xs + w * 1152 + 1152 + i * 512 + l16, vf[4 * i], vf[4 * i + 1], vf[4 * i + 2], vf[4 * i + 3]);
        sts32(xs + w * 1152 + 1152 + 2048 + l16 / 4, vf[16]); sts32(xs + w * 1152 + 1152 + 2176 + l16 / 4, vf[17]);
        if (w < 3) {
          stsm4(xs + KSTG + 1152 + l16, kf[1], kf[3], kf[5], kf[7]);
          stsm4(xs + KSTG + 1152 + 512 + l16, kf[9], kf[11], kf[13], kf[15]);
          sts32(xs + KSTG + 1152 + 1024 + l16 / 4, kf[17]);
        } else if (rb < 15) {
          const uint32_t tag = lds32(SM_EPOCH) * 2 + L + 1;
          const uint32_t ho = l16 + (L * 8 + j) * 3072;
#pragma unroll
          for (int c = 0; c < 3; c++) {
            st16(sb, ho, 2 * STRM + OFF_HALO + c * 512, tag, kf[6 * c + 1], kf[6 * c + 3], kf[6 * c + 5]);
            st16(sb, ho, 2 * STRM + OFF_HALO + 1536 + c * 512, tag, vf[9 + 3 * c], vf[10 + 3 * c], vf[11 + 3 * c]);
          }
          hint_post(sb + 2 * STRM + OFF_HINT + 512 + j * 128);
        }
      }
      lds128(a, ytail(wg * 2) + tid_() * 16);
      bar_arrive(NB_FREE + wg, 160);
      uint32_t kh[12];
      {
        float acc[36];
        if (wg == 1) bar_sync(NB_ORD1, 256);
        mma_pass<72, PS_Q, 6, 256, 0, false, false>(acc, a, DESC_Q, 0, rel, -1, nullptr, 0, wg, 0, 0, 0, [&]() {
          bar_sync(NB_HALO + wg, 160);
#pragma unroll
          for (int i = 0; i < 3; i++) ldsm4(&kh[4 * i], slot_addr(12) + wg * SLOT + w * 640 + tid_() * 16 + KSTG + i * 512);
        });
#pragma unroll
        for (int i = 0; i < 18; i++) qf[i] = pack_bf16(acc[2 * i], acc[2 * i + 1]);
      }
      TS(3 + L * 20);
      uint32_t xr[18];
      {
        const int tid = tid_(), g = (tid >> 2) & 7, q = tid & 3;
        uint32_t vt[28];
#pragma unroll
        for (int i = 0; i < 7; i++) ldsm4t(&vt[4 * i], slot_addr(12) + wg * SLOT + w * 1792 + tid * 16 + i * 512);
        const bool nohalo = (rb == 0 && w == 0);
        const bool le0 = 2 * q <= g, le1 = 2 * q + 1 <= g;
        const uint32_t M = (le0 ? 0xffffu : 0u) | (le1 ? 0xffff0000u : 0u);
        const float sc0 = r0 * (0.23570226039551584f * 1.4426950408889634f), sc1 = r1 * (0.23570226039551584f * 1.4426950408889634f);
        float l[16], t[8];
#pragma unroll
        for (int h = 0; h < 4; h++) {
          const uint32_t qa0 = q >= h ? qf[4 * h] : 0u, qa1 = q >= h ? qf[4 * h + 1] : 0u;
          const uint32_t qc0 = q <= h ? qf[4 * h + 4] : 0u, qc1 = q <= h ? qf[4 * h + 5] : 0u;
          float sm[4] = {0, 0, 0, 0}, s0[4] = {0, 0, 0, 0}, s1[4] = {0, 0, 0, 0};
          mma16816(s0, qa0, qa1, qf[4 * h + 2], qf[4 * h + 3], kf[4 * h], kf[4 * h + 2]);
          mma16816(s1, qa0, qa1, qf[4 * h + 2], qf[4 * h + 3], kf[4 * h + 1], kf[4 * h + 3]);
          mma16816(sm, qa0, qa1, qf[4 * h + 2], qf[4 * h + 3], kh[2 * h], kh[2 * h + 1]);
          mma1688(s0, qc0, qc1, kf[4 * h + 4]);
          mma1688(s1, qc0, qc1, kf[4 * h + 5]);
          mma1688(sm, qc0, qc1, kh[2 * h + 2]);
          if (nohalo) sm[0] = sm[1] = -3e38f;
          l[4 * h] = le0 ? s0[0] : sm[0]; l[4 * h + 1] = le1 ? s0[1] : sm[1];
          l[4 * h + 2] = le0 ? s1[2] : s0[2]; l[4 * h + 3] = le1 ? s1[3] : s0[3];
        }
#pragma unroll
        for (int i = 0; i < 8; i++) t[i] = fmaxf(l[2 * i], l[2 * i + 1]);
        if (wg == 0) {
          uint32_t x = 0;
#pragma unroll
          for (int i = 0; i < 8; i++) x |= __float_as_uint(t[i]);
          bar_arrive(NB_ORD1 + (x & P.zero), 256);
        }
        TS(14 + L * 20);
#pragma unroll
        for (int i = 0; i < 8; i++) t[i] = fmaxf(t[i], __shfl_xor_sync(0xffffffffu, t[i], 1));
#pragma unroll
        for (int i = 0; i < 8; i++) t[i] = fmaxf(t[i], __shfl_xor_sync(0xffffffffu, t[i], 2)) * ((i & 1) ? sc1 : sc0);
#pragma unroll
        for (int i = 0; i < 8; i++) {
          const float sc = (i & 1) ? sc1 : sc0;
          l[2 * i] = ex2(fmaf(l[2 * i], sc, -t[i])); l[2 * i + 1] = ex2(fmaf(l[2 * i + 1], sc, -t[i])); t[i] = l[2 * i] + l[2 * i + 1];
        }
#pragma unroll
        for (int i = 0; i < 8; i++) t[i] += __shfl_xor_sync(0xffffffffu, t[i], 1);
#pragma unroll
        for (int i = 0; i < 8; i++) t[i] += __shfl_xor_sync(0xffffffffu, t[i], 2);
        uint32_t pf[16];
#pragma unroll
        for (int i = 0; i < 8; i++) {
          float r; asm("rcp.approx.ftz.f32 %0, %1;" : "=f"(r) : "f"(t[i]));
          const uint32_t p = pack_bf16(l[2 * i] * r, l[2 * i + 1] * r);
          pf[2 * i] = p & ~M; pf[2 * i + 1] = p & M;
        }
#pragma unroll
        for (int c = 0; c < 9; c++) {
          const int h = c == 8 ? 3 : c >> 1;
          float o[4] = {0, 0, 0, 0};
          mma16816(o, pf[4 * h], 0u, pf[4 * h + 1], pf[4 * h + 2], vt[c], vt[9 + c]);
          mma1688(o, 0u, pf[4 * h + 3], vt[18 + c]);
          if (c == 2 || c == 4 || c == 6) {
            float e[4] = {0, 0, 0, 0};
            mma16816(e, pf[4 * h - 4], 0u, pf[4 * h - 3], pf[4 * h - 2], vt[c], vt[9 + c]);
            mma1688(e, 0u, pf[4 * h - 1], vt[18 + c]);
            if (q < h) { o[0] = e[0]; o[1] = e[1]; o[2] = e[2]; o[3] = e[3]; }
          }
          qf[2 * c] = pack_bf16(o[0], o[1]); qf[2 * c + 1] = pack_bf16(o[2], o[3]);
        }
        {
          uint32_t x = 0;
#pragma unroll
          for (int i = 0; i < 18; i += 2) x |= qf[i];
          bar_arrive((wg ? NB_ORD0 : NB_ORD2) + (x & P.zero), 256);
        }
        store_own(qf, sb, OFF_O, j, tid);
        hint_post(hint);
        load_own(xr, sb, OFF_X2, j);
      }
      TS(4 + L * 20);
      {
        hint_wait(hint, hint_target(L * 7));
        TS(5 + L * 20);
        load_frags<N_WO>(a, sb, OFF_O, tid_());
        float acc[36];
        if (wg == 0) bar_sync(NB_ORD0, 256);
        load_frags<N_UP, N_WO>(a, sb, OFF_O, tid_());
        TS(19 + L * 20);
        mma_pass<72, PS_WO, 6, 256, D_WO, false>(acc, a, DESC_Q, 0, rel, -1, sb, OFF_O);
        TS(6 + L * 20);
#pragma unroll
        for (int c = 0; c < 9; c++) {
          xr[2 * c] = bf2_add(xr[2 * c], pack_bf16(acc[4 * c], acc[4 * c + 1]));
          xr[2 * c + 1] = bf2_add(xr[2 * c + 1], pack_bf16(acc[4 * c + 2], acc[4 * c + 3]));
        }
        store_own(xr, sb, L * 3 * TILE, j, tid_());
        RowStats rs;
        rs.add<18>(xr);
        rs.store(sb, L * 4096 + j * 128, tid_());
        hint_post(hint);
      }
      TS(16 + L * 20);
      hint_wait(hint, hint_target(L * 7 + 1));
      TS(15 + L * 20);
      gather_ln<4 * D_T0>(a, sb, L * 3 * TILE, L * 4096, m0, m1, r0, r1, P.zero);
      TS(7 + L * 20);
      const uint32_t hb = OFF_H + j * 24576;
      {
        float ka0, kb0, kc0, ka1, kb1, kc1;
        float acc[64];
        uint32_t hf[16];
        auto geglu = [&](auto chains, uint32_t hsm) {
          constexpr int CH = decltype(chains)::value & 15;
          float r[32];
#pragma unroll
          for (int e = 0; e < 32; e++) {
            float x = acc[e];
            if (e >= CH) x = __uint_as_float(__float_as_uint(x) ^ (__float_as_uint(r[e - CH]) & P.zero));
            if (decltype(chains)::value > 15 && e < 20) {
              const uint32_t ad = (e < 8 ? slot_addr(12) + e * 2048 + wg * 8192 : slot_addr(7 + (e >> 2)) + (e & 3) * 2048) + hsm;
              lds128(&a[48 + 4 * e], e >= CH ? ad ^ (__float_as_uint(r[e - CH]) & P.zero) : ad);
            }
            const bool hi = e & 2;
            float t = x * fmaf(x * x, hi ? kb1 : kb0, hi ? ka1 : ka0);
            asm("tanh.approx.f32 %0, %0;" : "+f"(t));
            const float u = x * acc[32 + e] * (hi ? kc1 : kc0);
            r[e] = fmaf(u, t, u);
            if (e & 1) hf[e >> 1] = pack_bf16(r[e - 1], r[e]);
          }
        };
        if (wg == 1) bar_sync(NB_ORD1, 256);
        mma_pass<128, PS_FF, 4, 2048, D_T0, true>(acc, a, DESC_SW128, 1, rel, NB_ORD1 - wg, sb, L * 3 * TILE, 0, m0, m1);
        if (tid_() == 0) mbar_arrive(bar_empty(13));
        TS(8 + L * 20);
        r0 = ln_rstd(r0, acc[0], P.zero); r1 = ln_rstd(r1, acc[0], P.zero);
        ka0 = 0.7978845608028654f * r0; kb0 = 0.035677408136300125f * r0 * r0 * r0; kc0 = 0.5f * r0 * r0;
        ka1 = 0.7978845608028654f * r1; kb1 = 0.035677408136300125f * r1 * r1 * r1; kc1 = 0.5f * r1 * r1;
#pragma unroll 1
        for (int t = 0; t < 8; t++) {
          geglu(IntC<2>(), 0);
          const uint32_t t16 = tid_() * 16;
          if (t < 5) {
            const uint32_t d = (t < 2 ? slot_addr(12) + wg * SLOT + t * 8192 : slot_addr(7) + t * SLOT + wg * 8192) + t16;
#pragma unroll
            for (int i = 0; i < 4; i++)
              sts128(d + i * 2048, hf[4 * i], hf[4 * i + 1], hf[4 * i + 2], hf[4 * i + 3]);
            if (t == 4) asm volatile("fence.proxy.async.shared::cta;" ::: "memory");
          } else {
#pragma unroll
            for (int i = 0; i < 4; i++) st16(sb, hb + (t - 5) * 8192 + t16, i * 2048, hf[4 * i], hf[4 * i + 1], hf[4 * i + 2], hf[4 * i + 3]);
          }
          bar_sync(NB_ORD0 + wg, 256);
          mma_pass<128, PS_FF, 4, 2048, 0, false, true>(acc, a, DESC_SW128, t & 1, rel, NB_ORD1 - wg, sb, hb + t16, t == 7);
        }
        TS(9 + L * 20);
        const uint32_t hsm = wg * 8192 + tid_() * 16;
        geglu(IntC<16 + CH_LAST>(), hsm);
#pragma unroll
        for (int i = 0; i < 16; i++) a[128 + i] = hf[i];
      }
      TS(10 + L * 20);
      {
        const uint32_t xs = slot_addr(12) + wg * SLOT;
        auto verify = [&](int p, uint32_t t16) {
          mbar_wait(bar_full(12) + wg * 8, p & 1);
          TS(71 + L * 32 + p * 5);
          const uint32_t ta = p < 2, tb = (p & 1) ? ta : L ^ 1, nb = p ? 4 : 7, sh = p == 0;
          uint32_t m = 0;
#pragma unroll
          for (int s = 0; s < 4; s++) m |= (lds32(xs + s * 2048 + t16) ^ ta) | (lds32(xs + 8192 + ((s * 2048 + t16) >> sh)) ^ tb);
          if (p == 0) {
#pragma unroll
            for (int s = 4; s < 7; s++) m |= lds32(xs + 8192 + s * 1024 + t16 / 2) ^ tb;
          }
          if (__any_sync(0xffffffffu, m & 1)) {
#pragma unroll 1
            for (int s = 0; s < 4 + nb; s++) {
              const bool nar = sh && s >= 4;
              const uint32_t o = nar ? 4096 + s * 1024 + t16 / 2 : s * 2048 + t16;
              uint32_t v[4] = {0, 0, 0, 0};
              do {
                if (nar) ld8(v, sb, j * PSRC + o, OFF_P + 32768 - 8192);
                else ld16(v, sb, j * PSRC + (p & 1) * 16384 + o, OFF_P);
              } while (__any_sync(0xffffffffu, (v[0] ^ (s < 4 ? ta : tb)) & 1));
              sts64(xs + o, v[0], v[1]);
              if (!nar) sts64(xs + o + 8, v[2], v[3]);
            }
            asm volatile("fence.proxy.async.shared::cta;" ::: "memory");
          }
        };
        uint32_t t16 = (a[142] | a[143]) & P.zero;
#pragma unroll 1
        for (int p = 0; p < 4; p++) {
          float acc[64];
          bar_sync(NB_ORD0 + wg + (p ? 0 : t16), 256);
          TS(64 + L * 32 + p * 5);
          if (p == 0) { rel(9); rel(10); rel(11); }
          mma_pass<128, PS_FF, 4, 2048, 0, false, false>(acc, a, DESC_SW128, p & 1, rel, NB_ORD1 - wg, nullptr, 0, 0, 0, 0, 0, [&]() {
            t16 = tid_() * 16;
            if (p) verify(p - 1, t16);
          });
          TS(65 + L * 32 + p * 5);
          if (p == 1 || p == 2) add_piece<false>(acc, xs + t16);
          const uint32_t oa = ((j + (p < 3 ? 1 : 4)) & 7) * PSRC + (p & 1) * 16384 + t16;
#pragma unroll
          for (int i = 0; i < 4; i++)
            st16(sb, oa, OFF_P + i * 2048, (pack_bf16(acc[8 * i], acc[8 * i + 1]) & ~1u) | (p < 2), pack_bf16(acc[8 * i + 2], acc[8 * i + 3]),
                 pack_bf16(acc[8 * i + 4], acc[8 * i + 5]), pack_bf16(acc[8 * i + 6], acc[8 * i + 7]));
          if (p == 0) {
#pragma unroll
            for (int i = 0; i < 8; i++)
              send8(sb, j * 1024 + t16 / 2, OFF_P + 32768 + i * PSRC, xs + 15360 + t16 / 2, i, j,
                    (pack_bf16(acc[32 + 4 * i], acc[33 + 4 * i]) & ~1u) | (L ^ 1), pack_bf16(acc[34 + 4 * i], acc[35 + 4 * i]));
          } else {
            if (p == 2) add_piece<false>(acc + 32, xs + 8192 + t16);
            const uint32_t ob = ((j + (p < 3 ? 7 : 5)) & 7) * PSRC + (p & 1) * 16384 + t16, tb = p == 2 ? L ^ 1 : p < 2;
#pragma unroll
            for (int i = 4; i < 8; i++)
              st16(sb, ob, OFF_P + i * 2048, (pack_bf16(acc[8 * i], acc[8 * i + 1]) & ~1u) | tb, pack_bf16(acc[8 * i + 2], acc[8 * i + 3]),
                   pack_bf16(acc[8 * i + 4], acc[8 * i + 5]), pack_bf16(acc[8 * i + 6], acc[8 * i + 7]));
          }
          hint_post(hint);
          TS(68 + L * 32 + p * 5);
          if (p == 1) {
            float s0 = 0.f, s1 = 0.f, s2 = 0.f, s3 = 0.f;
#pragma unroll
            for (int s = 0; s < 8; s++) {
              uint32_t u, v;
              lds64(u, v, xs + 8192 + s * 1024 + t16 / 2);
              s0 += bf_lo(u); s1 += bf_hi(u); s2 += bf_lo(v); s3 += bf_hi(v);
            }
            sts64(ytail(wg * 2) + t16 / 2, pack_bf16(s0, s1), pack_bf16(s2, s3));
          }
          if (p < 3) bar_arrive(NB_FREE + wg, 160);
          TS(67 + L * 32 + p * 5);
        }
        float acc[32];
        add_piece<true>(acc, xs + t16);
        add_piece<false>(acc, xs + 8192 + t16);
        bar_arrive(NB_FREE + wg, 160);
        load_own(xr, sb, L * 3 * TILE, j);
        bar_sync(NB_ORD0 + wg, 256);
        TS(84 + L * 32);
        uint32_t t, yn[2];
        mma_pass<64, PS_FFA, 4, 2048, 0, false, false>(acc, a, DESC_SW128, 0, rel, wg ? -1 : NB_ORD1, nullptr, 0, 0, 0, 0, 0, [&]() {
          t = tid_();
          lds64(yn[0], yn[1], ytail(wg * 2) + t * 8);
          mbar_wait(bar_full(12) + wg * 8, 1);
#pragma unroll
          for (int i = 0; i < 8; i++) lds128(&a[4 * i], xs + i * 2048 + t * 16);
        });
        TS(11 + L * 20);
        while (true) {
          uint32_t m = 0;
#pragma unroll
          for (int i = 0; i < 8; i++) m |= a[4 * i];
          if (!__any_sync(0xffffffffu, m & 1)) break;
#pragma unroll
          for (int i = 0; i < 8; i++) ld16(&a[4 * i], sb, j * PSRC + t * 16, OFF_P + 16384 + i * 2048);
        }
        TS(12 + L * 20);
#pragma unroll
        for (int i = 0; i < 18; i++)
          xr[i] = bf2_add(xr[i], i < 16 ? pack_bf16(acc[2 * i] + (bf_lo(a[i]) + bf_lo(a[16 + i])), acc[2 * i + 1] + (bf_hi(a[i]) + bf_hi(a[16 + i]))) : yn[i - 16]);
        TS(18 + L * 20);
        if (L == 0) {
          store_own(xr, sb, OFF_X2, j, t);
          RowStats rs;
          rs.add<18>(xr);
          rs.store(sb, 8192 + j * 128, t);
          hint_post(hint);
        } else {
          const uint32_t l = t & 31, wb = xs + w * 512;
          __syncwarp();
#pragma unroll
          for (int i = 0; i < 4; i++) stsm4(wb + i * 2048 + (l & 24) * 16 + (((l & 7) ^ (i * 2 + (l >> 4))) << 4), xr[4 * i], xr[4 * i + 1], xr[4 * i + 2], xr[4 * i + 3]);
          stsm4(wb + 8192 + l * 16, xr[16], xr[17], 0, 0);
          __syncwarp();
          uint8_t* op = (uint8_t*)P.out + row_off(rb, wg, w * 32 + (l >> 3)) + j * 128 + (l & 7) * 16;
#pragma unroll
          for (int i = 0; i < 4; i++) {
            uint32_t r[4];
            lds128(r, wb + ((l & 6) << 10) + ((l & 1) * 2 + (i >> 1)) * 128 + (((((i & 1) * 4 + (l >> 3)) ^ l) & 7) << 4));
            *(uint4*)(op + i * 16 * DM) = make_uint4(r[0], r[1], r[2], r[3]);
          }
          uint32_t r[4];
          lds128(r, wb + 8192 + l * 16);
          if (l < 16) *(uint4*)((uint8_t*)P.out + row_off(rb, wg, t) + 1024 + j * 16) = make_uint4(r[0], r[1], r[2], r[3]);
        }
      }
      TS(13 + L * 20);
    }
    bar_sync(NB_WG + wg, 128);
    if (tid_() == 0) mbar_arrive(bar_empty(12));
  }
}

typedef CUresult (*EncodeFn)(CUtensorMap*, CUtensorMapDataType, cuuint32_t, void*, const cuuint64_t*, const cuuint64_t*, const cuuint32_t*,
                             const cuuint32_t*, CUtensorMapInterleave, CUtensorMapSwizzle, CUtensorMapL2promotion, CUtensorMapFloatOOBfill);

void encode(EncodeFn fn, CUtensorMap* m, const void* p, int rank, const cuuint64_t* dims, const cuuint64_t* str, const cuuint32_t* box) {
  const cuuint32_t es[3] = {1, 1, 1};
  fn(m, CU_TENSOR_MAP_DATA_TYPE_BFLOAT16, rank, const_cast<void*>(p), dims, str, box, es, CU_TENSOR_MAP_INTERLEAVE_NONE,
     CU_TENSOR_MAP_SWIZZLE_128B, CU_TENSOR_MAP_L2_PROMOTION_L2_256B, CU_TENSOR_MAP_FLOAT_OOB_FILL_NONE);
}

}

extern "C" void kernel_launch(void* const* d_in, const int* in_sizes, int n_in, void* d_out, int out_size) {
  (void)in_sizes; (void)n_in; (void)out_size;
  Params P;
  P.x = (const __nv_bfloat16*)d_in[0]; P.wqkv = (const __nv_bfloat16*)d_in[1]; P.wo = (const __nv_bfloat16*)d_in[2];
  P.wg = (const __nv_bfloat16*)d_in[4]; P.wu = (const __nv_bfloat16*)d_in[5]; P.wd = (const __nv_bfloat16*)d_in[6];
  P.out = (__nv_bfloat16*)d_out; P.zero = 0;
  cudaGetSymbolAddress((void**)&P.scr, g_scr);
  void* fnp = nullptr; cudaDriverEntryPointQueryResult qr;
  cudaGetDriverEntryPoint("cuTensorMapEncodeTiled", &fnp, cudaEnableDefault, &qr);
  EncodeFn fn = (EncodeFn)fnp;
  CUtensorMap mx, mg, mu, md;
  { const cuuint64_t dims[3] = {DM, SEQ / 2, 2}, str[2] = {DM * 4, DM * 2}; const cuuint32_t box[3] = {64, 64, 2}; encode(fn, &mx, P.x, 3, dims, str, box); }
  { const cuuint64_t dims[2] = {DFF, DM}, str[1] = {DFF * 2}; const cuuint32_t box[2] = {64, 64}; encode(fn, &mg, P.wg, 2, dims, str, box); encode(fn, &mu, P.wu, 2, dims, str, box); }
  { const cuuint64_t dims[2] = {DM, DFF}, str[1] = {DM * 2}; const cuuint32_t box[2] = {64, 64}; encode(fn, &md, P.wd, 2, dims, str, box); }
  cudaFuncSetAttribute(fused_kernel, cudaFuncAttributeMaxDynamicSharedMemorySize, SMEM_BYTES);
  fused_kernel<<<128, 384, SMEM_BYTES, cudaStreamPerThread>>>(mx, mg, mu, md, P);
}
```

```cpp
#include <cuda_runtime.h>
#include <cuda_bf16.h>
#include <cuda.h>
#include <stdint.h>

#define KV_LEAD 5
#define D_KV 6
#define D_WO 3
#define D_T0 5
#define PF_AHEAD 3
#define CH_LAST 3
#define MC 1
#define MAP 5
#define N_WO 12
#define DBG_PS 2
#define SMALLPOS 1
#define AORD 0
#define N_UP 26
#define CLR_NS 0
#define EVF 15
#define TIMING 0

#define EFP 0x12F0000000000000ull
#define ENP 0x1000000000000000ull
namespace {

constexpr int SEQ = 2048, DM = 576, DFF = 4608;
constexpr uint32_t SB = 1024;
constexpr uint32_t SLOT = 16384;
constexpr uint32_t PSLOT = 13824;
constexpr uint32_t BARS = SB + 14 * SLOT;
constexpr int SMEM_BYTES = 14 * SLOT + 256 + 2560;
__host__ __device__ constexpr uint32_t slot_addr(int s) { return SB + s * SLOT; }
__host__ __device__ constexpr uint32_t bar_full(int s) { return BARS + 8 * s; }
__host__ __device__ constexpr uint32_t bar_empty(int s) { return BARS + 128 + 8 * s; }
enum { NB_ORD0 = 1, NB_ORD1 = 2, NB_WG = 3  , NB_HALO = 5  , NB_FREE = 7  , NB_PUB = 9   };
constexpr uint32_t SM_EPOCH = BARS + 120;
__host__ __device__ constexpr uint32_t ytail(uint32_t k) { return k < 3 ? slot_addr(9) + PSLOT + k * SLOT : BARS + 256; }
constexpr uint32_t KSTG = 9 * 1152;

constexpr uint32_t TILE = 36 * 2048;
constexpr uint32_t OFF_X1 = 0  , OFF_O = TILE, OFF_X2 = 2 * TILE, OFF_ST = 4 * TILE  ;
constexpr uint32_t PSRC = 2 * 16384 + 7 * 1024;
constexpr uint32_t OFF_P = OFF_ST + 3 * 4096, OFF_HALO = OFF_P + 8 * PSRC  , OFF_HINT = OFF_HALO + 2 * 8 * 3072  ,
                   OFF_H = OFF_HINT + 16 * 128  , STRM = OFF_H + 8 * 24576;
constexpr uint32_t OFF_WPACK = 32 * STRM, OFF_FLAGS = OFF_WPACK + 8 * 24 * PSLOT;
__device__ __align__(1024) uint8_t g_scr[OFF_FLAGS + (8 + 64 + 128) * 32];

__device__ __forceinline__ uint32_t smem_u32(const void* p) { return (uint32_t)__cvta_generic_to_shared(p); }
extern __shared__ __align__(1024) uint8_t smem_raw[];
__device__ __forceinline__ uint32_t win() { return MC ? (blockIdx.x & 1) << 24 : 0; }
#define SA(A, W) ".reg .u32 sa;\nadd.u32 sa, " A ", " W ";\n"
__device__ __forceinline__ void mbar_init(uint32_t bar, uint32_t cnt) { asm volatile("{\n" SA("%0", "%2") "mbarrier.init.shared::cta.b64 [sa], %1;\n}" ::"r"(bar), "r"(cnt), "r"(win())); }
__device__ __forceinline__ void mbar_expect_tx(uint32_t bar, uint32_t bytes) { asm volatile("{\n" SA("%0", "%2") "mbarrier.arrive.expect_tx.shared::cta.b64 _, [sa], %1;\n}" ::"r"(bar), "r"(bytes), "r"(win()) : "memory"); }
__device__ __forceinline__ void mbar_arrive(uint32_t bar) { asm volatile("{\n" SA("%0", "%1") "mbarrier.arrive.shared::cta.b64 _, [sa];\n}" ::"r"(bar), "r"(win()) : "memory"); }
__device__ __forceinline__ uint32_t lds32(uint32_t a) { uint32_t v; asm volatile("{\n" SA("%1", "%2") "ld.shared.u32 %0, [sa];\n}" : "=r"(v) : "r"(a), "r"(win()) : "memory"); return v; }
__device__ __forceinline__ void lds64(uint32_t& x, uint32_t& y, uint32_t a) { asm volatile("{\n" SA("%2", "%3") "ld.shared.v2.u32 {%0,%1}, [sa];\n}" : "=r"(x), "=r"(y) : "r"(a), "r"(win()) : "memory"); }
__device__ __forceinline__ void lds128(uint32_t* v, uint32_t a) {
  asm volatile("{\n" SA("%4", "%5") "ld.shared.v4.u32 {%0,%1,%2,%3}, [sa];\n}" : "=r"(v[0]), "=r"(v[1]), "=r"(v[2]), "=r"(v[3]) : "r"(a), "r"(win()) : "memory");
}
__device__ __forceinline__ void stsm4(uint32_t a, uint32_t x, uint32_t y, uint32_t z, uint32_t w) {
  asm volatile("{\n" SA("%0", "%5") "stmatrix.sync.aligned.m8n8.x4.shared.b16 [sa], {%1,%2,%3,%4};\n}" ::"r"(a), "r"(x), "r"(y), "r"(z), "r"(w), "r"(win()) : "memory");
}
__device__ __forceinline__ void ldsm4(uint32_t* v, uint32_t a) {
  asm volatile("{\n" SA("%4", "%5") "ldmatrix.sync.aligned.m8n8.x4.shared.b16 {%0,%1,%2,%3}, [sa];\n}" : "=r"(v[0]), "=r"(v[1]), "=r"(v[2]), "=r"(v[3]) : "r"(a), "r"(win()) : "memory");
}
__device__ __forceinline__ void ldsm4t(uint32_t* v, uint32_t a) {
  asm volatile("{\n" SA("%4", "%5") "ldmatrix.sync.aligned.m8n8.x4.trans.shared.b16 {%0,%1,%2,%3}, [sa];\n}" : "=r"(v[0]), "=r"(v[1]), "=r"(v[2]), "=r"(v[3]) : "r"(a), "r"(win()) : "memory");
}
__device__ __forceinline__ void sts32(uint32_t a, uint32_t x) { asm volatile("{\n" SA("%0", "%2") "st.shared.u32 [sa], %1;\n}" ::"r"(a), "r"(x), "r"(win()) : "memory"); }
__device__ __forceinline__ void sts64(uint32_t a, uint32_t x, uint32_t y) { asm volatile("{\n" SA("%0", "%3") "st.shared.v2.u32 [sa], {%1,%2};\n}" ::"r"(a), "r"(x), "r"(y), "r"(win()) : "memory"); }
__device__ __forceinline__ void sts128(uint32_t a, uint32_t x, uint32_t y, uint32_t z, uint32_t w) {
  asm volatile("{\n" SA("%0", "%5") "st.shared.v4.u32 [sa], {%1,%2,%3,%4};\n}" ::"r"(a), "r"(x), "r"(y), "r"(z), "r"(w), "r"(win()) : "memory");
}
__device__ __forceinline__ void mbar_wait(uint32_t bar, uint32_t parity) {
  asm volatile("{\n.reg .pred p;\n" SA("%0", "%2") "LAB_WAIT:\nmbarrier.try_wait.parity.shared::cta.b64 p, [sa], %1;\n@!p bra LAB_WAIT;\n}" ::"r"(bar), "r"(parity), "r"(win()) : "memory");
}
__device__ __forceinline__ void timed_wait(uint32_t bar, uint32_t par) {
  asm volatile("{\n.reg .pred p;\n.reg .u64 t0, t1;\nmov.u64 t0, %%globaltimer;\nLAB_WD:\n"
               "mbarrier.try_wait.parity.shared::cta.b64 p, [%0], %1, 100000;\n@p bra LAB_OK;\n"
               "mov.u64 t1, %%globaltimer;\nsub.u64 t1, t1, t0;\nsetp.lt.u64 p, t1, 2000000000;\n@p bra LAB_WD;\ntrap;\nLAB_OK:\n}" ::"r"(bar + win()), "r"(par) : "memory");
}
__device__ __forceinline__ void flag_wait(const unsigned* flag, unsigned target) {
  asm volatile("{\n.reg .pred p;\n.reg .u32 v;\nLAB_WAIT:\nld.acquire.gpu.global.u32 v, [%0];\nsub.u32 v, v, %1;\n"
               "setp.lt.s32 p, v, 0;\nvote.sync.any.pred p, p, 0xffffffff;\n@p nanosleep.u32 100;\n@p bra LAB_WAIT;\n}" ::"l"(flag), "r"(target) : "memory");
}
__device__ __forceinline__ void hint_post(uint8_t* p) {
  __syncwarp();
  asm volatile("{\n.reg .pred p;\nelect.sync _|p, 0xffffffff;\n@p red.relaxed.gpu.global.add.u32 [%0], 1;\n}" ::"l"(p) : "memory");
}
__device__ __forceinline__ void hint_wait(const uint8_t* p, uint32_t target) {
  asm volatile("{\n.reg .pred p;\n.reg .u32 v;\nLAB_WAIT:\nld.relaxed.gpu.global.u32 v, [%0];\nsub.u32 v, v, %1;\n"
               "setp.lt.s32 p, v, 0;\nvote.sync.any.pred p, p, 0xffffffff;\n@p bra LAB_WAIT;\n}" ::"l"(p), "r"(target) : "memory");
}
__device__ __forceinline__ void flag_signal(unsigned* flag) { asm volatile("red.release.gpu.global.add.u32 [%0], 1;" ::"l"(flag) : "memory"); }
struct Rel {
  bool on; uint32_t base;
  __device__ __forceinline__ void operator()(int s) const {
    if (on) {
      if (MC) asm volatile("{\n" SA("%0", "%1") "mbarrier.arrive.shared::cluster.b64 _, [sa];\n}" ::"r"(bar_empty(s)), "r"(base) : "memory");
      else mbar_arrive(bar_empty(s));
    }
  }
};
__device__ __forceinline__ uint32_t cta_window(uint32_t rank) { uint32_t a; asm("mapa.shared::cluster.u32 %0, %1, %2;" : "=r"(a) : "r"(0), "r"(rank)); return a; }
#define ELECT ".reg .pred e;\nelect.sync _|e, 0xffffffff;\n"
__device__ __forceinline__ void w_expect_tx(uint32_t bar, uint32_t bytes) {
  asm volatile("{\n" ELECT "@e mbarrier.arrive.expect_tx.shared::cta.b64 _, [%0], %1;\n}" ::"r"(bar), "r"(bytes) : "memory");
}
__device__ __forceinline__ void w_tma_2d_mc(uint32_t dst, const CUtensorMap* m, int c0, int c1, uint32_t bar) {
  asm volatile("{\n" ELECT "@e cp.async.bulk.tensor.2d.shared::cluster.global.mbarrier::complete_tx::bytes.multicast::cluster [%0], [%1, {%3, %4}], [%2], %5;\n}"
               ::"r"(dst), "l"(m), "r"(bar), "r"(c0), "r"(c1), "h"((uint16_t)3) : "memory");
}
__device__ __forceinline__ void w_bulk_load_mc(uint32_t dst, const void* src, uint32_t bytes, uint32_t bar) {
  asm volatile("{\n" ELECT "@e cp.async.bulk.shared::cluster.global.mbarrier::complete_tx::bytes.multicast::cluster [%0], [%1], %2, [%3], %4;\n}"
               ::"r"(dst), "l"(src), "r"(bytes), "r"(bar), "h"((uint16_t)3) : "memory");
}
__device__ __forceinline__ void w_bulk_load(uint32_t dst, const void* src, uint32_t bytes, uint32_t bar, uint64_t pol = (EVF & 8) ? EFP : ENP) {
  asm volatile("{\n" ELECT "@e cp.async.bulk.shared::cluster.global.mbarrier::complete_tx::bytes.L2::cache_hint [%0], [%1], %2, [%3], %4;\n}" ::"r"(dst), "l"(src), "r"(bytes), "r"(bar), "l"(pol) : "memory");
}
__device__ __forceinline__ void w_l2_prefetch(const void* src, uint32_t bytes) { asm volatile("{\n" ELECT "@e cp.async.bulk.prefetch.L2.global [%0], %1;\n}" ::"l"(src), "r"(bytes) : "memory"); }
__device__ __forceinline__ void w_tma_prefetch(const CUtensorMap* m, int c0, int c1) {
  asm volatile("{\n" ELECT "@e cp.async.bulk.prefetch.tensor.2d.L2.global [%0, {%1, %2}];\n}" ::"l"(m), "r"(c0), "r"(c1) : "memory");
}
__device__ __forceinline__ void tma_3d(uint32_t dst, const CUtensorMap* m, int c0, int c1, int c2, uint32_t bar) {
  asm volatile("cp.async.bulk.tensor.3d.shared::cluster.global.mbarrier::complete_tx::bytes.L2::cache_hint [%0], [%1, {%3, %4, %5}], [%2], %6;"
               ::"r"(dst), "l"(m), "r"(bar), "r"(c0), "r"(c1), "r"(c2), "l"((EVF & 1) ? EFP : ENP) : "memory");
}
__device__ __forceinline__ void wg_fence() { asm volatile("wgmma.fence.sync.aligned;" ::: "memory"); }
__device__ __forceinline__ void wg_commit() { asm volatile("wgmma.commit_group.sync.aligned;" ::: "memory"); }
template <int N> __device__ __forceinline__ void wg_wait() { asm volatile("wgmma.wait_group.sync.aligned %0;" ::"n"(N) : "memory"); }
__device__ __forceinline__ void bar_sync(int id, int n) { asm volatile("bar.sync %0, %1;" ::"r"(id), "r"(n) : "memory"); }
__device__ __forceinline__ void bar_arrive(int id, int n) { asm volatile("bar.arrive %0, %1;" ::"r"(id), "r"(n) : "memory"); }
__device__ __forceinline__ void bar_arrive_if(uint32_t on, int id, int n) { asm volatile("{\n.reg .pred p;\nsetp.ne.u32 p, %2, 0;\n@p bar.arrive %0, %1;\n}" ::"r"(id), "r"(n), "r"(on) : "memory"); }
__device__ __forceinline__ uint32_t pack_bf16(float lo, float hi) { uint32_t r; asm("cvt.rn.bf16x2.f32 %0, %1, %2;" : "=r"(r) : "f"(hi), "f"(lo)); return r; }
__device__ __forceinline__ float bf_lo(uint32_t w) { return __uint_as_float(w << 16); }
__device__ __forceinline__ float bf_hi(uint32_t w) { return __uint_as_float(w & 0xffff0000u); }
__device__ __forceinline__ float bf_round(float x) { return bf_lo(pack_bf16(x, 0.f)); }
__device__ __forceinline__ uint32_t bf2_sub(uint32_t a, uint32_t b) { uint32_t r; asm("sub.rn.bf16x2 %0, %1, %2;" : "=r"(r) : "r"(a), "r"(b)); return r; }
__device__ __forceinline__ uint32_t bf2_add(uint32_t a, uint32_t b) { uint32_t r; asm("add.rn.bf16x2 %0, %1, %2;" : "=r"(r) : "r"(a), "r"(b)); return r; }
#define GADDR(B, O, I) "cvt.u64.u32 ad, " O ";\nadd.u64 ad, ad, " B ";\nadd.u64 ad, ad, " I ";\n"
__device__ __forceinline__ void ld16(uint32_t* v, const uint8_t* ub, uint32_t off, uint32_t imm) {
  asm volatile("{\n.reg .b128 z;\n.reg .b64 x, y, ad;\n" GADDR("%4", "%5", "%6") "ld.relaxed.gpu.global.b128 z, [ad];\n"
               "mov.b128 {x, y}, z;\nmov.b64 {%0,%1}, x;\nmov.b64 {%2,%3}, y;\n}"
               : "=r"(v[0]), "=r"(v[1]), "=r"(v[2]), "=r"(v[3]) : "l"(ub), "r"(off), "l"((uint64_t)imm) : "memory");
}
__device__ __forceinline__ void ld8(uint32_t* v, const uint8_t* ub, uint32_t off, uint32_t imm) {
  asm volatile("{\n.reg .b64 x, ad;\n" GADDR("%2", "%3", "%4") "ld.relaxed.gpu.global.b64 x, [ad];\nmov.b64 {%0,%1}, x;\n}"
               : "=r"(v[0]), "=r"(v[1]) : "l"(ub), "r"(off), "l"((uint64_t)imm) : "memory");
}
__device__ __forceinline__ void st16(uint8_t* ub, uint32_t off, uint32_t imm, uint32_t a, uint32_t b, uint32_t c, uint32_t d) {
  asm volatile("{\n.reg .b128 z;\n.reg .b64 x, y, ad;\n" GADDR("%0", "%1", "%2") "mov.b64 x, {%3,%4};\nmov.b64 y, {%5,%6};\nmov.b128 z, {x, y};\n"
               "st.relaxed.gpu.global.b128 [ad], z;\n}" ::"l"(ub), "r"(off), "l"((uint64_t)imm), "r"(a), "r"(b), "r"(c), "r"(d) : "memory");
}
__device__ __forceinline__ void st16e(uint8_t* ub, uint32_t off, uint32_t imm, uint32_t a, uint32_t b, uint32_t c, uint32_t d) {
  asm volatile("{\n.reg .b64 ad;\n" GADDR("%0", "%1", "%2") "st.relaxed.gpu.global.L2::cache_hint.v4.b32 [ad], {%3,%4,%5,%6}, %7;\n}" ::"l"(ub), "r"(off), "l"((uint64_t)imm), "r"(a), "r"(b), "r"(c), "r"(d), "l"(EFP) : "memory");
}
__device__ __forceinline__ void ld16e(uint32_t* v, const uint8_t* ub, uint32_t off, uint32_t imm) {
  asm volatile("{\n.reg .b64 ad;\n" GADDR("%4", "%5", "%6") ".reg .b128 z;\n.reg .b64 x, y;\nld.relaxed.gpu.global.L2::cache_hint.b128 z, [ad], %7;\nmov.b128 {x, y}, z;\nmov.b64 {%0,%1}, x;\nmov.b64 {%2,%3}, y;\n}"
               : "=r"(v[0]), "=r"(v[1]), "=r"(v[2]), "=r"(v[3]) : "l"(ub), "r"(off), "l"((uint64_t)imm), "l"(EFP) : "memory");
}
__device__ __forceinline__ void st8(uint8_t* ub, uint32_t off, uint32_t imm, uint32_t a, uint32_t b) {
  asm volatile("{\n.reg .b64 x, ad;\n" GADDR("%0", "%1", "%2") "mov.b64 x, {%3,%4};\nst.relaxed.gpu.global.b64 [ad], x;\n}"
               ::"l"(ub), "r"(off), "l"((uint64_t)imm), "r"(a), "r"(b) : "memory");
}
__device__ __forceinline__ void send8(uint8_t* ub, uint32_t off, uint32_t imm, uint32_t sm, int i, int j, uint32_t a, uint32_t b) {
  asm volatile("{\n.reg .pred p, q, e;\n.reg .b64 x, ad;\n" SA("%3", "%8") GADDR("%0", "%1", "%2")
               "setp.lt.s32 p, %4, %5;\nsetp.gt.s32 q, %4, %5;\nsetp.eq.s32 e, %4, %5;\nmov.b64 x, {%6,%7};\n"
               "@p st.relaxed.gpu.global.b64 [ad+-1024], x;\n@q st.relaxed.gpu.global.b64 [ad], x;\n@e st.shared.v2.u32 [sa], {%6,%7};\n}"
               ::"l"(ub), "r"(off), "l"((uint64_t)imm), "r"(sm), "r"(i), "r"(j), "r"(a), "r"(b), "r"(win()) : "memory");
}
__device__ __forceinline__ uint4 ldg_line(const void* p) {
  uint4 v; asm volatile("ld.global.nc.L2::cache_hint.L2::128B.v4.u32 {%0,%1,%2,%3}, [%4], %5;" : "=r"(v.x), "=r"(v.y), "=r"(v.z), "=r"(v.w) : "l"(p), "l"((EVF & 1) ? EFP : ENP)); return v;
}
__device__ __forceinline__ void stg4(void* ub, uint32_t off, uint32_t imm, uint32_t v) {
  asm volatile("{\n.reg .b64 ad;\n" GADDR("%0", "%1", "%2") "st.global.u32 [ad], %3;\n}" ::"l"(ub), "r"(off), "l"((uint64_t)imm), "r"(v) : "memory");
}
__device__ __forceinline__ uint32_t tid_() { uint32_t t; asm volatile("mov.u32 %0, %%tid.x;" : "=r"(t)); return t & 127; }
__device__ __forceinline__ uint32_t nz(uint32_t w) { asm("max.u32 %0, %0, 1;" : "+r"(w)); return w; }
__device__ __forceinline__ void mma16816(float (&c)[4], uint32_t a0, uint32_t a1, uint32_t a2, uint32_t a3, uint32_t b0, uint32_t b1) {
  asm("mma.sync.aligned.m16n8k16.row.col.f32.bf16.bf16.f32 {%0,%1,%2,%3}, {%4,%5,%6,%7}, {%8,%9}, {%0,%1,%2,%3};"
               : "+f"(c[0]), "+f"(c[1]), "+f"(c[2]), "+f"(c[3]) : "r"(a0), "r"(a1), "r"(a2), "r"(a3), "r"(b0), "r"(b1));
}
__device__ __forceinline__ void mma1688(float (&c)[4], uint32_t a0, uint32_t a1, uint32_t b0) {
  asm("mma.sync.aligned.m16n8k8.row.col.f32.bf16.bf16.f32 {%0,%1,%2,%3}, {%4,%5}, {%6}, {%0,%1,%2,%3};"
               : "+f"(c[0]), "+f"(c[1]), "+f"(c[2]), "+f"(c[3]) : "r"(a0), "r"(a1), "r"(b0));
}
__device__ __forceinline__ float ex2(float x) { float r; asm("ex2.approx.ftz.f32 %0, %1;" : "=f"(r) : "f"(x)); return r; }
__device__ __forceinline__ float quad_sum(float v) { v += __shfl_xor_sync(0xffffffffu, v, 1); v += __shfl_xor_sync(0xffffffffu, v, 2); return v; }
__device__ __forceinline__ float quad_max(float v) { v = fmaxf(v, __shfl_xor_sync(0xffffffffu, v, 1)); v = fmaxf(v, __shfl_xor_sync(0xffffffffu, v, 2)); return v; }

__device__ __forceinline__ void wgmma_rs_n64(float (&d)[32], uint32_t a0, uint32_t a1, uint32_t a2, uint32_t a3, uint64_t desc, int scale_d) {
  asm volatile("{\n.reg .pred p;\nsetp.ne.b32 p, %37, 0;\n"
    "wgmma.mma_async.sync.aligned.m64n64k16.f32.bf16.bf16 "
    "{%0, %1, %2, %3, %4, %5, %6, %7, %8, %9, %10, %11, %12, %13, %14, %15, %16, %17, %18, %19, %20, %21, %22, %23, %24, %25, %26, %27, %28, %29, %30, %31}, "
    "{%32, %33, %34, %35}, %36, p, 1, 1, 1;\n}\n"
    : "+f"(d[0]), "+f"(d[1]), "+f"(d[2]), "+f"(d[3]), "+f"(d[4]), "+f"(d[5]), "+f"(d[6]), "+f"(d[7]), "+f"(d[8]), "+f"(d[9]), "+f"(d[10]), "+f"(d[11]), "+f"(d[12]), "+f"(d[13]), "+f"(d[14]), "+f"(d[15]), "+f"(d[16]), "+f"(d[17]), "+f"(d[18]), "+f"(d[19]), "+f"(d[20]), "+f"(d[21]), "+f"(d[22]), "+f"(d[23]), "+f"(d[24]), "+f"(d[25]), "+f"(d[26]), "+f"(d[27]), "+f"(d[28]), "+f"(d[29]), "+f"(d[30]), "+f"(d[31])
    : "r"(a0), "r"(a1), "r"(a2), "r"(a3), "l"(desc), "r"(scale_d));
}

__device__ __forceinline__ void wgmma_rs_n72(float (&d)[36], uint32_t a0, uint32_t a1, uint32_t a2, uint32_t a3, uint64_t desc, int scale_d) {
  asm volatile("{\n.reg .pred p;\nsetp.ne.b32 p, %41, 0;\n"
    "wgmma.mma_async.sync.aligned.m64n72k16.f32.bf16.bf16 "
    "{%0, %1, %2, %3, %4, %5, %6, %7, %8, %9, %10, %11, %12, %13, %14, %15, %16, %17, %18, %19, %20, %21, %22, %23, %24, %25, %26, %27, %28, %29, %30, %31, %32, %33, %34, %35}, "
    "{%36, %37, %38, %39}, %40, p, 1, 1, 1;\n}\n"
    : "+f"(d[0]), "+f"(d[1]), "+f"(d[2]), "+f"(d[3]), "+f"(d[4]), "+f"(d[5]), "+f"(d[6]), "+f"(d[7]), "+f"(d[8]), "+f"(d[9]), "+f"(d[10]), "+f"(d[11]), "+f"(d[12]), "+f"(d[13]), "+f"(d[14]), "+f"(d[15]), "+f"(d[16]), "+f"(d[17]), "+f"(d[18]), "+f"(d[19]), "+f"(d[20]), "+f"(d[21]), "+f"(d[22]), "+f"(d[23]), "+f"(d[24]), "+f"(d[25]), "+f"(d[26]), "+f"(d[27]), "+f"(d[28]), "+f"(d[29]), "+f"(d[30]), "+f"(d[31]), "+f"(d[32]), "+f"(d[33]), "+f"(d[34]), "+f"(d[35])
    : "r"(a0), "r"(a1), "r"(a2), "r"(a3), "l"(desc), "r"(scale_d));
}

__device__ __forceinline__ void wgmma_rs_n128(float (&d)[64], uint32_t a0, uint32_t a1, uint32_t a2, uint32_t a3, uint64_t desc, int scale_d) {
  asm volatile("{\n.reg .pred p;\nsetp.ne.b32 p, %69, 0;\n"
    "wgmma.mma_async.sync.aligned.m64n128k16.f32.bf16.bf16 "
    "{%0, %1, %2, %3, %4, %5, %6, %7, %8, %9, %10, %11, %12, %13, %14, %15, %16, %17, %18, %19, %20, %21, %22, %23, %24, %25, %26, %27, %28, %29, %30, %31, %32, %33, %34, %35, %36, %37, %38, %39, %40, %41, %42, %43, %44, %45, %46, %47, %48, %49, %50, %51, %52, %53, %54, %55, %56, %57, %58, %59, %60, %61, %62, %63}, "
    "{%64, %65, %66, %67}, %68, p, 1, 1, 1;\n}\n"
    : "+f"(d[0]), "+f"(d[1]), "+f"(d[2]), "+f"(d[3]), "+f"(d[4]), "+f"(d[5]), "+f"(d[6]), "+f"(d[7]), "+f"(d[8]), "+f"(d[9]), "+f"(d[10]), "+f"(d[11]), "+f"(d[12]), "+f"(d[13]), "+f"(d[14]), "+f"(d[15]), "+f"(d[16]), "+f"(d[17]), "+f"(d[18]), "+f"(d[19]), "+f"(d[20]), "+f"(d[21]), "+f"(d[22]), "+f"(d[23]), "+f"(d[24]), "+f"(d[25]), "+f"(d[26]), "+f"(d[27]), "+f"(d[28]), "+f"(d[29]), "+f"(d[30]), "+f"(d[31]), "+f"(d[32]), "+f"(d[33]), "+f"(d[34]), "+f"(d[35]), "+f"(d[36]), "+f"(d[37]), "+f"(d[38]), "+f"(d[39]), "+f"(d[40]), "+f"(d[41]), "+f"(d[42]), "+f"(d[43]), "+f"(d[44]), "+f"(d[45]), "+f"(d[46]), "+f"(d[47]), "+f"(d[48]), "+f"(d[49]), "+f"(d[50]), "+f"(d[51]), "+f"(d[52]), "+f"(d[53]), "+f"(d[54]), "+f"(d[55]), "+f"(d[56]), "+f"(d[57]), "+f"(d[58]), "+f"(d[59]), "+f"(d[60]), "+f"(d[61]), "+f"(d[62]), "+f"(d[63])
    : "r"(a0), "r"(a1), "r"(a2), "r"(a3), "l"(desc), "r"(scale_d));
}

__device__ __forceinline__ void wgmma_rs_n144(float (&d)[72], uint32_t a0, uint32_t a1, uint32_t a2, uint32_t a3, uint64_t desc, int scale_d) {
  asm volatile("{\n.reg .pred p;\nsetp.ne.b32 p, %77, 0;\n"
    "wgmma.mma_async.sync.aligned.m64n144k16.f32.bf16.bf16 "
    "{%0, %1, %2, %3, %4, %5, %6, %7, %8, %9, %10, %11, %12, %13, %14, %15, %16, %17, %18, %19, %20, %21, %22, %23, %24, %25, %26, %27, %28, %29, %30, %31, %32, %33, %34, %35, %36, %37, %38, %39, %40, %41, %42, %43, %44, %45, %46, %47, %48, %49, %50, %51, %52, %53, %54, %55, %56, %57, %58, %59, %60, %61, %62, %63, %64, %65, %66, %67, %68, %69, %70, %71}, "
    "{%72, %73, %74, %75}, %76, p, 1, 1, 1;\n}\n"
    : "+f"(d[0]), "+f"(d[1]), "+f"(d[2]), "+f"(d[3]), "+f"(d[4]), "+f"(d[5]), "+f"(d[6]), "+f"(d[7]), "+f"(d[8]), "+f"(d[9]), "+f"(d[10]), "+f"(d[11]), "+f"(d[12]), "+f"(d[13]), "+f"(d[14]), "+f"(d[15]), "+f"(d[16]), "+f"(d[17]), "+f"(d[18]), "+f"(d[19]), "+f"(d[20]), "+f"(d[21]), "+f"(d[22]), "+f"(d[23]), "+f"(d[24]), "+f"(d[25]), "+f"(d[26]), "+f"(d[27]), "+f"(d[28]), "+f"(d[29]), "+f"(d[30]), "+f"(d[31]), "+f"(d[32]), "+f"(d[33]), "+f"(d[34]), "+f"(d[35]), "+f"(d[36]), "+f"(d[37]), "+f"(d[38]), "+f"(d[39]), "+f"(d[40]), "+f"(d[41]), "+f"(d[42]), "+f"(d[43]), "+f"(d[44]), "+f"(d[45]), "+f"(d[46]), "+f"(d[47]), "+f"(d[48]), "+f"(d[49]), "+f"(d[50]), "+f"(d[51]), "+f"(d[52]), "+f"(d[53]), "+f"(d[54]), "+f"(d[55]), "+f"(d[56]), "+f"(d[57]), "+f"(d[58]), "+f"(d[59]), "+f"(d[60]), "+f"(d[61]), "+f"(d[62]), "+f"(d[63]), "+f"(d[64]), "+f"(d[65]), "+f"(d[66]), "+f"(d[67]), "+f"(d[68]), "+f"(d[69]), "+f"(d[70]), "+f"(d[71])
    : "r"(a0), "r"(a1), "r"(a2), "r"(a3), "l"(desc), "r"(scale_d));
}

template <int N> struct WG;
template <> struct WG<64>  { static __device__ __forceinline__ void f(float (&d)[32], const uint32_t* a, uint64_t ds, int s) { wgmma_rs_n64(d, a[0], a[1], a[2], a[3], ds, s); } };
template <> struct WG<72>  { static __device__ __forceinline__ void f(float (&d)[36], const uint32_t* a, uint64_t ds, int s) { wgmma_rs_n72(d, a[0], a[1], a[2], a[3], ds, s); } };
template <> struct WG<128> { static __device__ __forceinline__ void f(float (&d)[64], const uint32_t* a, uint64_t ds, int s) { wgmma_rs_n128(d, a[0], a[1], a[2], a[3], ds, s); } };
template <> struct WG<144> { static __device__ __forceinline__ void f(float (&d)[72], const uint32_t* a, uint64_t ds, int s) { wgmma_rs_n144(d, a[0], a[1], a[2], a[3], ds, s); } };

constexpr uint64_t DESC_SW128 = ((uint64_t)(8192 >> 4) << 16) | ((uint64_t)(1024 >> 4) << 32) | (1ull << 62);
constexpr uint64_t DESC_KV = ((uint64_t)(128 >> 4) << 16) | ((uint64_t)(768 >> 4) << 32);
constexpr uint64_t DESC_Q = ((uint64_t)(128 >> 4) << 16) | ((uint64_t)(1536 >> 4) << 32);

template <int V> struct IntC { static constexpr int value = V; };
enum { PS_KV, PS_Q, PS_WO, PS_FF, PS_FFA   };
template <int PS> __host__ __device__ constexpr int pass_slot(int i) {
  return PS == PS_KV ? (i < 3 ? 9 + i : i - 3) : PS == PS_WO ? 6 + i : i;
}

__device__ __forceinline__ void load_frag(uint32_t (&a)[144], int i, const uint8_t* sb, uint32_t uo, uint32_t t) {
  if (i < 32 && (EVF & 16)) ld16e(&a[4 * i], sb, uo + t * 16, i * 2048);
  else if (i < 32) ld16(&a[4 * i], sb, uo + t * 16, i * 2048);
  else { ld8(&a[4 * i], sb, uo + t * 8, i * 2048); ld8(&a[4 * i + 2], sb, uo + t * 8, i * 2048 + 1024); }
}
__device__ __forceinline__ void store_own(const uint32_t (&y)[18], uint8_t* sb, uint32_t uo, int j, uint32_t t) {
#pragma unroll
  for (int i = 0; i < 4; i++) st16(sb, uo + j * 8192 + t * 16, i * 2048, nz(y[4 * i]), y[4 * i + 1], y[4 * i + 2], y[4 * i + 3]);
  st8(sb, uo + j * 1024 + t * 8, 65536, nz(y[16]), y[17]);
}
__device__ __forceinline__ void load_own(uint32_t* y, const uint8_t* sb, uint32_t uo, int j) {
  const uint32_t t = tid_();
#pragma unroll
  for (int i = 0; i < 4; i++) ld16(&y[4 * i], sb, uo + j * 8192 + t * 16, i * 2048);
  ld8(&y[16], sb, uo + j * 1024 + t * 8, 65536);
}

struct NoTail { __device__ __forceinline__ void operator()() const {} };
template <int N, int PS, int KPS, int KSTEP, int CHK, bool SUB, bool HREL = false, class Tail = NoTail>
__device__ __forceinline__ void mma_pass(float (&acc)[N / 2], uint32_t (&a)[144], uint64_t desc, uint32_t par, const Rel& rel, int bar_id,
                                         const uint8_t* sb = nullptr, uint32_t uo = 0, uint32_t flag = 0, uint32_t m0 = 0, uint32_t m1 = 0, uint32_t park = 0, Tail tail = Tail()) {
  constexpr int NS = 36 / KPS;
  auto check = [&](int lo, int hi, uint32_t m0_) {
    while (true) {
      uint32_t m = m0_;
#pragma unroll
      for (int i = hi - 1; i >= lo; i--) m = min(m, i < 32 ? a[4 * i] : min(a[4 * i], a[4 * i + 2]));
      if (!__any_sync(0xffffffffu, (m | flag) == 0)) break;
      const uint32_t t = tid_();
#pragma unroll
      for (int i = lo; i < hi; i++) load_frag(a, i, sb, uo, t);
    }
  };
#pragma unroll
  for (int s = 0; s < NS; s++) {
    const int sl = pass_slot<PS>(s);
    if (CHK && s == 0 && !SUB) check(0, CHK * KPS, ~0u);
    if (CHK && s == CHK) check(CHK * KPS, 36, lds32(SM_EPOCH) | 1);
    if (SUB) {
#pragma unroll
      for (int i = s * KPS * 4; i < (s + 1) * KPS * 4; i += 2) { a[i] = bf2_sub(a[i], m0); a[i + 1] = bf2_sub(a[i + 1], m1); }
    }
    if (PS == PS_KV && s == 0) sts128(park + tid_() * 16, a[0], a[1], a[2], a[3]);
    mbar_wait(bar_full(sl), sl < 9 ? par : par ^ 1);
    wg_fence();
#pragma unroll
    for (int kk = 0; kk < KPS; kk++)
      WG<N>::f(acc, &a[(s * KPS + kk) * 4], desc + ((slot_addr(sl) + kk * KSTEP) >> 4), (s | kk) || PS == PS_FFA);
    wg_commit();
    if (CHK && s < 2 && N_UP < 36 && !flag) {
      const uint32_t t = tid_();
#pragma unroll
      for (int i = s ? (N_UP + 36) / 2 : N_UP; i < (s ? 36 : (N_UP + 36) / 2); i++) load_frag(a, i, sb, uo, t);
    }
    if (s == (PS == PS_KV ? KV_LEAD : NS - 1) && bar_id >= 0) bar_arrive(bar_id, 256);
    if (s > 0) {
      wg_wait<1>();
      if (!(PS == PS_WO && s > 3)) rel(pass_slot<PS>(s - 1));
    }
    if (HREL && s == 3 && flag) {
#pragma unroll
      for (int i = 0; i < 12; i++) { if (EVF & 4) ld16e(&a[4 * i], sb, uo, i * 2048); else ld16(&a[4 * i], sb, uo, i * 2048); }
    }
  }
  tail();
  wg_wait<0>();
  if (PS != PS_WO) rel(pass_slot<PS>(NS - 1));
}

template <int NF, int N0 = 0> __device__ __forceinline__ void load_frags(uint32_t (&a)[144], const uint8_t* sb, uint32_t uo, uint32_t t) {
#pragma unroll
  for (int i = N0; i < NF; i++) load_frag(a, i, sb, uo, t);
}
__device__ __forceinline__ void ln_scalars(float s1, float s2, uint32_t& m, float& var, uint32_t zero) {
  const float mean = s1 * (1.f / DM);
  var = s2 * (1.f / DM) - mean * mean;
  m = pack_bf16(mean, mean) ^ (__float_as_uint(var) & zero);
}
__device__ __forceinline__ float ln_rstd(float var, float after, uint32_t zero) {
  var = __uint_as_float(__float_as_uint(var) ^ (__float_as_uint(after) & zero));
  float sd, r;
  asm("sqrt.approx.ftz.f32 %0, %1;" : "=f"(sd) : "f"(bf_round(bf_round(fmaxf(var, 0.f)) + 1e-5f)));
  asm("rcp.approx.ftz.f32 %0, %1;" : "=f"(r) : "f"(bf_round(sd)));
  return r;
}
template <int NF> __device__ __forceinline__ void gather_ln(uint32_t (&a)[144], const uint8_t* sb, uint32_t uo, uint32_t sto,
                                          uint32_t& m0, uint32_t& m1, float& r0, float& r1, uint32_t zero) {
  uint32_t u[32];
  const uint32_t t = tid_(), so = sto + (t >> 5) * 1024 + (t & 28) * 4;
#pragma unroll
  for (int i = 0; i < 8; i++) ld16(&u[4 * i], sb, so, OFF_ST + i * 128);
  load_frags<N_UP>(a, sb, uo, t);
  while (true) {
    uint32_t m = a[4 * NF - 4];
#pragma unroll
    for (int i = NF - 2; i >= 0; i--) m = min(m, a[4 * i]);
#pragma unroll
    for (int i = 0; i < 8; i++) m = min(m, u[4 * i]);
    if (!__any_sync(0xffffffffu, m == 0)) break;
#pragma unroll
    for (int i = 0; i < 8; i++) ld16(&u[4 * i], sb, so, OFF_ST + i * 128);
    load_frags<NF>(a, sb, uo, t);
  }
  float v[4];
#pragma unroll
  for (int k = 0; k < 4; k++)
    v[k] = ((__uint_as_float(u[k]) + __uint_as_float(u[4 + k])) + (__uint_as_float(u[8 + k]) + __uint_as_float(u[12 + k]))) +
           ((__uint_as_float(u[16 + k]) + __uint_as_float(u[20 + k])) + (__uint_as_float(u[24 + k]) + __uint_as_float(u[28 + k])));
  ln_scalars(v[1], v[0], m0, r0, zero); ln_scalars(v[3], v[2], m1, r1, zero);
}
struct Stats {
  float s[4] = {0, 0, 0, 0}, d0[4] = {0, 0, 0, 0}, d1[4] = {0, 0, 0, 0};
  __device__ __forceinline__ void add16(const uint32_t* f) {
    mma16816(s, f[0], f[1], f[2], f[3], 0x3f803f80u, 0x3f803f80u);
    mma1688(d0, f[0], f[1], f[0]); mma1688(d1, f[0], f[1], f[1]);
    mma1688(d0, f[2], f[3], f[2]); mma1688(d1, f[2], f[3], f[3]);
  }
  __device__ __forceinline__ float sq0(int g) const { return (g & 1) ? d0[1] : d0[0]; }
  __device__ __forceinline__ float sq1(int g) const { return (g & 1) ? d1[3] : d1[2]; }
};
struct RowStats {
  float s[4] = {0, 0, 0, 0}, u[4] = {0, 0, 0, 0};
  template <int N> __device__ __forceinline__ void add(const uint32_t* y) {
#pragma unroll
    for (int i = 0; i < N; i++) {
      const float lo = bf_lo(y[i]), hi = bf_hi(y[i]);
      const int r = (i & 1) * 2;
      s[r] = fmaf(lo, lo, s[r]); u[r] = fmaf(hi, hi, u[r]); s[r + 1] += lo; u[r + 1] += hi;
    }
  }
  __device__ __forceinline__ uint32_t fold() {
    uint32_t x = 0;
#pragma unroll
    for (int i = 0; i < 4; i++) { s[i] += u[i]; u[i] = 0; x |= __float_as_uint(s[i]); }
    return x;
  }
  __device__ __forceinline__ void store(uint8_t* sb, uint32_t sto, uint32_t t) {
    fold();
#pragma unroll
    for (int i = 0; i < 4; i++) s[i] += __shfl_xor_sync(0xffffffffu, s[i], 1);
#pragma unroll
    for (int i = 0; i < 4; i++) s[i] += __shfl_xor_sync(0xffffffffu, s[i], 2);
    if ((t & 3) == 0) st16(sb, sto + (t >> 5) * 1024 + (t & 28) * 4, OFF_ST, __float_as_uint(s[0]) | 1u, __float_as_uint(s[1]), __float_as_uint(s[2]), __float_as_uint(s[3]));
  }
};
template <bool SET> __device__ __forceinline__ void add_piece(float* acc, uint32_t sm) {
#pragma unroll
  for (int i = 0; i < 4; i++) {
    uint32_t v[4];
    lds128(v, sm + i * 2048);
#pragma unroll
    for (int k = 0; k < 4; k++) {
      acc[8 * i + 2 * k] = SET ? bf_lo(v[k]) : acc[8 * i + 2 * k] + bf_lo(v[k]);
      acc[8 * i + 2 * k + 1] = SET ? bf_hi(v[k]) : acc[8 * i + 2 * k + 1] + bf_hi(v[k]);
    }
  }
}

#define TS(i) do {} while (0)
#define TSP(i) do {} while (0)
#define TSH(i) do {} while (0)

__host__ __device__ constexpr int cl_grp(int c) { return c < 4 ? 8 + SMALLPOS : c < 36 ? (c - 4) & 7 : 8 + (c - 36) % 7 + ((c - 36) % 7 >= SMALLPOS); }
__host__ __device__ constexpr int cl_mem(int c) { return c < 4 ? c : c < 36 ? (c - 4) >> 3 : (c - 36) / 7; }
__host__ __device__ constexpr int role_j(int c) {
  return MAP == 0 ? (MC ? (c >> 1) & 7 : c & 7) : MAP == 1 ? c >> 4 : MAP == 2 ? ((c >> 6) << 2) | ((c >> 1) & 3)
       : MAP == 3 ? ((c >> 5) << 1) | ((c >> 2) & 1) : MAP == 4 ? ((c >> 3) & 3) * 2 + ((c >> 2) & 1)
       : MAP == 5 ? (cl_grp(c >> 1) >> 3) * 4 + cl_mem(c >> 1) : MAP == 6 ? (cl_grp(c >> 1) >> 2) * 2 + (cl_mem(c >> 1) & 1)
       : ((cl_grp(c >> 1) >> 1) & 3) * 2 + (cl_mem(c >> 1) & 1);
}
__host__ __device__ constexpr int role_rb(int c) {
  return MAP == 0 ? (MC ? (c >> 4) * 2 + (c & 1) : c >> 3) : MAP == 1 ? c & 15 : MAP == 2 ? ((c >> 3) & 7) * 2 + (c & 1)
       : MAP == 3 ? ((c >> 3) & 3) * 4 + (c & 3) : MAP == 4 ? (c >> 5) * 4 + (c & 3)
       : MAP == 5 ? (cl_grp(c >> 1) & 7) * 2 + (c & 1) : MAP == 6 ? (cl_grp(c >> 1) & 3) * 4 + (cl_mem(c >> 1) >> 1) * 2 + (c & 1)
       : ((cl_grp(c >> 1) >> 3) * 2 + (cl_grp(c >> 1) & 1)) * 4 + (cl_mem(c >> 1) >> 1) * 2 + (c & 1);
}

__device__ __forceinline__ uint32_t row_off(int rb, int wg, uint32_t t) { return (rb * 128 + wg + ((t >> 5) * 16 + (t & 15)) * 2) * (2 * DM); }

__device__ __forceinline__ const __nv_bfloat16* wo_src(const __nv_bfloat16* wo, int k, int u, int j) {
  const int ko = k < 512 ? (k >> 6) * 72 + (k & 63) : ((k >> 3) & 7) * 72 + 64 + (k & 7);
  return wo + ko * 576 + (u < 8 ? j * 64 + u * 8 : 512 + j * 8);
}

struct Params {
  const __nv_bfloat16 *x, *wqkv, *wo, *wg, *wu, *wd;
  __nv_bfloat16* out;
  uint8_t* scr;
  uint8_t* times;
  unsigned zero;
};

__cluster_dims__(2, 1, 1)
__global__ void __launch_bounds__(384, 1)
fused_kernel(const __grid_constant__ CUtensorMap map_x, const __grid_constant__ CUtensorMap map_wg,
             const __grid_constant__ CUtensorMap map_wu, const __grid_constant__ CUtensorMap map_wd, const Params P) {
  const int wg = __shfl_sync(0xffffffffu, threadIdx.x >> 7, 0);
  const int cta = blockIdx.x, rank = MC ? cta & 1 : 0, j = role_j(cta), rb = role_rb(cta);
  const uint32_t own = win();
  unsigned* const flags = (unsigned*)(P.scr + OFF_FLAGS);
  if (__shfl_sync(0xffffffffu, threadIdx.x >> 5, 0) == 11) {
    if (threadIdx.x == 352) {
#pragma unroll
      for (int i = 0; i < 14; i++) { mbar_init(bar_full(i), 1); mbar_init(bar_empty(i), MC && i < 12 ? 4 : 2); }
      mbar_init(bar_full(14), 1); mbar_init(bar_empty(14), 1);
      asm volatile("fence.mbarrier_init.release.cluster;" ::: "memory");
      if (smem_u32(smem_raw) != own + SB) asm volatile("trap;");
    }
    __syncwarp();
    bar_arrive(0, 384);
    if (MC) asm volatile("barrier.cluster.arrive.relaxed.aligned;" ::: "memory");
    if (threadIdx.x == 352) {
#pragma unroll 1
      for (int c = 0; c < 9; c++) {
        mbar_expect_tx(bar_full(c), SLOT);
        tma_3d(own + slot_addr(c), &map_x, c * 64, rb * 64, 0, own + bar_full(c));
      }
    }
  } else {
    const bool on = threadIdx.x < 324;
    const int k = rb * 36 + (on ? threadIdx.x / 36 : 0) * 4 + (threadIdx.x & 3), u = (threadIdx.x % 36) >> 2;
    const uint4* s = (const uint4*)(P.wqkv + k * 1728 + j * 72 + u * 8);
    const uint4 vk = ldg_line(s + 72), vv = ldg_line(s + 144);
    const unsigned ep0 = *(volatile unsigned*)&flags[(72 + cta) * 8];
    if (MC) asm volatile("barrier.cluster.arrive.relaxed.aligned;" ::: "memory");
    bar_sync(0, 384);
    uint8_t* d = P.scr + OFF_WPACK + j * 24 * PSLOT;
    if (on) {
      const uint32_t dkv = (k / 48) * PSLOT + u * 768 + (k % 48) * 16;
      st16(d, dkv, 0, vk.x, vk.y, vk.z, vk.w);
      st16(d, dkv, 9 * 768, vv.x, vv.y, vv.z, vv.w);
    }
    asm volatile("fence.proxy.async.global;" ::: "memory");
    bar_arrive(NB_PUB + 3, 384);
    if (threadIdx.x == 351) sts32(SM_EPOCH, ep0);
    if (wg == 2) bar_sync(NB_PUB + 1, 96);
  }
  __syncwarp();
  if (MC) asm volatile("barrier.cluster.wait.acquire.aligned;" ::: "memory");

  if (wg == 2) {
    asm volatile("setmaxnreg.dec.sync.aligned.u32 24;");
    const int pw = __shfl_sync(0xffffffffu, (threadIdx.x >> 5) & 3, 0), lane = threadIdx.x & 31;
    auto tile_col = [](int t, int h, int j) { return t < 9 ? j * 576 + t * 64 : (t == 9 && h) ? 512 : ((j + ((h ? 0x05760 : 0x04123) >> (4 * (t - 9)))) & 7) * 64; };
    auto prefetch_tile = [&](int t) {
#pragma unroll 1
      for (int b = rb; b < 18; b += 16) {
        const int h = b & 1, k = b >> 1;
        if (t < 9) w_tma_prefetch(h ? &map_wu : &map_wg, tile_col(t, h, j), k * 64);
        else if (t != 13 || !h) w_tma_prefetch(&map_wd, tile_col(t, h, j), j * 576 + k * 64);
      }
    };
    if (pw == 0) {
      {
        flag_wait(&flags[j * 8], (lds32(SM_EPOCH) + 1) * 16);
        TSP(7);
        asm volatile("fence.proxy.async.global;" ::: "memory");
        const uint8_t* wp = P.scr + OFF_WPACK + j * 24 * PSLOT;
        wp += rank * (PSLOT / 2);
        auto packed = [&](int sl, uint32_t par, int f) {
          mbar_wait(bar_empty(0) + sl * 8, par);
          w_bulk_load_mc(own + SB + rank * (PSLOT / 2) + sl * SLOT, wp + f * PSLOT, PSLOT / 2, own + bar_full(0) + sl * 8);
          w_expect_tx(own + bar_full(0) + sl * 8, PSLOT);
        };
        const uint32_t half = own + SB + rank * 8192;
#pragma unroll 1
        for (int L = 0; L < 2; L++) {
#pragma unroll 1
          for (int s = L ? 0 : -3; s < 21; s++) {
            if (s == 9 && L == 0) { flag_wait(&flags[(56 + j) * 8], (lds32(SM_EPOCH) + 1) * 16); asm volatile("fence.proxy.async.global;" ::: "memory"); }
            packed(s < 0 ? s + 12 : s < 9 ? s : s - 9, s < 0 || (s >= 9 && s < 18), s + 3);
          }
#pragma unroll 1
          for (int t = 0; t < 14; t++) {
            if (L * 14 + t + PF_AHEAD < 28) prefetch_tile((t + PF_AHEAD) % 14);
            const CUtensorMap* mp = t >= 9 ? &map_wd : rank ? &map_wu : &map_wg;
            const bool nar = t == 13;
            const int col = tile_col(t, nar ? 0 : rank, j);
            const uint32_t dst = nar ? own + SB : half, bytes = nar ? 8192 : SLOT;
            const int ra = t < 9 ? 0 : j * 576 + 320, rbs = t < 9 ? 0 : j * 576 - 192, rc = t < 9 ? 0 : j * 576;
#pragma unroll
            for (int k = 0; k < 9; k++) {
              mbar_wait(bar_empty(k), t & 1);
              if (!nar || rank == (k & 1)) w_tma_2d_mc(dst + k * SLOT, mp, col, (k < 3 ? ra : k < 8 ? rbs : rc) + k * 64, own + bar_full(k));
              w_expect_tx(own + bar_full(k), bytes);
            }
            if (t == 10 && L == 0) {
              w_l2_prefetch(P.scr + OFF_WPACK + j * 24 * PSLOT + rb * (24 * PSLOT / 16), 24 * PSLOT / 16);
#pragma unroll 1
              for (int s = 0; s < 3; s++) packed(9 + s, 1, s);
            }
          }
        }
        flags[(72 + cta) * 8] = lds32(SM_EPOCH) + 1;
      }
    } else if (pw < 3) {
      const int hw = pw - 1;
      const uint32_t ep = __shfl_sync(0xffffffffu, lds32(SM_EPOCH), 0);
      uint8_t* const sb = P.scr + (rb * 2 + hw) * STRM;
      const uint32_t xs = slot_addr(12) + hw * SLOT, fb = bar_full(12) + hw * 8;
      uint32_t hph = 0;
#pragma unroll 1
      for (int L = 0; L < 2; L++) {
        const uint32_t tag = ep * 2 + L + 1;
        bar_sync(NB_FREE + hw, 160);
        if (rb > 0) hint_wait(sb + OFF_HINT + 512 + j * 128, tag);
        uint32_t bad;
        do {
          if (rb > 0) {
            w_bulk_load(own + ytail(hw * 2), sb + OFF_HALO + (L * 8 + j) * 3072, 1536, own + bar_full(14) + hw * 128);
            w_bulk_load(own + ytail(hw * 2 + 1), sb + OFF_HALO + (L * 8 + j) * 3072 + 1536, 1536, own + bar_full(14) + hw * 128);
            w_expect_tx(own + bar_full(14) + hw * 128, 3072);
            mbar_wait(bar_full(14) + hw * 128, hph);
            hph ^= 1;
          }
          bad = 0;
#pragma unroll 1
          for (int c = 0; c < 3; c++) {
            uint32_t u[4] = {tag, 0, 0, 0}, v[4] = {tag, 0, 0, 0};
            if (rb > 0) { lds128(u, ytail(hw * 2) + c * 512 + lane * 16); lds128(v, ytail(hw * 2 + 1) + c * 512 + lane * 16); }
            bad |= (u[0] ^ tag) | (v[0] ^ tag);
#pragma unroll
            for (int i = 0; i < 3; i++) { sts32(xs + KSTG + (c * 3 + i) * 128 + lane * 4, u[i + 1]); sts32(xs + (c * 3 + i) * 128 + lane * 4, v[i + 1]); }
          }
        } while (__any_sync(0xffffffffu, bad != 0));
        bar_arrive(NB_HALO + hw, 160);
#pragma unroll 1
        for (int p = 0; p < 4; p++) {
          if (L == 0 && p == 3) flag_wait(flags + (40 + rb) * 8, (ep + 1) * 8);
          bar_sync(NB_FREE + hw, 160);
          TSH(L * 12 + p * 3);
          hint_wait(sb + OFF_HINT + (lane & 3) * 128, (ep * 13 + L * 7 + p + 3) * 8);
          TSH(L * 12 + p * 3 + 1);
          w_bulk_load(own + xs, sb + OFF_P + j * PSRC + (p & 1) * 16384, p ? 16384 : 8192, own + fb, (EVF & 8) && (p >= 2 || (EVF & 64)) ? EFP : ENP);
          if (p == 0) w_bulk_load(own + xs + 8192, sb + OFF_P + j * PSRC + 32768, 7168, own + fb);
          w_expect_tx(own + fb, p ? 16384 : 15360);
          TSH(L * 12 + p * 3 + 2);
        }
      }
    } else {
      auto clear = [&](int t) {
        const uint32_t so = rb * 2 * STRM + (threadIdx.x & 31) * 16;
#pragma unroll 1
        for (int i = 0; i < 18; i++) {
          if (EVF & 2) { st16e(P.scr, so + t * TILE + j * 9216 + i * 512, 0, 0, 0, 0, 0); st16e(P.scr, so + t * TILE + j * 9216 + i * 512, STRM, 0, 0, 0, 0); } else {
          st16(P.scr, so + t * TILE + j * 9216 + i * 512, 0, 0, 0, 0, 0);
          st16(P.scr, so + t * TILE + j * 9216 + i * 512, STRM, 0, 0, 0, 0); }
          __nanosleep(CLR_NS);
        }
        if (t != 1) {
          st16(P.scr, so + (t ? t - 1 : 0) * 4096 + j * 512, OFF_ST, 0, 0, 0, 0);
          st16(P.scr, so + (t ? t - 1 : 0) * 4096 + j * 512, OFF_ST + STRM, 0, 0, 0, 0);
        }
      };
      bar_sync(NB_PUB + 3, 384);
      if (lane == 0) flag_signal(&flags[j * 8]);
      TSP(5);
      bar_sync(NB_PUB + 2, 288);
      if (lane == 0) flag_signal(&flags[(56 + j) * 8]);
      TSP(4);
      __syncwarp();
#pragma unroll 1
      for (int t = 0; t < PF_AHEAD; t++) prefetch_tile(t);
#pragma unroll 1
      for (int L = 0; L < 2; L++) {
        timed_wait(bar_empty(13), L);
#pragma unroll 1
        for (int t = L ^ 1; t < 4 - 2 * L; t++) clear(t);
        __syncwarp();
        if (lane == 0 && L == 0) flag_signal(flags + (40 + rb) * 8);
      }
      timed_wait(bar_empty(12), 0);
      if (MC) asm volatile("barrier.cluster.arrive.relaxed.aligned;\nbarrier.cluster.wait.aligned;" ::: "memory");
    }
  } else {
    asm volatile("setmaxnreg.inc.sync.aligned.u32 240;");
    const int w = __shfl_sync(0xffffffffu, (threadIdx.x >> 5) & 3, 0);
    const bool leader = (threadIdx.x & 127) == 0;
    const Rel rel{MC ? (threadIdx.x & 95) == 0 : leader, MC ? cta_window(w & 1) : 0};
    uint8_t* const sb = P.scr + (rb * 2 + wg) * STRM;
    uint8_t* const hint = sb + OFF_HINT + w * 128;
    auto hint_target = [](int e) { return (lds32(SM_EPOCH) * 13 + e + 1) * 8; };
    TS(0);
    uint32_t a[144];
#pragma unroll 1
    for (int L = 0; L < 2; L++) {
      uint32_t m0, m1; float r0, r1;
      if (L == 0) {
        Stats st;
        const int lane = tid_() & 31, g = lane >> 2;
        const int row = w * 16 + (lane & 15);
        const uint32_t ra = SB + wg * 8192 + row * 128;
        const uint32_t pt = tid_(), pu = (pt % 36) >> 2, pk = rb * 36 + (pt < 108 ? pt / 36 : 0) * 4 + (pt & 3);
        uint4 pv[3];
#pragma unroll
        for (int i = 0; i < 3; i++) pv[i] = ldg_line(wg ? wo_src(P.wo, pk + i * 12, pu, j) : P.wqkv + (pk + i * 12) * 1728 + j * 72 + pu * 8);
#pragma unroll
        for (int c = 0; c < 9; c++) {
          mbar_wait(bar_full(c), 0);
          if (c == 0) TS(60); if (c == 8) TS(62);
#pragma unroll
          for (int kk = 0; kk < 4; kk++) ldsm4(&a[c * 16 + kk * 4], ra + (((kk * 2 + (lane >> 4)) ^ (row & 7)) << 4) + c * SLOT);
          if (c == 8) {
            uint32_t y[18], z[4];
#pragma unroll
            for (int i = 0; i < 4; i++) ldsm4(&y[4 * i], ra + (((i * 2 + (lane >> 4)) ^ (row & 7)) << 4) + j * SLOT);
            ldsm4(z, ra + ((j ^ (row & 7)) << 4) + 8 * SLOT);
            y[16] = z[0]; y[17] = z[1];
            bar_sync(NB_WG + wg, 128);
#pragma unroll
            for (int i = 0; i < 9; i++) rel(i);
            if (pt < 108) {
#pragma unroll
              for (int i = 0; i < 3; i++) {
                const uint32_t k = pk + i * 12;
                st16(P.scr, (j * 24 + wg * 6 + k / 96) * PSLOT + pu * 1536 + (k % 96) * 16, OFF_WPACK + 12 * PSLOT, pv[i].x, pv[i].y, pv[i].z, pv[i].w);
              }
            }
            asm volatile("fence.proxy.async.global;" ::: "memory");
            bar_arrive(NB_PUB + 2, 288);
            store_own(y, sb, OFF_X2, j, tid_());
          }
#pragma unroll
          for (int kk = 0; kk < 4; kk++) st.add16(&a[c * 16 + kk * 4]);
        }
        const int dl = (lane & ~3) | (g >> 1);
        ln_scalars(st.s[0], __shfl_sync(0xffffffffu, st.sq0(g), dl), m0, r0, P.zero);
        ln_scalars(st.s[2], __shfl_sync(0xffffffffu, st.sq1(g), dl), m1, r1, P.zero);
      } else {
#pragma unroll
        for (int i = 4 * N_UP; i < 144; i++) a[i] = 0;
        hint_wait(hint, hint_target(6));
        TS(61);
        gather_ln<3 * D_KV>(a, sb, OFF_X2, 8192, m0, m1, r0, r1, P.zero);
      }
      TS(1 + L * 20);
      uint32_t kf[18], qf[18];
      {
        float acc[72];
        if (wg == 1) bar_sync(NB_ORD1, 256);
        mma_pass<144, PS_KV, 3, 256, D_KV, true>(acc, a, DESC_KV, 1, rel, wg == 0 ? NB_ORD1 : -1, sb, OFF_X2, L ^ 1, m0, m1, ytail(wg * 2));
        r0 = ln_rstd(r0, acc[0], P.zero); r1 = ln_rstd(r1, acc[0], P.zero);
        uint32_t vf[18];
#pragma unroll
        for (int c = 0; c < 9; c++) {
          kf[c] = pack_bf16(acc[4 * c] * r0, acc[4 * c + 1] * r0);
          kf[9 + c] = pack_bf16(acc[4 * c + 2] * r1, acc[4 * c + 3] * r1);
          vf[c] = pack_bf16(acc[36 + 4 * c] * r0, acc[36 + 4 * c + 1] * r0);
          vf[9 + c] = pack_bf16(acc[36 + 4 * c + 2] * r1, acc[36 + 4 * c + 3] * r1);
        }
        TS(2 + L * 20);
        const uint32_t l16 = (tid_() & 31) * 16, xs = slot_addr(12) + wg * SLOT + w * 1152;
#pragma unroll
        for (int i = 0; i < 4; i++) stsm4(xs + w * 1152 + 1152 + i * 512 + l16, vf[4 * i], vf[4 * i + 1], vf[4 * i + 2], vf[4 * i + 3]);
        sts32(xs + w * 1152 + 1152 + 2048 + l16 / 4, vf[16]); sts32(xs + w * 1152 + 1152 + 2176 + l16 / 4, vf[17]);
        if (w < 3) {
          stsm4(xs + KSTG + 1152 + l16, kf[9], kf[10], kf[11], kf[12]);
          stsm4(xs + KSTG + 1152 + 512 + l16, kf[13], kf[14], kf[15], kf[16]);
          sts32(xs + KSTG + 1152 + 1024 + l16 / 4, kf[17]);
        } else if (rb < 15) {
          const uint32_t tag = lds32(SM_EPOCH) * 2 + L + 1;
          const uint32_t ho = l16 + (L * 8 + j) * 3072;
#pragma unroll
          for (int c = 0; c < 3; c++) {
            st16(sb, ho, 2 * STRM + OFF_HALO + c * 512, tag, kf[9 + 3 * c], kf[10 + 3 * c], kf[11 + 3 * c]);
            st16(sb, ho, 2 * STRM + OFF_HALO + 1536 + c * 512, tag, vf[9 + 3 * c], vf[10 + 3 * c], vf[11 + 3 * c]);
          }
          hint_post(sb + 2 * STRM + OFF_HINT + 512 + j * 128);
        }
      }
      lds128(a, ytail(wg * 2) + tid_() * 16);
      bar_arrive(NB_FREE + wg, 160);
      uint32_t kh[12], vp[20], v1[12];
      {
        float acc[36];
        if (wg == 1) bar_sync(NB_ORD1, 256);
        mma_pass<72, PS_Q, 6, 256, 0, false, false>(acc, a, DESC_Q, 0, rel, -1, nullptr, 0, 0, 0, 0, 0, [&]() {
          bar_sync(NB_HALO + wg, 160);
#pragma unroll
          for (int i = 0; i < 3; i++) ldsm4(&kh[4 * i], slot_addr(12) + wg * SLOT + w * 640 + tid_() * 16 + KSTG + i * 512);
          const uint32_t l = tid_() & 31, vb = slot_addr(12) + wg * SLOT + w * 2304;
#pragma unroll
          for (int i = 0; i < 5; i++) ldsm4t(&vp[4 * i], vb + (l & 8) * 144 + (l & 16) * 8 + (l & 7) * 16 + i * 256);
#pragma unroll
          for (int i = 0; i < 3; i++) ldsm4t(&v1[4 * i], vb + 2304 + l * 16 + i * 512);
        });
#pragma unroll
        for (int i = 0; i < 18; i++) qf[i] = pack_bf16(acc[2 * i], acc[2 * i + 1]);
      }
      TS(3 + L * 20);
      uint32_t xr[18];
      {
        const int tid = tid_(), g = (tid >> 2) & 7, q = tid & 3;
        const bool nohalo = (rb == 0 && w == 0);
        const bool le0 = 2 * q <= g, le1 = 2 * q + 1 <= g;
        const uint32_t M = (le0 ? 0xffffu : 0u) | (le1 ? 0xffff0000u : 0u);
        const float sc0 = r0 * (0.23570226039551584f * 1.4426950408889634f), sc1 = r1 * (0.23570226039551584f * 1.4426950408889634f);
        float l[16], t[8];
#pragma unroll
        for (int h = 0; h < 4; h++) {
          const uint32_t qa0 = q >= h ? qf[4 * h] : 0u, qa1 = q >= h ? qf[4 * h + 1] : 0u;
          const uint32_t qc0 = q <= h ? qf[4 * h + 4] : 0u, qc1 = q <= h ? qf[4 * h + 5] : 0u;
          float sm[4] = {0, 0, 0, 0}, s0[4] = {0, 0, 0, 0}, s1[4] = {0, 0, 0, 0};
          mma16816(s0, qa0, qa1, qf[4 * h + 2], qf[4 * h + 3], kf[2 * h], kf[2 * h + 1]);
          mma16816(s1, qa0, qa1, qf[4 * h + 2], qf[4 * h + 3], kf[9 + 2 * h], kf[10 + 2 * h]);
          mma16816(sm, qa0, qa1, qf[4 * h + 2], qf[4 * h + 3], kh[2 * h], kh[2 * h + 1]);
          mma1688(s0, qc0, qc1, kf[2 * h + 2]);
          mma1688(s1, qc0, qc1, kf[11 + 2 * h]);
          mma1688(sm, qc0, qc1, kh[2 * h + 2]);
          if (nohalo) sm[0] = sm[1] = -3e38f;
          l[4 * h] = le0 ? s0[0] : sm[0]; l[4 * h + 1] = le1 ? s0[1] : sm[1];
          l[4 * h + 2] = le0 ? s1[2] : s0[2]; l[4 * h + 3] = le1 ? s1[3] : s0[3];
        }
#pragma unroll
        for (int i = 0; i < 8; i++) t[i] = fmaxf(l[2 * i], l[2 * i + 1]);
        TS(14 + L * 20);
#pragma unroll
        for (int i = 0; i < 8; i++) t[i] = fmaxf(t[i], __shfl_xor_sync(0xffffffffu, t[i], 1));
#pragma unroll
        for (int i = 0; i < 8; i++) t[i] = fmaxf(t[i], __shfl_xor_sync(0xffffffffu, t[i], 2)) * ((i & 1) ? sc1 : sc0);
#pragma unroll
        for (int i = 0; i < 8; i++) {
          const float sc = (i & 1) ? sc1 : sc0;
          l[2 * i] = ex2(fmaf(l[2 * i], sc, -t[i])); l[2 * i + 1] = ex2(fmaf(l[2 * i + 1], sc, -t[i])); t[i] = l[2 * i] + l[2 * i + 1];
        }
#pragma unroll
        for (int i = 0; i < 8; i++) t[i] += __shfl_xor_sync(0xffffffffu, t[i], 1);
#pragma unroll
        for (int i = 0; i < 8; i++) t[i] += __shfl_xor_sync(0xffffffffu, t[i], 2);
        uint32_t pf[16], pz[8];
#pragma unroll
        for (int i = 0; i < 8; i++) {
          float r; asm("rcp.approx.ftz.f32 %0, %1;" : "=f"(r) : "f"(t[i]));
          const uint32_t p = pack_bf16(l[2 * i] * r, l[2 * i + 1] * r);
          pf[2 * i] = p & ~M; pf[2 * i + 1] = p & M; pz[i] = p & P.zero;
        }
#pragma unroll
        for (int c = 0; c < 9; c++) {
          const int h = c == 8 ? 3 : c >> 1;
          float o[4] = {0, 0, 0, 0};
          mma16816(o, pf[4 * h], pz[2 * h], pf[4 * h + 1], pf[4 * h + 2], vp[2 * c], vp[2 * c + 1]);
          mma1688(o, pz[2 * h + 1], pf[4 * h + 3], v1[c]);
          if (c == 2 || c == 4 || c == 6) {
            float e[4] = {0, 0, 0, 0};
            mma16816(e, pf[4 * h - 4], pz[2 * h - 2], pf[4 * h - 3], pf[4 * h - 2], vp[2 * c], vp[2 * c + 1]);
            mma1688(e, pz[2 * h - 1], pf[4 * h - 1], v1[c]);
            const uint32_t u = pack_bf16(e[0], e[1]), v = pack_bf16(e[2], e[3]);
            qf[2 * c] = q < h ? u : pack_bf16(o[0], o[1]); qf[2 * c + 1] = q < h ? v : pack_bf16(o[2], o[3]);
          } else {
            qf[2 * c] = pack_bf16(o[0], o[1]); qf[2 * c + 1] = pack_bf16(o[2], o[3]);
          }
        }
        {
          uint32_t x = 0;
#pragma unroll
          for (int i = 0; i < 18; i += 2) x |= qf[i];
          if (AORD < 2) bar_arrive_if(AORD ? wg : 1, NB_ORD1 - wg + (x & P.zero), 256);
        }
        store_own(qf, sb, OFF_O, j, tid);
        hint_post(hint);
        if (AORD == 2 || (AORD && !wg)) bar_arrive(NB_ORD1 - wg, 256);
        load_own(xr, sb, OFF_X2, j);
      }
      TS(4 + L * 20);
      {
        hint_wait(hint, hint_target(L * 7));
        TS(5 + L * 20);
        load_frags<N_WO>(a, sb, OFF_O, tid_());
        float acc[36];
        if (wg == 0) bar_sync(NB_ORD0, 256);
        load_frags<N_UP, N_WO>(a, sb, OFF_O, tid_());
        TS(19 + L * 20);
        mma_pass<72, PS_WO, 6, 256, D_WO, false>(acc, a, DESC_Q, 0, rel, -1, sb, OFF_O);
        TS(6 + L * 20);
#pragma unroll
        for (int c = 0; c < 9; c++) {
          xr[2 * c] = bf2_add(xr[2 * c], pack_bf16(acc[4 * c], acc[4 * c + 1]));
          xr[2 * c + 1] = bf2_add(xr[2 * c + 1], pack_bf16(acc[4 * c + 2], acc[4 * c + 3]));
        }
        store_own(xr, sb, L * 3 * TILE, j, tid_());
        RowStats rs;
        rs.add<18>(xr);
        rs.store(sb, L * 4096 + j * 128, tid_());
        hint_post(hint);
      }
      TS(16 + L * 20);
      hint_wait(hint, hint_target(L * 7 + 1));
      TS(15 + L * 20);
      gather_ln<4 * D_T0>(a, sb, L * 3 * TILE, L * 4096, m0, m1, r0, r1, P.zero);
      TS(7 + L * 20);
      const uint32_t hb = OFF_H + j * 24576;
      {
        float ka0, kb0, kc0, ka1, kb1, kc1;
        float acc[64];
        uint32_t hf[16];
        auto geglu = [&](auto chains, uint32_t hsm) {
          constexpr int CH = decltype(chains)::value & 15;
          float r[32];
#pragma unroll
          for (int e = 0; e < 32; e++) {
            float x = acc[e];
            if (e >= CH) x = __uint_as_float(__float_as_uint(x) ^ (__float_as_uint(r[e - CH]) & P.zero));
            if (decltype(chains)::value > 15 && e < 20) {
              const uint32_t ad = (e < 8 ? slot_addr(12) + e * 2048 + wg * 8192 : slot_addr(7 + (e >> 2)) + (e & 3) * 2048) + hsm;
              lds128(&a[48 + 4 * e], e >= CH ? ad ^ (__float_as_uint(r[e - CH]) & P.zero) : ad);
            }
            const bool hi = e & 2;
            float t = x * fmaf(x * x, hi ? kb1 : kb0, hi ? ka1 : ka0);
            asm("tanh.approx.f32 %0, %0;" : "+f"(t));
            const float u = x * acc[32 + e] * (hi ? kc1 : kc0);
            r[e] = fmaf(u, t, u);
            if (e & 1) hf[e >> 1] = pack_bf16(r[e - 1], r[e]);
          }
        };
        if (wg == 1) bar_sync(NB_ORD1, 256);
        mma_pass<128, PS_FF, 4, 2048, D_T0, true>(acc, a, DESC_SW128, 1, rel, NB_ORD1 - wg, sb, L * 3 * TILE, 0, m0, m1);
        if (tid_() == 0) mbar_arrive(bar_empty(13));
        TS(8 + L * 20);
        r0 = ln_rstd(r0, acc[0], P.zero); r1 = ln_rstd(r1, acc[0], P.zero);
        ka0 = 0.7978845608028654f * r0; kb0 = 0.035677408136300125f * r0 * r0 * r0; kc0 = 0.5f * r0 * r0;
        ka1 = 0.7978845608028654f * r1; kb1 = 0.035677408136300125f * r1 * r1 * r1; kc1 = 0.5f * r1 * r1;
#pragma unroll 1
        for (int t = 0; t < 8; t++) {
          geglu(IntC<2>(), 0);
          const uint32_t t16 = tid_() * 16;
          if (t < 5) {
            const uint32_t d = (t < 2 ? slot_addr(12) + wg * SLOT + t * 8192 : slot_addr(7) + t * SLOT + wg * 8192) + t16;
#pragma unroll
            for (int i = 0; i < 4; i++)
              sts128(d + i * 2048, hf[4 * i], hf[4 * i + 1], hf[4 * i + 2], hf[4 * i + 3]);
            if (t == 4) asm volatile("fence.proxy.async.shared::cta;" ::: "memory");
          } else {
#pragma unroll
            for (int i = 0; i < 4; i++) { if (EVF & 32) st16e(sb, hb + (t - 5) * 8192 + t16, i * 2048, hf[4 * i], hf[4 * i + 1], hf[4 * i + 2], hf[4 * i + 3]); else st16(sb, hb + (t - 5) * 8192 + t16, i * 2048, hf[4 * i], hf[4 * i + 1], hf[4 * i + 2], hf[4 * i + 3]); }
          }
          bar_sync(NB_ORD0 + wg, 256);
          mma_pass<128, PS_FF, 4, 2048, 0, false, true>(acc, a, DESC_SW128, t & 1, rel, NB_ORD1 - wg, sb, hb + t16, t == 7);
        }
        TS(9 + L * 20);
        const uint32_t hsm = wg * 8192 + tid_() * 16;
        geglu(IntC<16 + CH_LAST>(), hsm);
#pragma unroll
        for (int i = 0; i < 16; i++) a[128 + i] = hf[i];
      }
      TS(10 + L * 20);
      {
        const uint32_t xs = slot_addr(12) + wg * SLOT;
        auto verify = [&](int p, uint32_t t16) {
          mbar_wait(bar_full(12) + wg * 8, p & 1);
          TS(71 + L * 32 + p * 5);
          const uint32_t ta = p < 2, tb = (p & 1) ? ta : L ^ 1, nb = p ? 4 : 7, sh = p == 0;
          uint32_t m = 0;
#pragma unroll
          for (int s = 0; s < 4; s++) m |= (lds32(xs + s * 2048 + t16) ^ ta) | (lds32(xs + 8192 + ((s * 2048 + t16) >> sh)) ^ tb);
          if (p == 0) {
#pragma unroll
            for (int s = 4; s < 7; s++) m |= lds32(xs + 8192 + s * 1024 + t16 / 2) ^ tb;
          }
          if (__any_sync(0xffffffffu, m & 1)) {
#pragma unroll 1
            for (int s = 0; s < 4 + nb; s++) {
              const bool nar = sh && s >= 4;
              const uint32_t o = nar ? 4096 + s * 1024 + t16 / 2 : s * 2048 + t16;
              uint32_t v[4] = {0, 0, 0, 0};
              do {
                if (nar) ld8(v, sb, j * PSRC + o, OFF_P + 32768 - 8192);
                else ld16(v, sb, j * PSRC + (p & 1) * 16384 + o, OFF_P);
              } while (__any_sync(0xffffffffu, (v[0] ^ (s < 4 ? ta : tb)) & 1));
              sts64(xs + o, v[0], v[1]);
              if (!nar) sts64(xs + o + 8, v[2], v[3]);
            }
            asm volatile("fence.proxy.async.shared::cta;" ::: "memory");
          }
        };
        uint32_t t16 = (a[142] | a[143]) & P.zero;
#pragma unroll 1
        for (int p = 0; p < 4; p++) {
          float acc[64];
          bar_sync(NB_ORD0 + wg + (p ? 0 : t16), 256);
          TS(64 + L * 32 + p * 5);
          if (p == 0) { rel(9); rel(10); rel(11); }
          mma_pass<128, PS_FF, 4, 2048, 0, false, false>(acc, a, DESC_SW128, p & 1, rel, NB_ORD1 - wg, nullptr, 0, 0, 0, 0, 0, [&]() {
            t16 = tid_() * 16;
            if (p) verify(p - 1, t16);
          });
          TS(65 + L * 32 + p * 5);
          if (p == 1 || p == 2) add_piece<false>(acc, xs + t16);
          const uint32_t oa = ((j + (p < 3 ? 1 : 4)) & 7) * PSRC + (p & 1) * 16384 + t16;
#pragma unroll
          for (int i = 0; i < 4; i++)
            st16(sb, oa, OFF_P + i * 2048, (pack_bf16(acc[8 * i], acc[8 * i + 1]) & ~1u) | (p < 2), pack_bf16(acc[8 * i + 2], acc[8 * i + 3]),
                 pack_bf16(acc[8 * i + 4], acc[8 * i + 5]), pack_bf16(acc[8 * i + 6], acc[8 * i + 7]));
          if (p == 0) {
#pragma unroll
            for (int i = 0; i < 8; i++)
              send8(sb, j * 1024 + t16 / 2, OFF_P + 32768 + i * PSRC, xs + 15360 + t16 / 2, i, j,
                    (pack_bf16(acc[32 + 4 * i], acc[33 + 4 * i]) & ~1u) | (L ^ 1), pack_bf16(acc[34 + 4 * i], acc[35 + 4 * i]));
          } else {
            if (p == 2) add_piece<false>(acc + 32, xs + 8192 + t16);
            const uint32_t ob = ((j + (p < 3 ? 7 : 5)) & 7) * PSRC + (p & 1) * 16384 + t16, tb = p == 2 ? L ^ 1 : p < 2;
#pragma unroll
            for (int i = 4; i < 8; i++)
              st16(sb, ob, OFF_P + i * 2048, (pack_bf16(acc[8 * i], acc[8 * i + 1]) & ~1u) | tb, pack_bf16(acc[8 * i + 2], acc[8 * i + 3]),
                   pack_bf16(acc[8 * i + 4], acc[8 * i + 5]), pack_bf16(acc[8 * i + 6], acc[8 * i + 7]));
          }
          hint_post(hint);
          TS(68 + L * 32 + p * 5);
          if (p == 1) {
            float s0 = 0.f, s1 = 0.f, s2 = 0.f, s3 = 0.f;
#pragma unroll
            for (int s = 0; s < 8; s++) {
              uint32_t u, v;
              lds64(u, v, xs + 8192 + s * 1024 + t16 / 2);
              s0 += bf_lo(u); s1 += bf_hi(u); s2 += bf_lo(v); s3 += bf_hi(v);
            }
            sts64(ytail(wg * 2) + t16 / 2, pack_bf16(s0, s1), pack_bf16(s2, s3));
          }
          if (p < 3) bar_arrive(NB_FREE + wg, 160);
          TS(67 + L * 32 + p * 5);
        }
        float acc[32];
        add_piece<true>(acc, xs + t16);
        add_piece<false>(acc, xs + 8192 + t16);
        bar_arrive(NB_FREE + wg, 160);
        load_own(xr, sb, L * 3 * TILE, j);
        bar_sync(NB_ORD0 + wg, 256);
        TS(84 + L * 32);
        uint32_t t, yn[2];
        mma_pass<64, PS_FFA, 4, 2048, 0, false, false>(acc, a, DESC_SW128, 0, rel, wg ? -1 : NB_ORD1, nullptr, 0, 0, 0, 0, 0, [&]() {
          t = tid_();
          lds64(yn[0], yn[1], ytail(wg * 2) + t * 8);
          mbar_wait(bar_full(12) + wg * 8, 1);
#pragma unroll
          for (int i = 0; i < 8; i++) lds128(&a[4 * i], xs + i * 2048 + t * 16);
        });
        TS(11 + L * 20);
        while (true) {
          uint32_t m = 0;
#pragma unroll
          for (int i = 0; i < 8; i++) m |= a[4 * i];
          if (!__any_sync(0xffffffffu, m & 1)) break;
#pragma unroll
          for (int i = 0; i < 8; i++) ld16(&a[4 * i], sb, j * PSRC + t * 16, OFF_P + 16384 + i * 2048);
        }
        TS(12 + L * 20);
#pragma unroll
        for (int i = 0; i < 18; i++)
          xr[i] = bf2_add(xr[i], i < 16 ? pack_bf16(acc[2 * i] + (bf_lo(a[i]) + bf_lo(a[16 + i])), acc[2 * i + 1] + (bf_hi(a[i]) + bf_hi(a[16 + i]))) : yn[i - 16]);
        TS(18 + L * 20);
        if (L == 0) {
          store_own(xr, sb, OFF_X2, j, t);
          RowStats rs;
          rs.add<18>(xr);
          rs.store(sb, 8192 + j * 128, t);
          hint_post(hint);
        } else {
          const uint32_t l = t & 31, wb = xs + w * 512;
          __syncwarp();
#pragma unroll
          for (int i = 0; i < 4; i++) stsm4(wb + i * 2048 + (l & 24) * 16 + (((l & 7) ^ (i * 2 + (l >> 4))) << 4), xr[4 * i], xr[4 * i + 1], xr[4 * i + 2], xr[4 * i + 3]);
          stsm4(wb + 8192 + l * 16, xr[16], xr[17], 0, 0);
          __syncwarp();
          uint8_t* op = (uint8_t*)P.out + row_off(rb, wg, w * 32 + (l >> 3)) + j * 128 + (l & 7) * 16;
#pragma unroll
          for (int i = 0; i < 4; i++) {
            uint32_t r[4];
            lds128(r, wb + ((l & 6) << 10) + ((l & 1) * 2 + (i >> 1)) * 128 + (((((i & 1) * 4 + (l >> 3)) ^ l) & 7) << 4));
            *(uint4*)(op + i * 16 * DM) = make_uint4(r[0], r[1], r[2], r[3]);
          }
          uint32_t r[4];
          lds128(r, wb + 8192 + l * 16);
          if (l < 16) *(uint4*)((uint8_t*)P.out + row_off(rb, wg, t) + 1024 + j * 16) = make_uint4(r[0], r[1], r[2], r[3]);
        }
      }
      TS(13 + L * 20);
    }
    bar_sync(NB_WG + wg, 128);
    if (tid_() == 0) mbar_arrive(bar_empty(12));
  }
}

typedef CUresult (*EncodeFn)(CUtensorMap*, CUtensorMapDataType, cuuint32_t, void*, const cuuint64_t*, const cuuint64_t*, const cuuint32_t*,
                             const cuuint32_t*, CUtensorMapInterleave, CUtensorMapSwizzle, CUtensorMapL2promotion, CUtensorMapFloatOOBfill);

void encode(EncodeFn fn, CUtensorMap* m, const void* p, int rank, const cuuint64_t* dims, const cuuint64_t* str, const cuuint32_t* box) {
  const cuuint32_t es[3] = {1, 1, 1};
  fn(m, CU_TENSOR_MAP_DATA_TYPE_BFLOAT16, rank, const_cast<void*>(p), dims, str, box, es, CU_TENSOR_MAP_INTERLEAVE_NONE,
     CU_TENSOR_MAP_SWIZZLE_128B, CU_TENSOR_MAP_L2_PROMOTION_L2_256B, CU_TENSOR_MAP_FLOAT_OOB_FILL_NONE);
}

}

extern "C" void kernel_launch(void* const* d_in, const int* in_sizes, int n_in, void* d_out, int out_size) {
  (void)in_sizes; (void)n_in; (void)out_size;
  Params P;
  P.x = (const __nv_bfloat16*)d_in[0]; P.wqkv = (const __nv_bfloat16*)d_in[1]; P.wo = (const __nv_bfloat16*)d_in[2];
  P.wg = (const __nv_bfloat16*)d_in[4]; P.wu = (const __nv_bfloat16*)d_in[5]; P.wd = (const __nv_bfloat16*)d_in[6];
  P.out = (__nv_bfloat16*)d_out; P.zero = 0;
  cudaGetSymbolAddress((void**)&P.scr, g_scr);
  void* fnp = nullptr; cudaDriverEntryPointQueryResult qr;
  cudaGetDriverEntryPoint("cuTensorMapEncodeTiled", &fnp, cudaEnableDefault, &qr);
  EncodeFn fn = (EncodeFn)fnp;
  CUtensorMap mx, mg, mu, md;
  { const cuuint64_t dims[3] = {DM, SEQ / 2, 2}, str[2] = {DM * 4, DM * 2}; const cuuint32_t box[3] = {64, 64, 2}; encode(fn, &mx, P.x, 3, dims, str, box); }
  { const cuuint64_t dims[2] = {DFF, DM}, str[1] = {DFF * 2}; const cuuint32_t box[2] = {64, 64}; encode(fn, &mg, P.wg, 2, dims, str, box); encode(fn, &mu, P.wu, 2, dims, str, box); }
  { const cuuint64_t dims[2] = {DM, DFF}, str[1] = {DM * 2}; const cuuint32_t box[2] = {64, 64}; encode(fn, &md, P.wd, 2, dims, str, box); }
  cudaFuncSetAttribute(fused_kernel, cudaFuncAttributeMaxDynamicSharedMemorySize, SMEM_BYTES);
  fused_kernel<<<128, 384, SMEM_BYTES, cudaStreamPerThread>>>(mx, mg, mu, md, P);
}
```

```cpp
#include <cuda_runtime.h>
#include <cuda_bf16.h>
#include <cuda.h>
#include <stdint.h>

#define TIMING 0
#define TRACE 0

namespace {

constexpr int SEQ = 2048, DM = 576, DFF = 4608;
constexpr int KV_LEAD = 5;
constexpr int D_KV = 6, D_WO = 3, D_T0 = 5;
constexpr int N_UP = 26, N_WO = 12;
constexpr int PF_AHEAD = 3;
constexpr int CH_LAST = 3;
constexpr uint32_t SB = 1024;
constexpr uint32_t SLOT = 16384;
constexpr uint32_t PSLOT = 13824;
constexpr uint32_t BARS = SB + 14 * SLOT;
constexpr int SMEM_BYTES = 14 * SLOT + 256 + 2560 + (TRACE ? 256 : 0);
__host__ __device__ constexpr uint32_t slot_addr(int s) { return SB + s * SLOT; }
__host__ __device__ constexpr uint32_t bar_full(int s) { return BARS + 8 * s; }
__host__ __device__ constexpr uint32_t bar_empty(int s) { return BARS + 128 + 8 * s; }
enum { NB_ORD0 = 1, NB_ORD1 = 2, NB_WG = 3  , NB_HALO = 5  , NB_FREE = 7  , NB_PUB = 9   };
constexpr uint32_t SM_EPOCH = BARS + 120;
__host__ __device__ constexpr uint32_t ytail(uint32_t k) { return k < 3 ? slot_addr(9) + PSLOT + k * SLOT : BARS + 256; }
constexpr uint32_t KSTG = 9 * 1152;

constexpr uint32_t TILE = 36 * 2048;
constexpr uint32_t OFF_X1 = 0  , OFF_O = TILE, OFF_X2 = 2 * TILE, OFF_ST = 4 * TILE  ;
constexpr uint32_t PSRC = 2 * 16384 + 7 * 1024;
constexpr uint32_t OFF_P = OFF_ST + 3 * 4096, OFF_HALO = OFF_P + 8 * PSRC  , OFF_HINT = OFF_HALO + 2 * 8 * 3072  ,
                   OFF_H = OFF_HINT + 16 * 128  , STRM = OFF_H + 8 * 24576;
constexpr uint32_t OFF_WPACK = 32 * STRM, OFF_FLAGS = OFF_WPACK + 8 * 24 * PSLOT;
__device__ __align__(1024) uint8_t g_scr[OFF_FLAGS + (8 + 64 + 128) * 32];

__device__ __forceinline__ uint32_t smem_u32(const void* p) { return (uint32_t)__cvta_generic_to_shared(p); }
extern __shared__ __align__(1024) uint8_t smem_raw[];
__device__ __forceinline__ uint32_t win() { return (blockIdx.x & 1) << 24; }
#define SA(A, W) ".reg .u32 sa;\nadd.u32 sa, " A ", " W ";\n"
__device__ __forceinline__ void mbar_init(uint32_t bar, uint32_t cnt) { asm volatile("{\n" SA("%0", "%2") "mbarrier.init.shared::cta.b64 [sa], %1;\n}" ::"r"(bar), "r"(cnt), "r"(win())); }
__device__ __forceinline__ void mbar_expect_tx(uint32_t bar, uint32_t bytes) { asm volatile("{\n" SA("%0", "%2") "mbarrier.arrive.expect_tx.shared::cta.b64 _, [sa], %1;\n}" ::"r"(bar), "r"(bytes), "r"(win()) : "memory"); }
__device__ __forceinline__ void mbar_arrive(uint32_t bar) { asm volatile("{\n" SA("%0", "%1") "mbarrier.arrive.shared::cta.b64 _, [sa];\n}" ::"r"(bar), "r"(win()) : "memory"); }
__device__ __forceinline__ uint32_t lds32(uint32_t a) { uint32_t v; asm volatile("{\n" SA("%1", "%2") "ld.shared.u32 %0, [sa];\n}" : "=r"(v) : "r"(a), "r"(win()) : "memory"); return v; }
__device__ __forceinline__ void lds64(uint32_t& x, uint32_t& y, uint32_t a) { asm volatile("{\n" SA("%2", "%3") "ld.shared.v2.u32 {%0,%1}, [sa];\n}" : "=r"(x), "=r"(y) : "r"(a), "r"(win()) : "memory"); }
__device__ __forceinline__ void lds128(uint32_t* v, uint32_t a) {
  asm volatile("{\n" SA("%4", "%5") "ld.shared.v4.u32 {%0,%1,%2,%3}, [sa];\n}" : "=r"(v[0]), "=r"(v[1]), "=r"(v[2]), "=r"(v[3]) : "r"(a), "r"(win()) : "memory");
}
__device__ __forceinline__ void stsm4(uint32_t a, uint32_t x, uint32_t y, uint32_t z, uint32_t w) {
  asm volatile("{\n" SA("%0", "%5") "stmatrix.sync.aligned.m8n8.x4.shared.b16 [sa], {%1,%2,%3,%4};\n}" ::"r"(a), "r"(x), "r"(y), "r"(z), "r"(w), "r"(win()) : "memory");
}
__device__ __forceinline__ void ldsm4(uint32_t* v, uint32_t a) {
  asm volatile("{\n" SA("%4", "%5") "ldmatrix.sync.aligned.m8n8.x4.shared.b16 {%0,%1,%2,%3}, [sa];\n}" : "=r"(v[0]), "=r"(v[1]), "=r"(v[2]), "=r"(v[3]) : "r"(a), "r"(win()) : "memory");
}
__device__ __forceinline__ void ldsm4t(uint32_t* v, uint32_t a) {
  asm volatile("{\n" SA("%4", "%5") "ldmatrix.sync.aligned.m8n8.x4.trans.shared.b16 {%0,%1,%2,%3}, [sa];\n}" : "=r"(v[0]), "=r"(v[1]), "=r"(v[2]), "=r"(v[3]) : "r"(a), "r"(win()) : "memory");
}
__device__ __forceinline__ void sts32(uint32_t a, uint32_t x) { asm volatile("{\n" SA("%0", "%2") "st.shared.u32 [sa], %1;\n}" ::"r"(a), "r"(x), "r"(win()) : "memory"); }
__device__ __forceinline__ void sts64(uint32_t a, uint32_t x, uint32_t y) { asm volatile("{\n" SA("%0", "%3") "st.shared.v2.u32 [sa], {%1,%2};\n}" ::"r"(a), "r"(x), "r"(y), "r"(win()) : "memory"); }
__device__ __forceinline__ void sts128(uint32_t a, uint32_t x, uint32_t y, uint32_t z, uint32_t w) {
  asm volatile("{\n" SA("%0", "%5") "st.shared.v4.u32 [sa], {%1,%2,%3,%4};\n}" ::"r"(a), "r"(x), "r"(y), "r"(z), "r"(w), "r"(win()) : "memory");
}
__device__ __forceinline__ void mbar_wait(uint32_t bar, uint32_t parity) {
  asm volatile("{\n.reg .pred p;\n" SA("%0", "%2") "LAB_WAIT:\nmbarrier.try_wait.parity.shared::cta.b64 p, [sa], %1;\n@!p bra LAB_WAIT;\n}" ::"r"(bar), "r"(parity), "r"(win()) : "memory");
}
__device__ __forceinline__ void timed_wait(uint32_t bar, uint32_t par) {
  asm volatile("{\n.reg .pred p;\n.reg .u64 t0, t1;\nmov.u64 t0, %%globaltimer;\nLAB_WD:\n"
               "mbarrier.try_wait.parity.shared::cta.b64 p, [%0], %1, 100000;\n@p bra LAB_OK;\n"
               "mov.u64 t1, %%globaltimer;\nsub.u64 t1, t1, t0;\nsetp.lt.u64 p, t1, 2000000000;\n@p bra LAB_WD;\ntrap;\nLAB_OK:\n}" ::"r"(bar + win()), "r"(par) : "memory");
}
__device__ __forceinline__ void flag_wait(const unsigned* flag, unsigned target) {
  asm volatile("{\n.reg .pred p;\n.reg .u32 v;\nLAB_WAIT:\nld.acquire.gpu.global.u32 v, [%0];\nsub.u32 v, v, %1;\n"
               "setp.lt.s32 p, v, 0;\nvote.sync.any.pred p, p, 0xffffffff;\n@p nanosleep.u32 100;\n@p bra LAB_WAIT;\n}" ::"l"(flag), "r"(target) : "memory");
}
__device__ __forceinline__ void hint_post(uint8_t* p) {
  __syncwarp();
  asm volatile("{\n.reg .pred p;\nelect.sync _|p, 0xffffffff;\n@p red.relaxed.gpu.global.add.u32 [%0], 1;\n}" ::"l"(p) : "memory");
}
__device__ __forceinline__ void hint_wait(const uint8_t* p, uint32_t target) {
  asm volatile("{\n.reg .pred p;\n.reg .u32 v;\nLAB_WAIT:\nld.relaxed.gpu.global.u32 v, [%0];\nsub.u32 v, v, %1;\n"
               "setp.lt.s32 p, v, 0;\nvote.sync.any.pred p, p, 0xffffffff;\n@p bra LAB_WAIT;\n}" ::"l"(p), "r"(target) : "memory");
}
__device__ __forceinline__ void flag_signal(unsigned* flag) { asm volatile("red.release.gpu.global.add.u32 [%0], 1;" ::"l"(flag) : "memory"); }
struct Rel {
  bool on; uint32_t base;
  uint32_t tr;
  __device__ __forceinline__ void operator()(int s) const {
    if (on) asm volatile("{\n" SA("%0", "%1") "mbarrier.arrive.shared::cluster.b64 _, [sa];\n}" ::"r"(bar_empty(s)), "r"(base) : "memory");
  }
};
__device__ __forceinline__ uint32_t cta_window(uint32_t rank) { uint32_t a; asm("mapa.shared::cluster.u32 %0, %1, %2;" : "=r"(a) : "r"(0), "r"(rank)); return a; }
#define ELECT ".reg .pred e;\nelect.sync _|e, 0xffffffff;\n"
__device__ __forceinline__ void w_expect_tx(uint32_t bar, uint32_t bytes) {
  asm volatile("{\n" ELECT "@e mbarrier.arrive.expect_tx.shared::cta.b64 _, [%0], %1;\n}" ::"r"(bar), "r"(bytes) : "memory");
}
__device__ __forceinline__ void w_tma_2d_mc(uint32_t dst, const CUtensorMap* m, int c0, int c1, uint32_t bar) {
  asm volatile("{\n" ELECT "@e cp.async.bulk.tensor.2d.shared::cluster.global.mbarrier::complete_tx::bytes.multicast::cluster [%0], [%1, {%3, %4}], [%2], %5;\n}"
               ::"r"(dst), "l"(m), "r"(bar), "r"(c0), "r"(c1), "h"((uint16_t)3) : "memory");
}
__device__ __forceinline__ void w_bulk_load_mc(uint32_t dst, const void* src, uint32_t bytes, uint32_t bar) {
  asm volatile("{\n" ELECT "@e cp.async.bulk.shared::cluster.global.mbarrier::complete_tx::bytes.multicast::cluster [%0], [%1], %2, [%3], %4;\n}"
               ::"r"(dst), "l"(src), "r"(bytes), "r"(bar), "h"((uint16_t)3) : "memory");
}
__device__ __forceinline__ void w_bulk_load(uint32_t dst, const void* src, uint32_t bytes, uint32_t bar) {
  asm volatile("{\n" ELECT "@e cp.async.bulk.shared::cluster.global.mbarrier::complete_tx::bytes [%0], [%1], %2, [%3];\n}" ::"r"(dst), "l"(src), "r"(bytes), "r"(bar) : "memory");
}
__device__ __forceinline__ void w_l2_prefetch(const void* src, uint32_t bytes) { asm volatile("{\n" ELECT "@e cp.async.bulk.prefetch.L2.global [%0], %1;\n}" ::"l"(src), "r"(bytes) : "memory"); }
__device__ __forceinline__ void w_tma_prefetch(const CUtensorMap* m, int c0, int c1) {
  asm volatile("{\n" ELECT "@e cp.async.bulk.prefetch.tensor.2d.L2.global [%0, {%1, %2}];\n}" ::"l"(m), "r"(c0), "r"(c1) : "memory");
}
__device__ __forceinline__ void tma_3d(uint32_t dst, const CUtensorMap* m, int c0, int c1, int c2, uint32_t bar) {
  asm volatile("cp.async.bulk.tensor.3d.shared::cluster.global.mbarrier::complete_tx::bytes [%0], [%1, {%3, %4, %5}], [%2];"
               ::"r"(dst), "l"(m), "r"(bar), "r"(c0), "r"(c1), "r"(c2) : "memory");
}
__device__ __forceinline__ void wg_fence() { asm volatile("wgmma.fence.sync.aligned;" ::: "memory"); }
__device__ __forceinline__ void wg_commit() { asm volatile("wgmma.commit_group.sync.aligned;" ::: "memory"); }
template <int N> __device__ __forceinline__ void wg_wait() { asm volatile("wgmma.wait_group.sync.aligned %0;" ::"n"(N) : "memory"); }
__device__ __forceinline__ void bar_sync(int id, int n) { asm volatile("bar.sync %0, %1;" ::"r"(id), "r"(n) : "memory"); }
__device__ __forceinline__ void bar_arrive(int id, int n) { asm volatile("bar.arrive %0, %1;" ::"r"(id), "r"(n) : "memory"); }
__device__ __forceinline__ uint32_t pack_bf16(float lo, float hi) { uint32_t r; asm("cvt.rn.bf16x2.f32 %0, %1, %2;" : "=r"(r) : "f"(hi), "f"(lo)); return r; }
__device__ __forceinline__ float bf_lo(uint32_t w) { return __uint_as_float(w << 16); }
__device__ __forceinline__ float bf_hi(uint32_t w) { return __uint_as_float(w & 0xffff0000u); }
__device__ __forceinline__ float bf_round(float x) { return bf_lo(pack_bf16(x, 0.f)); }
__device__ __forceinline__ uint32_t bf2_sub(uint32_t a, uint32_t b) { uint32_t r; asm("sub.rn.bf16x2 %0, %1, %2;" : "=r"(r) : "r"(a), "r"(b)); return r; }
__device__ __forceinline__ uint32_t bf2_add(uint32_t a, uint32_t b) { uint32_t r; asm("add.rn.bf16x2 %0, %1, %2;" : "=r"(r) : "r"(a), "r"(b)); return r; }
#define GADDR(B, O, I) "cvt.u64.u32 ad, " O ";\nadd.u64 ad, ad, " B ";\nadd.u64 ad, ad, " I ";\n"
__device__ __forceinline__ void ld16(uint32_t* v, const uint8_t* ub, uint32_t off, uint32_t imm) {
  asm volatile("{\n.reg .b128 z;\n.reg .b64 x, y, ad;\n" GADDR("%4", "%5", "%6") "ld.relaxed.gpu.global.b128 z, [ad];\n"
               "mov.b128 {x, y}, z;\nmov.b64 {%0,%1}, x;\nmov.b64 {%2,%3}, y;\n}"
               : "=r"(v[0]), "=r"(v[1]), "=r"(v[2]), "=r"(v[3]) : "l"(ub), "r"(off), "l"((uint64_t)imm) : "memory");
}
__device__ __forceinline__ void ld8(uint32_t* v, const uint8_t* ub, uint32_t off, uint32_t imm) {
  asm volatile("{\n.reg .b64 x, ad;\n" GADDR("%2", "%3", "%4") "ld.relaxed.gpu.global.b64 x, [ad];\nmov.b64 {%0,%1}, x;\n}"
               : "=r"(v[0]), "=r"(v[1]) : "l"(ub), "r"(off), "l"((uint64_t)imm) : "memory");
}
__device__ __forceinline__ void st16(uint8_t* ub, uint32_t off, uint32_t imm, uint32_t a, uint32_t b, uint32_t c, uint32_t d) {
  asm volatile("{\n.reg .b128 z;\n.reg .b64 x, y, ad;\n" GADDR("%0", "%1", "%2") "mov.b64 x, {%3,%4};\nmov.b64 y, {%5,%6};\nmov.b128 z, {x, y};\n"
               "st.relaxed.gpu.global.b128 [ad], z;\n}" ::"l"(ub), "r"(off), "l"((uint64_t)imm), "r"(a), "r"(b), "r"(c), "r"(d) : "memory");
}
__device__ __forceinline__ void st8(uint8_t* ub, uint32_t off, uint32_t imm, uint32_t a, uint32_t b) {
  asm volatile("{\n.reg .b64 x, ad;\n" GADDR("%0", "%1", "%2") "mov.b64 x, {%3,%4};\nst.relaxed.gpu.global.b64 [ad], x;\n}"
               ::"l"(ub), "r"(off), "l"((uint64_t)imm), "r"(a), "r"(b) : "memory");
}
__device__ __forceinline__ void send8(uint8_t* ub, uint32_t off, uint32_t imm, uint32_t sm, int i, int j, uint32_t a, uint32_t b) {
  asm volatile("{\n.reg .pred p, q, e;\n.reg .b64 x, ad;\n" SA("%3", "%8") GADDR("%0", "%1", "%2")
               "setp.lt.s32 p, %4, %5;\nsetp.gt.s32 q, %4, %5;\nsetp.eq.s32 e, %4, %5;\nmov.b64 x, {%6,%7};\n"
               "@p st.relaxed.gpu.global.b64 [ad+-1024], x;\n@q st.relaxed.gpu.global.b64 [ad], x;\n@e st.shared.v2.u32 [sa], {%6,%7};\n}"
               ::"l"(ub), "r"(off), "l"((uint64_t)imm), "r"(sm), "r"(i), "r"(j), "r"(a), "r"(b), "r"(win()) : "memory");
}
__device__ __forceinline__ uint4 ldg_line(const void* p) {
  uint4 v; asm volatile("ld.global.nc.L2::128B.v4.u32 {%0,%1,%2,%3}, [%4];" : "=r"(v.x), "=r"(v.y), "=r"(v.z), "=r"(v.w) : "l"(p)); return v;
}
__device__ __forceinline__ void stg4(void* ub, uint32_t off, uint32_t imm, uint32_t v) {
  asm volatile("{\n.reg .b64 ad;\n" GADDR("%0", "%1", "%2") "st.global.u32 [ad], %3;\n}" ::"l"(ub), "r"(off), "l"((uint64_t)imm), "r"(v) : "memory");
}
__device__ __forceinline__ uint32_t tid_() { uint32_t t; asm volatile("mov.u32 %0, %%tid.x;" : "=r"(t)); return t & 127; }
__device__ __forceinline__ uint32_t nz(uint32_t w) { return w ? w : 0x8000u; }
__device__ __forceinline__ void mma16816(float (&c)[4], uint32_t a0, uint32_t a1, uint32_t a2, uint32_t a3, uint32_t b0, uint32_t b1) {
  asm("mma.sync.aligned.m16n8k16.row.col.f32.bf16.bf16.f32 {%0,%1,%2,%3}, {%4,%5,%6,%7}, {%8,%9}, {%0,%1,%2,%3};"
               : "+f"(c[0]), "+f"(c[1]), "+f"(c[2]), "+f"(c[3]) : "r"(a0), "r"(a1), "r"(a2), "r"(a3), "r"(b0), "r"(b1));
}
__device__ __forceinline__ void mma1688(float (&c)[4], uint32_t a0, uint32_t a1, uint32_t b0) {
  asm("mma.sync.aligned.m16n8k8.row.col.f32.bf16.bf16.f32 {%0,%1,%2,%3}, {%4,%5}, {%6}, {%0,%1,%2,%3};"
               : "+f"(c[0]), "+f"(c[1]), "+f"(c[2]), "+f"(c[3]) : "r"(a0), "r"(a1), "r"(b0));
}
__device__ __forceinline__ float ex2(float x) { float r; asm("ex2.approx.ftz.f32 %0, %1;" : "=f"(r) : "f"(x)); return r; }
__device__ __forceinline__ float quad_sum(float v) { v += __shfl_xor_sync(0xffffffffu, v, 1); v += __shfl_xor_sync(0xffffffffu, v, 2); return v; }
__device__ __forceinline__ float quad_max(float v) { v = fmaxf(v, __shfl_xor_sync(0xffffffffu, v, 1)); v = fmaxf(v, __shfl_xor_sync(0xffffffffu, v, 2)); return v; }

__device__ __forceinline__ void wgmma_rs_n64(float (&d)[32], uint32_t a0, uint32_t a1, uint32_t a2, uint32_t a3, uint64_t desc, int scale_d) {
  asm volatile("{\n.reg .pred p;\nsetp.ne.b32 p, %37, 0;\n"
    "wgmma.mma_async.sync.aligned.m64n64k16.f32.bf16.bf16 "
    "{%0, %1, %2, %3, %4, %5, %6, %7, %8, %9, %10, %11, %12, %13, %14, %15, %16, %17, %18, %19, %20, %21, %22, %23, %24, %25, %26, %27, %28, %29, %30, %31}, "
    "{%32, %33, %34, %35}, %36, p, 1, 1, 1;\n}\n"
    : "+f"(d[0]), "+f"(d[1]), "+f"(d[2]), "+f"(d[3]), "+f"(d[4]), "+f"(d[5]), "+f"(d[6]), "+f"(d[7]), "+f"(d[8]), "+f"(d[9]), "+f"(d[10]), "+f"(d[11]), "+f"(d[12]), "+f"(d[13]), "+f"(d[14]), "+f"(d[15]), "+f"(d[16]), "+f"(d[17]), "+f"(d[18]), "+f"(d[19]), "+f"(d[20]), "+f"(d[21]), "+f"(d[22]), "+f"(d[23]), "+f"(d[24]), "+f"(d[25]), "+f"(d[26]), "+f"(d[27]), "+f"(d[28]), "+f"(d[29]), "+f"(d[30]), "+f"(d[31])
    : "r"(a0), "r"(a1), "r"(a2), "r"(a3), "l"(desc), "r"(scale_d));
}

__device__ __forceinline__ void wgmma_rs_n72(float (&d)[36], uint32_t a0, uint32_t a1, uint32_t a2, uint32_t a3, uint64_t desc, int scale_d) {
  asm volatile("{\n.reg .pred p;\nsetp.ne.b32 p, %41, 0;\n"
    "wgmma.mma_async.sync.aligned.m64n72k16.f32.bf16.bf16 "
    "{%0, %1, %2, %3, %4, %5, %6, %7, %8, %9, %10, %11, %12, %13, %14, %15, %16, %17, %18, %19, %20, %21, %22, %23, %24, %25, %26, %27, %28, %29, %30, %31, %32, %33, %34, %35}, "
    "{%36, %37, %38, %39}, %40, p, 1, 1, 1;\n}\n"
    : "+f"(d[0]), "+f"(d[1]), "+f"(d[2]), "+f"(d[3]), "+f"(d[4]), "+f"(d[5]), "+f"(d[6]), "+f"(d[7]), "+f"(d[8]), "+f"(d[9]), "+f"(d[10]), "+f"(d[11]), "+f"(d[12]), "+f"(d[13]), "+f"(d[14]), "+f"(d[15]), "+f"(d[16]), "+f"(d[17]), "+f"(d[18]), "+f"(d[19]), "+f"(d[20]), "+f"(d[21]), "+f"(d[22]), "+f"(d[23]), "+f"(d[24]), "+f"(d[25]), "+f"(d[26]), "+f"(d[27]), "+f"(d[28]), "+f"(d[29]), "+f"(d[30]), "+f"(d[31]), "+f"(d[32]), "+f"(d[33]), "+f"(d[34]), "+f"(d[35])
    : "r"(a0), "r"(a1), "r"(a2), "r"(a3), "l"(desc), "r"(scale_d));
}

__device__ __forceinline__ void wgmma_rs_n128(float (&d)[64], uint32_t a0, uint32_t a1, uint32_t a2, uint32_t a3, uint64_t desc, int scale_d) {
  asm volatile("{\n.reg .pred p;\nsetp.ne.b32 p, %69, 0;\n"
    "wgmma.mma_async.sync.aligned.m64n128k16.f32.bf16.bf16 "
    "{%0, %1, %2, %3, %4, %5, %6, %7, %8, %9, %10, %11, %12, %13, %14, %15, %16, %17, %18, %19, %20, %21, %22, %23, %24, %25, %26, %27, %28, %29, %30, %31, %32, %33, %34, %35, %36, %37, %38, %39, %40, %41, %42, %43, %44, %45, %46, %47, %48, %49, %50, %51, %52, %53, %54, %55, %56, %57, %58, %59, %60, %61, %62, %63}, "
    "{%64, %65, %66, %67}, %68, p, 1, 1, 1;\n}\n"
    : "+f"(d[0]), "+f"(d[1]), "+f"(d[2]), "+f"(d[3]), "+f"(d[4]), "+f"(d[5]), "+f"(d[6]), "+f"(d[7]), "+f"(d[8]), "+f"(d[9]), "+f"(d[10]), "+f"(d[11]), "+f"(d[12]), "+f"(d[13]), "+f"(d[14]), "+f"(d[15]), "+f"(d[16]), "+f"(d[17]), "+f"(d[18]), "+f"(d[19]), "+f"(d[20]), "+f"(d[21]), "+f"(d[22]), "+f"(d[23]), "+f"(d[24]), "+f"(d[25]), "+f"(d[26]), "+f"(d[27]), "+f"(d[28]), "+f"(d[29]), "+f"(d[30]), "+f"(d[31]), "+f"(d[32]), "+f"(d[33]), "+f"(d[34]), "+f"(d[35]), "+f"(d[36]), "+f"(d[37]), "+f"(d[38]), "+f"(d[39]), "+f"(d[40]), "+f"(d[41]), "+f"(d[42]), "+f"(d[43]), "+f"(d[44]), "+f"(d[45]), "+f"(d[46]), "+f"(d[47]), "+f"(d[48]), "+f"(d[49]), "+f"(d[50]), "+f"(d[51]), "+f"(d[52]), "+f"(d[53]), "+f"(d[54]), "+f"(d[55]), "+f"(d[56]), "+f"(d[57]), "+f"(d[58]), "+f"(d[59]), "+f"(d[60]), "+f"(d[61]), "+f"(d[62]), "+f"(d[63])
    : "r"(a0), "r"(a1), "r"(a2), "r"(a3), "l"(desc), "r"(scale_d));
}

__device__ __forceinline__ void wgmma_rs_n144(float (&d)[72], uint32_t a0, uint32_t a1, uint32_t a2, uint32_t a3, uint64_t desc, int scale_d) {
  asm volatile("{\n.reg .pred p;\nsetp.ne.b32 p, %77, 0;\n"
    "wgmma.mma_async.sync.aligned.m64n144k16.f32.bf16.bf16 "
    "{%0, %1, %2, %3, %4, %5, %6, %7, %8, %9, %10, %11, %12, %13, %14, %15, %16, %17, %18, %19, %20, %21, %22, %23, %24, %25, %26, %27, %28, %29, %30, %31, %32, %33, %34, %35, %36, %37, %38, %39, %40, %41, %42, %43, %44, %45, %46, %47, %48, %49, %50, %51, %52, %53, %54, %55, %56, %57, %58, %59, %60, %61, %62, %63, %64, %65, %66, %67, %68, %69, %70, %71}, "
    "{%72, %73, %74, %75}, %76, p, 1, 1, 1;\n}\n"
    : "+f"(d[0]), "+f"(d[1]), "+f"(d[2]), "+f"(d[3]), "+f"(d[4]), "+f"(d[5]), "+f"(d[6]), "+f"(d[7]), "+f"(d[8]), "+f"(d[9]), "+f"(d[10]), "+f"(d[11]), "+f"(d[12]), "+f"(d[13]), "+f"(d[14]), "+f"(d[15]), "+f"(d[16]), "+f"(d[17]), "+f"(d[18]), "+f"(d[19]), "+f"(d[20]), "+f"(d[21]), "+f"(d[22]), "+f"(d[23]), "+f"(d[24]), "+f"(d[25]), "+f"(d[26]), "+f"(d[27]), "+f"(d[28]), "+f"(d[29]), "+f"(d[30]), "+f"(d[31]), "+f"(d[32]), "+f"(d[33]), "+f"(d[34]), "+f"(d[35]), "+f"(d[36]), "+f"(d[37]), "+f"(d[38]), "+f"(d[39]), "+f"(d[40]), "+f"(d[41]), "+f"(d[42]), "+f"(d[43]), "+f"(d[44]), "+f"(d[45]), "+f"(d[46]), "+f"(d[47]), "+f"(d[48]), "+f"(d[49]), "+f"(d[50]), "+f"(d[51]), "+f"(d[52]), "+f"(d[53]), "+f"(d[54]), "+f"(d[55]), "+f"(d[56]), "+f"(d[57]), "+f"(d[58]), "+f"(d[59]), "+f"(d[60]), "+f"(d[61]), "+f"(d[62]), "+f"(d[63]), "+f"(d[64]), "+f"(d[65]), "+f"(d[66]), "+f"(d[67]), "+f"(d[68]), "+f"(d[69]), "+f"(d[70]), "+f"(d[71])
    : "r"(a0), "r"(a1), "r"(a2), "r"(a3), "l"(desc), "r"(scale_d));
}

template <int N> struct WG;
template <> struct WG<64>  { static __device__ __forceinline__ void f(float (&d)[32], const uint32_t* a, uint64_t ds, int s) { wgmma_rs_n64(d, a[0], a[1], a[2], a[3], ds, s); } };
template <> struct WG<72>  { static __device__ __forceinline__ void f(float (&d)[36], const uint32_t* a, uint64_t ds, int s) { wgmma_rs_n72(d, a[0], a[1], a[2], a[3], ds, s); } };
template <> struct WG<128> { static __device__ __forceinline__ void f(float (&d)[64], const uint32_t* a, uint64_t ds, int s) { wgmma_rs_n128(d, a[0], a[1], a[2], a[3], ds, s); } };
template <> struct WG<144> { static __device__ __forceinline__ void f(float (&d)[72], const uint32_t* a, uint64_t ds, int s) { wgmma_rs_n144(d, a[0], a[1], a[2], a[3], ds, s); } };

constexpr uint64_t DESC_SW128 = ((uint64_t)(8192 >> 4) << 16) | ((uint64_t)(1024 >> 4) << 32) | (1ull << 62);
constexpr uint64_t DESC_KV = ((uint64_t)(128 >> 4) << 16) | ((uint64_t)(768 >> 4) << 32);
constexpr uint64_t DESC_Q = ((uint64_t)(128 >> 4) << 16) | ((uint64_t)(1536 >> 4) << 32);

template <int V> struct IntC { static constexpr int value = V; };
enum { PS_KV, PS_Q, PS_WO, PS_FF, PS_FFA   };
template <int PS> __host__ __device__ constexpr int pass_slot(int i) {
  return PS == PS_KV ? (i < 3 ? 9 + i : i - 3) : PS == PS_WO ? 6 + i : i;
}

__device__ __forceinline__ void load_frag(uint32_t (&a)[144], int i, const uint8_t* sb, uint32_t uo, uint32_t t) {
  if (i < 32) ld16(&a[4 * i], sb, uo + t * 16, i * 2048);
  else { ld8(&a[4 * i], sb, uo + t * 8, i * 2048); ld8(&a[4 * i + 2], sb, uo + t * 8, i * 2048 + 1024); }
}
__device__ __forceinline__ void store_own(const uint32_t (&y)[18], uint8_t* sb, uint32_t uo, int j, uint32_t t) {
#pragma unroll
  for (int i = 0; i < 4; i++) st16(sb, uo + j * 8192 + t * 16, i * 2048, nz(y[4 * i]), y[4 * i + 1], y[4 * i + 2], y[4 * i + 3]);
  st8(sb, uo + j * 1024 + t * 8, 65536, nz(y[16]), y[17]);
}
__device__ __forceinline__ void load_own(uint32_t* y, const uint8_t* sb, uint32_t uo, int j) {
  const uint32_t t = tid_();
#pragma unroll
  for (int i = 0; i < 4; i++) ld16(&y[4 * i], sb, uo + j * 8192 + t * 16, i * 2048);
  ld8(&y[16], sb, uo + j * 1024 + t * 8, 65536);
}

#define TR(i) do {} while (0)
struct NoTail { __device__ __forceinline__ void operator()() const {} };
template <int N, int PS, int KPS, int KSTEP, int CHK, bool SUB, bool HREL = false, class Tail = NoTail>
__device__ __forceinline__ void mma_pass(float (&acc)[N / 2], uint32_t (&a)[144], uint64_t desc, uint32_t par, const Rel& rel, int bar_id,
                                         const uint8_t* sb = nullptr, uint32_t uo = 0, uint32_t flag = 0, uint32_t m0 = 0, uint32_t m1 = 0, uint32_t park = 0, Tail tail = Tail()) {
  constexpr int NS = 36 / KPS;
  auto check = [&](int lo, int hi, uint32_t m0_) {
    while (true) {
      uint32_t m = m0_;
#pragma unroll
      for (int i = hi - 1; i >= lo; i--) m = min(m, i < 32 ? a[4 * i] : min(a[4 * i], a[4 * i + 2]));
      if (!__any_sync(0xffffffffu, (m | flag) == 0)) break;
      const uint32_t t = tid_();
#pragma unroll
      for (int i = lo; i < hi; i++) load_frag(a, i, sb, uo, t);
    }
  };
#pragma unroll
  for (int s = 0; s < NS; s++) {
    const int sl = pass_slot<PS>(s);
    if (CHK && s == 0 && !SUB) check(0, CHK * KPS, ~0u);
    if (CHK && s == CHK) check(CHK * KPS, 36, lds32(SM_EPOCH) | 1);
    if (SUB) {
#pragma unroll
      for (int i = s * KPS * 4; i < (s + 1) * KPS * 4; i += 2) { a[i] = bf2_sub(a[i], m0); a[i + 1] = bf2_sub(a[i + 1], m1); }
    }
    if (PS == PS_KV && s == 0) sts128(park + tid_() * 16, a[0], a[1], a[2], a[3]);
    constexpr int TB = PS == PS_KV ? 0 : PS == PS_Q ? 26 : PS == PS_WO ? 40 : SUB ? 54 : PS == PS_FFA ? 74 : -1;
    if (TB >= 0) TR(TB + 2 * s);
    mbar_wait(bar_full(sl), sl < 9 ? par : par ^ 1);
    if (TB >= 0) TR(TB + 2 * s + 1);
    wg_fence();
#pragma unroll
    for (int kk = 0; kk < KPS; kk++)
      WG<N>::f(acc, &a[(s * KPS + kk) * 4], desc + ((slot_addr(sl) + kk * KSTEP) >> 4), (s | kk) || PS == PS_FFA);
    wg_commit();
    if (CHK && s < 2 && N_UP < 36 && !flag) {
      const uint32_t t = tid_();
#pragma unroll
      for (int i = s ? (N_UP + 36) / 2 : N_UP; i < (s ? 36 : (N_UP + 36) / 2); i++) load_frag(a, i, sb, uo, t);
    }
    if (s == (PS == PS_KV ? KV_LEAD : NS - 1) && bar_id >= 0) bar_arrive(bar_id, 256);
    if (s > 0) {
      wg_wait<1>();
      if (!(PS == PS_WO && s > 3)) rel(pass_slot<PS>(s - 1));
    }
    if (HREL && s == 3 && flag) {
#pragma unroll
      for (int i = 0; i < 12; i++) ld16(&a[4 * i], sb, uo, i * 2048);
    }
  }
  constexpr int TE = PS == PS_KV ? 24 : PS == PS_Q ? 38 : PS == PS_WO ? 52 : SUB ? 72 : PS == PS_FFA ? 92 : -1;
  tail();
  if (TE >= 0) TR(TE);
  wg_wait<0>();
  if (TE >= 0) TR(TE + 1);
  if (PS != PS_WO) rel(pass_slot<PS>(NS - 1));
}

template <int NF, int N0 = 0> __device__ __forceinline__ void load_frags(uint32_t (&a)[144], const uint8_t* sb, uint32_t uo, uint32_t t) {
#pragma unroll
  for (int i = N0; i < NF; i++) load_frag(a, i, sb, uo, t);
}
__device__ __forceinline__ void ln_scalars(float s1, float s2, uint32_t& m, float& var, uint32_t zero) {
  const float mean = s1 * (1.f / DM);
  var = s2 * (1.f / DM) - mean * mean;
  m = pack_bf16(mean, mean) ^ (__float_as_uint(var) & zero);
}
__device__ __forceinline__ float ln_rstd(float var, float after, uint32_t zero) {
  var = __uint_as_float(__float_as_uint(var) ^ (__float_as_uint(after) & zero));
  float sd, r;
  asm("sqrt.approx.ftz.f32 %0, %1;" : "=f"(sd) : "f"(bf_round(bf_round(fmaxf(var, 0.f)) + 1e-5f)));
  asm("rcp.approx.ftz.f32 %0, %1;" : "=f"(r) : "f"(bf_round(sd)));
  return r;
}
template <int NF> __device__ __forceinline__ void gather_ln(uint32_t (&a)[144], const uint8_t* sb, uint32_t uo, uint32_t sto,
                                          uint32_t& m0, uint32_t& m1, float& r0, float& r1, uint32_t zero) {
  uint32_t u[32];
  const uint32_t t = tid_(), so = sto + (t >> 5) * 1024 + (t & 28) * 4;
#pragma unroll
  for (int i = 0; i < 8; i++) ld16(&u[4 * i], sb, so, OFF_ST + i * 128);
  load_frags<N_UP>(a, sb, uo, t);
  while (true) {
    uint32_t m = a[4 * NF - 4];
#pragma unroll
    for (int i = NF - 2; i >= 0; i--) m = min(m, a[4 * i]);
#pragma unroll
    for (int i = 0; i < 8; i++) m = min(m, u[4 * i]);
    if (!__any_sync(0xffffffffu, m == 0)) break;
#pragma unroll
    for (int i = 0; i < 8; i++) ld16(&u[4 * i], sb, so, OFF_ST + i * 128);
    load_frags<NF>(a, sb, uo, t);
  }
  float v[4];
#pragma unroll
  for (int k = 0; k < 4; k++)
    v[k] = ((__uint_as_float(u[k]) + __uint_as_float(u[4 + k])) + (__uint_as_float(u[8 + k]) + __uint_as_float(u[12 + k]))) +
           ((__uint_as_float(u[16 + k]) + __uint_as_float(u[20 + k])) + (__uint_as_float(u[24 + k]) + __uint_as_float(u[28 + k])));
  ln_scalars(v[1], v[0], m0, r0, zero); ln_scalars(v[3], v[2], m1, r1, zero);
}
struct Stats {
  float s[4] = {0, 0, 0, 0}, d0[4] = {0, 0, 0, 0}, d1[4] = {0, 0, 0, 0};
  __device__ __forceinline__ void add16(const uint32_t* f) {
    mma16816(s, f[0], f[1], f[2], f[3], 0x3f803f80u, 0x3f803f80u);
    mma1688(d0, f[0], f[1], f[0]); mma1688(d1, f[0], f[1], f[1]);
    mma1688(d0, f[2], f[3], f[2]); mma1688(d1, f[2], f[3], f[3]);
  }
  __device__ __forceinline__ float sq0(int g) const { return (g & 1) ? d0[1] : d0[0]; }
  __device__ __forceinline__ float sq1(int g) const { return (g & 1) ? d1[3] : d1[2]; }
};
struct RowStats {
  float s[4] = {0, 0, 0, 0}, u[4] = {0, 0, 0, 0};
  template <int N> __device__ __forceinline__ void add(const uint32_t* y) {
#pragma unroll
    for (int i = 0; i < N; i++) {
      const float lo = bf_lo(y[i]), hi = bf_hi(y[i]);
      const int r = (i & 1) * 2;
      s[r] = fmaf(lo, lo, s[r]); u[r] = fmaf(hi, hi, u[r]); s[r + 1] += lo; u[r + 1] += hi;
    }
  }
  __device__ __forceinline__ uint32_t fold() {
    uint32_t x = 0;
#pragma unroll
    for (int i = 0; i < 4; i++) { s[i] += u[i]; u[i] = 0; x |= __float_as_uint(s[i]); }
    return x;
  }
  __device__ __forceinline__ void store(uint8_t* sb, uint32_t sto, uint32_t t) {
    fold();
#pragma unroll
    for (int i = 0; i < 4; i++) s[i] += __shfl_xor_sync(0xffffffffu, s[i], 1);
#pragma unroll
    for (int i = 0; i < 4; i++) s[i] += __shfl_xor_sync(0xffffffffu, s[i], 2);
    if ((t & 3) == 0) st16(sb, sto + (t >> 5) * 1024 + (t & 28) * 4, OFF_ST, __float_as_uint(s[0]) | 1u, __float_as_uint(s[1]), __float_as_uint(s[2]), __float_as_uint(s[3]));
  }
};
template <bool SET> __device__ __forceinline__ void add_piece(float* acc, uint32_t sm) {
#pragma unroll
  for (int i = 0; i < 4; i++) {
    uint32_t v[4];
    lds128(v, sm + i * 2048);
#pragma unroll
    for (int k = 0; k < 4; k++) {
      acc[8 * i + 2 * k] = SET ? bf_lo(v[k]) : acc[8 * i + 2 * k] + bf_lo(v[k]);
      acc[8 * i + 2 * k + 1] = SET ? bf_hi(v[k]) : acc[8 * i + 2 * k + 1] + bf_hi(v[k]);
    }
  }
}

#define TS(i) do {} while (0)
#define TSP(i) do {} while (0)
#define TSH(i) do {} while (0)

__device__ __forceinline__ uint32_t row_off(int rb, int wg, uint32_t t) { return (rb * 128 + wg + ((t >> 5) * 16 + (t & 15)) * 2) * (2 * DM); }

__device__ __forceinline__ const __nv_bfloat16* wo_src(const __nv_bfloat16* wo, int k, int u, int j) {
  const int ko = k < 512 ? (k >> 6) * 72 + (k & 63) : ((k >> 3) & 7) * 72 + 64 + (k & 7);
  return wo + ko * 576 + (u < 8 ? j * 64 + u * 8 : 512 + j * 8);
}

struct Params {
  const __nv_bfloat16* wqkv;
  uint8_t* scr;
  uint8_t role[64];
  const __nv_bfloat16* wo;
  __nv_bfloat16* out;
  uint8_t* times;
  unsigned zero;
};

__cluster_dims__(2, 1, 1)
__global__ void __launch_bounds__(384, 1)
fused_kernel(const __grid_constant__ Params P, const __grid_constant__ CUtensorMap map_x, const __grid_constant__ CUtensorMap map_wg,
             const __grid_constant__ CUtensorMap map_wu, const __grid_constant__ CUtensorMap map_wd) {
  const int wg = __shfl_sync(0xffffffffu, threadIdx.x >> 7, 0);
  const int cta = blockIdx.x, rank = cta & 1, role = P.role[cta >> 1], j = role & 7, rb = (role >> 3) * 2 + rank;
  const uint32_t own = win();
  unsigned* const flags = (unsigned*)(P.scr + OFF_FLAGS);
  if (__shfl_sync(0xffffffffu, threadIdx.x >> 5, 0) == 11) {
    if (threadIdx.x == 352) {
#pragma unroll
      for (int i = 0; i < 14; i++) { mbar_init(bar_full(i), 1); mbar_init(bar_empty(i), i < 12 ? 4 : 2); }
      mbar_init(bar_full(14), 1); mbar_init(bar_empty(14), 1);
      asm volatile("fence.mbarrier_init.release.cluster;" ::: "memory");
      if (smem_u32(smem_raw) != own + SB) asm volatile("trap;");
    }
    __syncwarp();
    bar_arrive(0, 384);
    asm volatile("barrier.cluster.arrive.relaxed.aligned;" ::: "memory");
    if (threadIdx.x == 352) {
#pragma unroll 1
      for (int c = 0; c < 9; c++) {
        mbar_expect_tx(bar_full(c), SLOT);
        tma_3d(own + slot_addr(c), &map_x, c * 64, rb * 64, 0, own + bar_full(c));
      }
    }
  } else {
    const bool on = threadIdx.x < 324;
    const int k = rb * 36 + (on ? threadIdx.x / 36 : 0) * 4 + (threadIdx.x & 3), u = (threadIdx.x % 36) >> 2;
    const uint4* s = (const uint4*)(P.wqkv + k * 1728 + j * 72 + u * 8);
    const uint4 vk = ldg_line(s + 72), vv = ldg_line(s + 144);
    const unsigned ep0 = *(volatile unsigned*)&flags[(72 + cta) * 8];
    asm volatile("barrier.cluster.arrive.relaxed.aligned;" ::: "memory");
    bar_sync(0, 384);
    uint8_t* d = P.scr + OFF_WPACK + j * 24 * PSLOT;
    if (on) {
      const uint32_t dkv = (k / 48) * PSLOT + u * 768 + (k % 48) * 16;
      st16(d, dkv, 0, vk.x, vk.y, vk.z, vk.w);
      st16(d, dkv, 9 * 768, vv.x, vv.y, vv.z, vv.w);
    }
    asm volatile("fence.proxy.async.global;" ::: "memory");
    bar_arrive(NB_PUB + 3, 384);
    if (threadIdx.x == 351) sts32(SM_EPOCH, ep0);
    if (wg == 2) bar_sync(NB_PUB + 1, 96);
  }
  __syncwarp();
  asm volatile("barrier.cluster.wait.acquire.aligned;" ::: "memory");

  if (wg == 2) {
    asm volatile("setmaxnreg.dec.sync.aligned.u32 24;");
    const int pw = __shfl_sync(0xffffffffu, (threadIdx.x >> 5) & 3, 0), lane = threadIdx.x & 31;
    auto tile_col = [](int t, int h, int j) { return t < 9 ? j * 576 + t * 64 : (t == 9 && h) ? 512 : ((j + ((h ? 0x05760 : 0x04123) >> (4 * (t - 9)))) & 7) * 64; };
    auto prefetch_tile = [&](int t) {
#pragma unroll 1
      for (int b = rb; b < 18; b += 16) {
        const int h = b & 1, k = b >> 1;
        if (t < 9) w_tma_prefetch(h ? &map_wu : &map_wg, tile_col(t, h, j), k * 64);
        else if (t != 13 || !h) w_tma_prefetch(&map_wd, tile_col(t, h, j), j * 576 + k * 64);
      }
    };
    if (pw == 0) {
      {
        flag_wait(&flags[j * 8], (lds32(SM_EPOCH) + 1) * 16);
        TSP(7);
        asm volatile("fence.proxy.async.global;" ::: "memory");
        const uint8_t* wp = P.scr + OFF_WPACK + j * 24 * PSLOT;
        wp += rank * (PSLOT / 2);
        auto packed = [&](int sl, uint32_t par, int f) {
          mbar_wait(bar_empty(0) + sl * 8, par);
          w_bulk_load_mc(own + SB + rank * (PSLOT / 2) + sl * SLOT, wp + f * PSLOT, PSLOT / 2, own + bar_full(0) + sl * 8);
          w_expect_tx(own + bar_full(0) + sl * 8, PSLOT);
        };
        const uint32_t half = own + SB + rank * 8192;
#pragma unroll 1
        for (int L = 0; L < 2; L++) {
#pragma unroll 1
          for (int s = L ? 0 : -3; s < 21; s++) {
            if (s == 9 && L == 0) { flag_wait(&flags[(56 + j) * 8], (lds32(SM_EPOCH) + 1) * 16); asm volatile("fence.proxy.async.global;" ::: "memory"); }
            packed(s < 0 ? s + 12 : s < 9 ? s : s - 9, s < 0 || (s >= 9 && s < 18), s + 3);
          }
#pragma unroll 1
          for (int t = 0; t < 14; t++) {
            if (L * 14 + t + PF_AHEAD < 28) prefetch_tile((t + PF_AHEAD) % 14);
            const CUtensorMap* mp = t >= 9 ? &map_wd : rank ? &map_wu : &map_wg;
            const bool nar = t == 13;
            const int col = tile_col(t, nar ? 0 : rank, j);
            const uint32_t dst = nar ? own + SB : half, bytes = nar ? 8192 : SLOT;
            const int ra = t < 9 ? 0 : j * 576 + 320, rbs = t < 9 ? 0 : j * 576 - 192, rc = t < 9 ? 0 : j * 576;
#pragma unroll
            for (int k = 0; k < 9; k++) {
              mbar_wait(bar_empty(k), t & 1);
              if (!nar || rank == (k & 1)) w_tma_2d_mc(dst + k * SLOT, mp, col, (k < 3 ? ra : k < 8 ? rbs : rc) + k * 64, own + bar_full(k));
              w_expect_tx(own + bar_full(k), bytes);
            }
            if (t == 10 && L == 0) {
              w_l2_prefetch(P.scr + OFF_WPACK + j * 24 * PSLOT + rb * (24 * PSLOT / 16), 24 * PSLOT / 16);
#pragma unroll 1
              for (int s = 0; s < 3; s++) packed(9 + s, 1, s);
            }
          }
        }
        flags[(72 + cta) * 8] = lds32(SM_EPOCH) + 1;
      }
    } else if (pw < 3) {
      const int hw = pw - 1;
      const uint32_t ep = __shfl_sync(0xffffffffu, lds32(SM_EPOCH), 0);
      uint8_t* const sb = P.scr + (rb * 2 + hw) * STRM;
      const uint32_t xs = slot_addr(12) + hw * SLOT, fb = bar_full(12) + hw * 8;
      uint32_t hph = 0;
#pragma unroll 1
      for (int L = 0; L < 2; L++) {
        const uint32_t tag = ep * 2 + L + 1;
        bar_sync(NB_FREE + hw, 160);
        if (rb > 0) hint_wait(sb + OFF_HINT + 512 + j * 128, tag);
        uint32_t bad;
        do {
          if (rb > 0) {
            w_bulk_load(own + ytail(hw * 2), sb + OFF_HALO + (L * 8 + j) * 3072, 1536, own + bar_full(14) + hw * 128);
            w_bulk_load(own + ytail(hw * 2 + 1), sb + OFF_HALO + (L * 8 + j) * 3072 + 1536, 1536, own + bar_full(14) + hw * 128);
            w_expect_tx(own + bar_full(14) + hw * 128, 3072);
            mbar_wait(bar_full(14) + hw * 128, hph);
            hph ^= 1;
          }
          bad = 0;
#pragma unroll 1
          for (int c = 0; c < 3; c++) {
            uint32_t u[4] = {tag, 0, 0, 0}, v[4] = {tag, 0, 0, 0};
            if (rb > 0) { lds128(u, ytail(hw * 2) + c * 512 + lane * 16); lds128(v, ytail(hw * 2 + 1) + c * 512 + lane * 16); }
            bad |= (u[0] ^ tag) | (v[0] ^ tag);
#pragma unroll
            for (int i = 0; i < 3; i++) { sts32(xs + KSTG + (c * 3 + i) * 128 + lane * 4, u[i + 1]); sts32(xs + (c * 3 + i) * 128 + lane * 4, v[i + 1]); }
          }
        } while (__any_sync(0xffffffffu, bad != 0));
        bar_arrive(NB_HALO + hw, 160);
#pragma unroll 1
        for (int p = 0; p < 4; p++) {
          if (L == 0 && p == 3) flag_wait(flags + (40 + rb) * 8, (ep + 1) * 8);
          bar_sync(NB_FREE + hw, 160);
          TSH(L * 12 + p * 3);
          hint_wait(sb + OFF_HINT + (lane & 3) * 128, (ep * 13 + L * 7 + p + 3) * 8);
          TSH(L * 12 + p * 3 + 1);
          w_bulk_load(own + xs, sb + OFF_P + j * PSRC + (p & 1) * 16384, p ? 16384 : 8192, own + fb);
          if (p == 0) w_bulk_load(own + xs + 8192, sb + OFF_P + j * PSRC + 32768, 7168, own + fb);
          w_expect_tx(own + fb, p ? 16384 : 15360);
          TSH(L * 12 + p * 3 + 2);
        }
      }
    } else {
      auto clear = [&](int t) {
        const uint32_t so = rb * 2 * STRM + (threadIdx.x & 31) * 16;
#pragma unroll 1
        for (int i = 0; i < 18; i++) {
          st16(P.scr, so + t * TILE + j * 9216 + i * 512, 0, 0, 0, 0, 0);
          st16(P.scr, so + t * TILE + j * 9216 + i * 512, STRM, 0, 0, 0, 0);
          __nanosleep(0);
        }
        if (t != 1) {
          st16(P.scr, so + (t ? t - 1 : 0) * 4096 + j * 512, OFF_ST, 0, 0, 0, 0);
          st16(P.scr, so + (t ? t - 1 : 0) * 4096 + j * 512, OFF_ST + STRM, 0, 0, 0, 0);
        }
      };
      bar_sync(NB_PUB + 3, 384);
      if (lane == 0) flag_signal(&flags[j * 8]);
      TSP(5);
      bar_sync(NB_PUB + 2, 288);
      if (lane == 0) flag_signal(&flags[(56 + j) * 8]);
      TSP(4);
      __syncwarp();
#pragma unroll 1
      for (int t = 0; t < PF_AHEAD; t++) prefetch_tile(t);
#pragma unroll 1
      for (int L = 0; L < 2; L++) {
        timed_wait(bar_empty(13), L);
#pragma unroll 1
        for (int t = L ^ 1; t < 4 - 2 * L; t++) clear(t);
        __syncwarp();
        if (lane == 0 && L == 0) flag_signal(flags + (40 + rb) * 8);
      }
      timed_wait(bar_empty(12), 0);
      asm volatile("barrier.cluster.arrive.relaxed.aligned;\nbarrier.cluster.wait.aligned;" ::: "memory");
    }
  } else {
    asm volatile("setmaxnreg.inc.sync.aligned.u32 240;");
    const int w = __shfl_sync(0xffffffffu, (threadIdx.x >> 5) & 3, 0);
    Rel rel{(threadIdx.x & 95) == 0, cta_window(w & 1), 0};
    uint8_t* const sb = P.scr + (rb * 2 + wg) * STRM;
    uint8_t* const hint = sb + OFF_HINT + w * 128;
    auto hint_target = [](int e) { return (lds32(SM_EPOCH) * 13 + e + 1) * 8; };
    TS(0);
    uint32_t a[144];
#pragma unroll 1
    for (int L = 0; L < 2; L++) {
      uint32_t m0, m1; float r0, r1;
      rel.tr = win() + ytail(3) + 1536 + (L == TRACE - 1 && w == 1 ? wg * 384 : 768);
      if (L == 0) {
        Stats st;
        const int lane = tid_() & 31, g = lane >> 2;
        const int row = w * 16 + (lane & 15);
        const uint32_t ra = SB + wg * 8192 + row * 128;
        const uint32_t pt = tid_(), pu = (pt % 36) >> 2, pk = rb * 36 + (pt < 108 ? pt / 36 : 0) * 4 + (pt & 3);
        uint4 pv[3];
#pragma unroll
        for (int i = 0; i < 3; i++) pv[i] = ldg_line(wg ? wo_src(P.wo, pk + i * 12, pu, j) : P.wqkv + (pk + i * 12) * 1728 + j * 72 + pu * 8);
#pragma unroll
        for (int c = 0; c < 9; c++) {
          mbar_wait(bar_full(c), 0);
          if (c == 0) TS(60); if (c == 8) TS(62);
#pragma unroll
          for (int kk = 0; kk < 4; kk++) ldsm4(&a[c * 16 + kk * 4], ra + (((kk * 2 + (lane >> 4)) ^ (row & 7)) << 4) + c * SLOT);
          if (c == 8) {
            uint32_t y[18], z[4];
#pragma unroll
            for (int i = 0; i < 4; i++) ldsm4(&y[4 * i], ra + (((i * 2 + (lane >> 4)) ^ (row & 7)) << 4) + j * SLOT);
            ldsm4(z, ra + ((j ^ (row & 7)) << 4) + 8 * SLOT);
            y[16] = z[0]; y[17] = z[1];
            bar_sync(NB_WG + wg, 128);
#pragma unroll
            for (int i = 0; i < 9; i++) rel(i);
            if (pt < 108) {
#pragma unroll
              for (int i = 0; i < 3; i++) {
                const uint32_t k = pk + i * 12;
                st16(P.scr, (j * 24 + wg * 6 + k / 96) * PSLOT + pu * 1536 + (k % 96) * 16, OFF_WPACK + 12 * PSLOT, pv[i].x, pv[i].y, pv[i].z, pv[i].w);
              }
            }
            asm volatile("fence.proxy.async.global;" ::: "memory");
            bar_arrive(NB_PUB + 2, 288);
            store_own(y, sb, OFF_X2, j, tid_());
          }
#pragma unroll
          for (int kk = 0; kk < 4; kk++) st.add16(&a[c * 16 + kk * 4]);
        }
        const int dl = (lane & ~3) | (g >> 1);
        ln_scalars(st.s[0], __shfl_sync(0xffffffffu, st.sq0(g), dl), m0, r0, P.zero);
        ln_scalars(st.s[2], __shfl_sync(0xffffffffu, st.sq1(g), dl), m1, r1, P.zero);
      } else {
#pragma unroll
        for (int i = 4 * N_UP; i < 144; i++) a[i] = 0;
        hint_wait(hint, hint_target(6));
        TS(61);
        gather_ln<3 * D_KV>(a, sb, OFF_X2, 8192, m0, m1, r0, r1, P.zero);
      }
      TS(1 + L * 20);
      uint32_t kf[18], qf[18];
      {
        float acc[72];
        if (wg == 1) bar_sync(NB_ORD1, 256);
        mma_pass<144, PS_KV, 3, 256, D_KV, true>(acc, a, DESC_KV, 1, rel, wg == 0 ? NB_ORD1 : -1, sb, OFF_X2, L ^ 1, m0, m1, ytail(wg * 2));
        r0 = ln_rstd(r0, acc[0], P.zero); r1 = ln_rstd(r1, acc[0], P.zero);
        uint32_t vf[18];
#pragma unroll
        for (int c = 0; c < 9; c++) {
          kf[c] = pack_bf16(acc[4 * c] * r0, acc[4 * c + 1] * r0);
          kf[9 + c] = pack_bf16(acc[4 * c + 2] * r1, acc[4 * c + 3] * r1);
          vf[c] = pack_bf16(acc[36 + 4 * c] * r0, acc[36 + 4 * c + 1] * r0);
          vf[9 + c] = pack_bf16(acc[36 + 4 * c + 2] * r1, acc[36 + 4 * c + 3] * r1);
        }
        TS(2 + L * 20);
        const uint32_t l16 = (tid_() & 31) * 16, xs = slot_addr(12) + wg * SLOT + w * 1152;
#pragma unroll
        for (int i = 0; i < 4; i++) stsm4(xs + w * 1152 + 1152 + i * 512 + l16, vf[4 * i], vf[4 * i + 1], vf[4 * i + 2], vf[4 * i + 3]);
        sts32(xs + w * 1152 + 1152 + 2048 + l16 / 4, vf[16]); sts32(xs + w * 1152 + 1152 + 2176 + l16 / 4, vf[17]);
        if (w < 3) {
          stsm4(xs + KSTG + 1152 + l16, kf[9], kf[10], kf[11], kf[12]);
          stsm4(xs + KSTG + 1152 + 512 + l16, kf[13], kf[14], kf[15], kf[16]);
          sts32(xs + KSTG + 1152 + 1024 + l16 / 4, kf[17]);
        } else if (rb < 15) {
          const uint32_t tag = lds32(SM_EPOCH) * 2 + L + 1;
          const uint32_t ho = l16 + (L * 8 + j) * 3072;
#pragma unroll
          for (int c = 0; c < 3; c++) {
            st16(sb, ho, 2 * STRM + OFF_HALO + c * 512, tag, kf[9 + 3 * c], kf[10 + 3 * c], kf[11 + 3 * c]);
            st16(sb, ho, 2 * STRM + OFF_HALO + 1536 + c * 512, tag, vf[9 + 3 * c], vf[10 + 3 * c], vf[11 + 3 * c]);
          }
          hint_post(sb + 2 * STRM + OFF_HINT + 512 + j * 128);
        }
      }
      lds128(a, ytail(wg * 2) + tid_() * 16);
      bar_arrive(NB_FREE + wg, 160);
      uint32_t kh[12], vp[20], v1[12];
      {
        float acc[36];
        if (wg == 1) bar_sync(NB_ORD1, 256);
        mma_pass<72, PS_Q, 6, 256, 0, false, false>(acc, a, DESC_Q, 0, rel, -1, nullptr, 0, 0, 0, 0, 0, [&]() {
          bar_sync(NB_HALO + wg, 160);
#pragma unroll
          for (int i = 0; i < 3; i++) ldsm4(&kh[4 * i], slot_addr(12) + wg * SLOT + w * 640 + tid_() * 16 + KSTG + i * 512);
          const uint32_t l = tid_() & 31, vb = slot_addr(12) + wg * SLOT + w * 2304;
#pragma unroll
          for (int i = 0; i < 5; i++) ldsm4t(&vp[4 * i], vb + (l & 8) * 144 + (l & 16) * 8 + (l & 7) * 16 + i * 256);
#pragma unroll
          for (int i = 0; i < 3; i++) ldsm4t(&v1[4 * i], vb + 2304 + l * 16 + i * 512);
        });
#pragma unroll
        for (int i = 0; i < 18; i++) qf[i] = pack_bf16(acc[2 * i], acc[2 * i + 1]);
      }
      TS(3 + L * 20);
      uint32_t xr[18];
      {
        const int tid = tid_(), g = (tid >> 2) & 7, q = tid & 3;
        const bool nohalo = (rb == 0 && w == 0);
        const bool le0 = 2 * q <= g, le1 = 2 * q + 1 <= g;
        const uint32_t M = (le0 ? 0xffffu : 0u) | (le1 ? 0xffff0000u : 0u);
        const float sc0 = r0 * (0.23570226039551584f * 1.4426950408889634f), sc1 = r1 * (0.23570226039551584f * 1.4426950408889634f);
        float l[16], t[8];
#pragma unroll
        for (int h = 0; h < 4; h++) {
          const uint32_t qa0 = q >= h ? qf[4 * h] : 0u, qa1 = q >= h ? qf[4 * h + 1] : 0u;
          const uint32_t qc0 = q <= h ? qf[4 * h + 4] : 0u, qc1 = q <= h ? qf[4 * h + 5] : 0u;
          float sm[4] = {0, 0, 0, 0}, s0[4] = {0, 0, 0, 0}, s1[4] = {0, 0, 0, 0};
          mma16816(s0, qa0, qa1, qf[4 * h + 2], qf[4 * h + 3], kf[2 * h], kf[2 * h + 1]);
          mma16816(s1, qa0, qa1, qf[4 * h + 2], qf[4 * h + 3], kf[9 + 2 * h], kf[10 + 2 * h]);
          mma16816(sm, qa0, qa1, qf[4 * h + 2], qf[4 * h + 3], kh[2 * h], kh[2 * h + 1]);
          mma1688(s0, qc0, qc1, kf[2 * h + 2]);
          mma1688(s1, qc0, qc1, kf[11 + 2 * h]);
          mma1688(sm, qc0, qc1, kh[2 * h + 2]);
          if (nohalo) sm[0] = sm[1] = -3e38f;
          l[4 * h] = le0 ? s0[0] : sm[0]; l[4 * h + 1] = le1 ? s0[1] : sm[1];
          l[4 * h + 2] = le0 ? s1[2] : s0[2]; l[4 * h + 3] = le1 ? s1[3] : s0[3];
        }
#pragma unroll
        for (int i = 0; i < 8; i++) t[i] = fmaxf(l[2 * i], l[2 * i + 1]);
        TS(14 + L * 20);
#pragma unroll
        for (int i = 0; i < 8; i++) t[i] = fmaxf(t[i], __shfl_xor_sync(0xffffffffu, t[i], 1));
#pragma unroll
        for (int i = 0; i < 8; i++) t[i] = fmaxf(t[i], __shfl_xor_sync(0xffffffffu, t[i], 2)) * ((i & 1) ? sc1 : sc0);
#pragma unroll
        for (int i = 0; i < 8; i++) {
          const float sc = (i & 1) ? sc1 : sc0;
          l[2 * i] = ex2(fmaf(l[2 * i], sc, -t[i])); l[2 * i + 1] = ex2(fmaf(l[2 * i + 1], sc, -t[i])); t[i] = l[2 * i] + l[2 * i + 1];
        }
#pragma unroll
        for (int i = 0; i < 8; i++) t[i] += __shfl_xor_sync(0xffffffffu, t[i], 1);
#pragma unroll
        for (int i = 0; i < 8; i++) t[i] += __shfl_xor_sync(0xffffffffu, t[i], 2);
        uint32_t pf[16], pz[8];
#pragma unroll
        for (int i = 0; i < 8; i++) {
          float r; asm("rcp.approx.ftz.f32 %0, %1;" : "=f"(r) : "f"(t[i]));
          const uint32_t p = pack_bf16(l[2 * i] * r, l[2 * i + 1] * r);
          pf[2 * i] = p & ~M; pf[2 * i + 1] = p & M; pz[i] = p & P.zero;
        }
#pragma unroll
        for (int c = 0; c < 9; c++) {
          const int h = c == 8 ? 3 : c >> 1;
          float o[4] = {0, 0, 0, 0};
          mma16816(o, pf[4 * h], pz[2 * h], pf[4 * h + 1], pf[4 * h + 2], vp[2 * c], vp[2 * c + 1]);
          mma1688(o, pz[2 * h + 1], pf[4 * h + 3], v1[c]);
          if (c == 2 || c == 4 || c == 6) {
            float e[4] = {0, 0, 0, 0};
            mma16816(e, pf[4 * h - 4], pz[2 * h - 2], pf[4 * h - 3], pf[4 * h - 2], vp[2 * c], vp[2 * c + 1]);
            mma1688(e, pz[2 * h - 1], pf[4 * h - 1], v1[c]);
            const uint32_t u = pack_bf16(e[0], e[1]), v = pack_bf16(e[2], e[3]);
            qf[2 * c] = q < h ? u : pack_bf16(o[0], o[1]); qf[2 * c + 1] = q < h ? v : pack_bf16(o[2], o[3]);
          } else {
            qf[2 * c] = pack_bf16(o[0], o[1]); qf[2 * c + 1] = pack_bf16(o[2], o[3]);
          }
        }
        {
          uint32_t x = 0;
#pragma unroll
          for (int i = 0; i < 18; i += 2) x |= qf[i];
          bar_arrive(NB_ORD1 - wg + (x & P.zero), 256);
        }
        store_own(qf, sb, OFF_O, j, tid);
        hint_post(hint);
        load_own(xr, sb, OFF_X2, j);
      }
      TS(4 + L * 20);
      {
        hint_wait(hint, hint_target(L * 7));
        TS(5 + L * 20);
        load_frags<N_WO>(a, sb, OFF_O, tid_());
        float acc[36];
        if (wg == 0) bar_sync(NB_ORD0, 256);
        load_frags<N_UP, N_WO>(a, sb, OFF_O, tid_());
        TS(19 + L * 20);
        mma_pass<72, PS_WO, 6, 256, D_WO, false>(acc, a, DESC_Q, 0, rel, -1, sb, OFF_O);
        TS(6 + L * 20);
#pragma unroll
        for (int c = 0; c < 9; c++) {
          xr[2 * c] = bf2_add(xr[2 * c], pack_bf16(acc[4 * c], acc[4 * c + 1]));
          xr[2 * c + 1] = bf2_add(xr[2 * c + 1], pack_bf16(acc[4 * c + 2], acc[4 * c + 3]));
        }
        store_own(xr, sb, L * 3 * TILE, j, tid_());
        RowStats rs;
        rs.add<18>(xr);
        rs.store(sb, L * 4096 + j * 128, tid_());
        hint_post(hint);
      }
      TS(16 + L * 20);
      hint_wait(hint, hint_target(L * 7 + 1));
      TS(15 + L * 20);
      gather_ln<4 * D_T0>(a, sb, L * 3 * TILE, L * 4096, m0, m1, r0, r1, P.zero);
      TS(7 + L * 20);
      const uint32_t hb = OFF_H + j * 24576;
      {
        float ka0, kb0, kc0, ka1, kb1, kc1;
        float acc[64];
        uint32_t hf[16];
        auto geglu = [&](auto chains, uint32_t hsm) {
          constexpr int CH = decltype(chains)::value & 15;
          float r[32];
#pragma unroll
          for (int e = 0; e < 32; e++) {
            float x = acc[e];
            if (e >= CH) x = __uint_as_float(__float_as_uint(x) ^ (__float_as_uint(r[e - CH]) & P.zero));
            if (decltype(chains)::value > 15 && e < 20) {
              const uint32_t ad = (e < 8 ? slot_addr(12) + e * 2048 + wg * 8192 : slot_addr(7 + (e >> 2)) + (e & 3) * 2048) + hsm;
              lds128(&a[48 + 4 * e], e >= CH ? ad ^ (__float_as_uint(r[e - CH]) & P.zero) : ad);
            }
            const bool hi = e & 2;
            float t = x * fmaf(x * x, hi ? kb1 : kb0, hi ? ka1 : ka0);
            asm("tanh.approx.f32 %0, %0;" : "+f"(t));
            const float u = x * acc[32 + e] * (hi ? kc1 : kc0);
            r[e] = fmaf(u, t, u);
            if (e & 1) hf[e >> 1] = pack_bf16(r[e - 1], r[e]);
          }
        };
        if (wg == 1) bar_sync(NB_ORD1, 256);
        mma_pass<128, PS_FF, 4, 2048, D_T0, true>(acc, a, DESC_SW128, 1, rel, NB_ORD1 - wg, sb, L * 3 * TILE, 0, m0, m1);
        if (tid_() == 0) mbar_arrive(bar_empty(13));
        TS(8 + L * 20);
        r0 = ln_rstd(r0, acc[0], P.zero); r1 = ln_rstd(r1, acc[0], P.zero);
        ka0 = 0.7978845608028654f * r0; kb0 = 0.035677408136300125f * r0 * r0 * r0; kc0 = 0.5f * r0 * r0;
        ka1 = 0.7978845608028654f * r1; kb1 = 0.035677408136300125f * r1 * r1 * r1; kc1 = 0.5f * r1 * r1;
#pragma unroll 1
        for (int t = 0; t < 8; t++) {
          geglu(IntC<2>(), 0);
          const uint32_t t16 = tid_() * 16;
          if (t < 5) {
            const uint32_t d = (t < 2 ? slot_addr(12) + wg * SLOT + t * 8192 : slot_addr(7) + t * SLOT + wg * 8192) + t16;
#pragma unroll
            for (int i = 0; i < 4; i++)
              sts128(d + i * 2048, hf[4 * i], hf[4 * i + 1], hf[4 * i + 2], hf[4 * i + 3]);
            if (t == 4) asm volatile("fence.proxy.async.shared::cta;" ::: "memory");
          } else {
#pragma unroll
            for (int i = 0; i < 4; i++) st16(sb, hb + (t - 5) * 8192 + t16, i * 2048, hf[4 * i], hf[4 * i + 1], hf[4 * i + 2], hf[4 * i + 3]);
          }
          bar_sync(NB_ORD0 + wg, 256);
          mma_pass<128, PS_FF, 4, 2048, 0, false, true>(acc, a, DESC_SW128, t & 1, rel, NB_ORD1 - wg, sb, hb + t16, t == 7);
        }
        TS(9 + L * 20);
        const uint32_t hsm = wg * 8192 + tid_() * 16;
        geglu(IntC<16 + CH_LAST>(), hsm);
#pragma unroll
        for (int i = 0; i < 16; i++) a[128 + i] = hf[i];
      }
      TS(10 + L * 20);
      {
        const uint32_t xs = slot_addr(12) + wg * SLOT;
        auto verify = [&](int p, uint32_t t16) {
          mbar_wait(bar_full(12) + wg * 8, p & 1);
          TS(71 + L * 32 + p * 5);
          const uint32_t ta = p < 2, tb = (p & 1) ? ta : L ^ 1, nb = p ? 4 : 7, sh = p == 0;
          uint32_t m = 0;
#pragma unroll
          for (int s = 0; s < 4; s++) m |= (lds32(xs + s * 2048 + t16) ^ ta) | (lds32(xs + 8192 + ((s * 2048 + t16) >> sh)) ^ tb);
          if (p == 0) {
#pragma unroll
            for (int s = 4; s < 7; s++) m |= lds32(xs + 8192 + s * 1024 + t16 / 2) ^ tb;
          }
          if (__any_sync(0xffffffffu, m & 1)) {
#pragma unroll 1
            for (int s = 0; s < 4 + nb; s++) {
              const bool nar = sh && s >= 4;
              const uint32_t o = nar ? 4096 + s * 1024 + t16 / 2 : s * 2048 + t16;
              uint32_t v[4] = {0, 0, 0, 0};
              do {
                if (nar) ld8(v, sb, j * PSRC + o, OFF_P + 32768 - 8192);
                else ld16(v, sb, j * PSRC + (p & 1) * 16384 + o, OFF_P);
              } while (__any_sync(0xffffffffu, (v[0] ^ (s < 4 ? ta : tb)) & 1));
              sts64(xs + o, v[0], v[1]);
              if (!nar) sts64(xs + o + 8, v[2], v[3]);
            }
            asm volatile("fence.proxy.async.shared::cta;" ::: "memory");
          }
        };
        uint32_t t16 = (a[142] | a[143]) & P.zero;
#pragma unroll 1
        for (int p = 0; p < 4; p++) {
          float acc[64];
          bar_sync(NB_ORD0 + wg + (p ? 0 : t16), 256);
          TS(64 + L * 32 + p * 5);
          if (p == 0) { rel(9); rel(10); rel(11); }
          mma_pass<128, PS_FF, 4, 2048, 0, false, false>(acc, a, DESC_SW128, p & 1, rel, NB_ORD1 - wg, nullptr, 0, 0, 0, 0, 0, [&]() {
            t16 = tid_() * 16;
            if (p) verify(p - 1, t16);
          });
          TS(65 + L * 32 + p * 5);
          if (p == 1 || p == 2) add_piece<false>(acc, xs + t16);
          const uint32_t oa = ((j + (p < 3 ? 1 : 4)) & 7) * PSRC + (p & 1) * 16384 + t16;
#pragma unroll
          for (int i = 0; i < 4; i++)
            st16(sb, oa, OFF_P + i * 2048, (pack_bf16(acc[8 * i], acc[8 * i + 1]) & ~1u) | (p < 2), pack_bf16(acc[8 * i + 2], acc[8 * i + 3]),
                 pack_bf16(acc[8 * i + 4], acc[8 * i + 5]), pack_bf16(acc[8 * i + 6], acc[8 * i + 7]));
          if (p == 0) {
#pragma unroll
            for (int i = 0; i < 8; i++)
              send8(sb, j * 1024 + t16 / 2, OFF_P + 32768 + i * PSRC, xs + 15360 + t16 / 2, i, j,
                    (pack_bf16(acc[32 + 4 * i], acc[33 + 4 * i]) & ~1u) | (L ^ 1), pack_bf16(acc[34 + 4 * i], acc[35 + 4 * i]));
          } else {
            if (p == 2) add_piece<false>(acc + 32, xs + 8192 + t16);
            const uint32_t ob = ((j + (p < 3 ? 7 : 5)) & 7) * PSRC + (p & 1) * 16384 + t16, tb = p == 2 ? L ^ 1 : p < 2;
#pragma unroll
            for (int i = 4; i < 8; i++)
              st16(sb, ob, OFF_P + i * 2048, (pack_bf16(acc[8 * i], acc[8 * i + 1]) & ~1u) | tb, pack_bf16(acc[8 * i + 2], acc[8 * i + 3]),
                   pack_bf16(acc[8 * i + 4], acc[8 * i + 5]), pack_bf16(acc[8 * i + 6], acc[8 * i + 7]));
          }
          hint_post(hint);
          TS(68 + L * 32 + p * 5);
          if (p == 1) {
            float s0 = 0.f, s1 = 0.f, s2 = 0.f, s3 = 0.f;
#pragma unroll
            for (int s = 0; s < 8; s++) {
              uint32_t u, v;
              lds64(u, v, xs + 8192 + s * 1024 + t16 / 2);
              s0 += bf_lo(u); s1 += bf_hi(u); s2 += bf_lo(v); s3 += bf_hi(v);
            }
            sts64(ytail(wg * 2) + t16 / 2, pack_bf16(s0, s1), pack_bf16(s2, s3));
          }
          if (p < 3) bar_arrive(NB_FREE + wg, 160);
          TS(67 + L * 32 + p * 5);
        }
        float acc[32];
        add_piece<true>(acc, xs + t16);
        add_piece<false>(acc, xs + 8192 + t16);
        bar_arrive(NB_FREE + wg, 160);
        load_own(xr, sb, L * 3 * TILE, j);
        bar_sync(NB_ORD0 + wg, 256);
        TS(84 + L * 32);
        uint32_t t, yn[2];
        mma_pass<64, PS_FFA, 4, 2048, 0, false, false>(acc, a, DESC_SW128, 0, rel, wg ? -1 : NB_ORD1, nullptr, 0, 0, 0, 0, 0, [&]() {
          t = tid_();
          lds64(yn[0], yn[1], ytail(wg * 2) + t * 8);
          mbar_wait(bar_full(12) + wg * 8, 1);
#pragma unroll
          for (int i = 0; i < 8; i++) lds128(&a[4 * i], xs + i * 2048 + t * 16);
        });
        TS(11 + L * 20);
        while (true) {
          uint32_t m = 0;
#pragma unroll
          for (int i = 0; i < 8; i++) m |= a[4 * i];
          if (!__any_sync(0xffffffffu, m & 1)) break;
#pragma unroll
          for (int i = 0; i < 8; i++) ld16(&a[4 * i], sb, j * PSRC + t * 16, OFF_P + 16384 + i * 2048);
        }
        TS(12 + L * 20);
#pragma unroll
        for (int i = 0; i < 18; i++)
          xr[i] = bf2_add(xr[i], i < 16 ? pack_bf16(acc[2 * i] + (bf_lo(a[i]) + bf_lo(a[16 + i])), acc[2 * i + 1] + (bf_hi(a[i]) + bf_hi(a[16 + i]))) : yn[i - 16]);
        TS(18 + L * 20);
        if (L == 0) {
          store_own(xr, sb, OFF_X2, j, t);
          RowStats rs;
          rs.add<18>(xr);
          rs.store(sb, 8192 + j * 128, t);
          hint_post(hint);
        } else {
          const uint32_t l = t & 31, wb = xs + w * 512;
          __syncwarp();
#pragma unroll
          for (int i = 0; i < 4; i++) stsm4(wb + i * 2048 + (l & 24) * 16 + (((l & 7) ^ (i * 2 + (l >> 4))) << 4), xr[4 * i], xr[4 * i + 1], xr[4 * i + 2], xr[4 * i + 3]);
          stsm4(wb + 8192 + l * 16, xr[16], xr[17], 0, 0);
          __syncwarp();
          uint8_t* op = (uint8_t*)P.out + row_off(rb, wg, w * 32 + (l >> 3)) + j * 128 + (l & 7) * 16;
#pragma unroll
          for (int i = 0; i < 4; i++) {
            uint32_t r[4];
            lds128(r, wb + ((l & 6) << 10) + ((l & 1) * 2 + (i >> 1)) * 128 + (((((i & 1) * 4 + (l >> 3)) ^ l) & 7) << 4));
            *(uint4*)(op + i * 16 * DM) = make_uint4(r[0], r[1], r[2], r[3]);
          }
          uint32_t r[4];
          lds128(r, wb + 8192 + l * 16);
          if (l < 16) *(uint4*)((uint8_t*)P.out + row_off(rb, wg, t) + 1024 + j * 16) = make_uint4(r[0], r[1], r[2], r[3]);
        }
      }
      TS(13 + L * 20);
    }
    bar_sync(NB_WG + wg, 128);
    if (tid_() == 0) mbar_arrive(bar_empty(12));
  }
}

typedef CUresult (*EncodeFn)(CUtensorMap*, CUtensorMapDataType, cuuint32_t, void*, const cuuint64_t*, const cuuint64_t*, const cuuint32_t*,
                             const cuuint32_t*, CUtensorMapInterleave, CUtensorMapSwizzle, CUtensorMapL2promotion, CUtensorMapFloatOOBfill);

void encode(EncodeFn fn, CUtensorMap* m, const void* p, int rank, const cuuint64_t* dims, const cuuint64_t* str, const cuuint32_t* box) {
  const cuuint32_t es[3] = {1, 1, 1};
  fn(m, CU_TENSOR_MAP_DATA_TYPE_BFLOAT16, rank, const_cast<void*>(p), dims, str, box, es, CU_TENSOR_MAP_INTERLEAVE_NONE,
     CU_TENSOR_MAP_SWIZZLE_128B, CU_TENSOR_MAP_L2_PROMOTION_L2_256B, CU_TENSOR_MAP_FLOAT_OOB_FILL_NONE);
}

__global__ void probe_kernel() {}

void make_roles(uint8_t* role) {
  int cnt[8];
  cudaFuncSetAttribute(probe_kernel, cudaFuncAttributeMaxDynamicSharedMemorySize, SMEM_BYTES);
  cudaFuncSetAttribute(probe_kernel, cudaFuncAttributeNonPortableClusterSizeAllowed, 1);
  for (int r = 7; r >= 0; r--) {
    int n = 0;
    cudaLaunchConfig_t cfg = {};
    cudaLaunchAttribute at;
    at.id = cudaLaunchAttributeClusterDimension; at.val.clusterDim.x = 2 * (r < 3 ? 4 : r + 1); at.val.clusterDim.y = at.val.clusterDim.z = 1;
    cfg.gridDim = dim3(at.val.clusterDim.x); cfg.blockDim = dim3(384); cfg.dynamicSmemBytes = SMEM_BYTES; cfg.attrs = &at; cfg.numAttrs = 1;
    if (cudaOccupancyMaxActiveClusters(&n, probe_kernel, &cfg) != cudaSuccess) { cudaGetLastError(); n = r > 3 ? 8 : 8 + cnt[7]; }
    cnt[r] = r > 3 ? n : n - cnt[7];
  }
  int key[64], c = 0, total = 0, seg = 0;
  for (int r = 0; r < 8; r++) total += cnt[r];
  for (; c < 64 - total; c++) key[c] = -1;
  for (int r = 0; r < 8; r++) {
    if (r && cnt[r] != cnt[r - 1]) seg++;
    for (int i = 0; i < cnt[r] && c < 64; i++) key[c++] = seg * 16 + i;
  }
  int order[64], n = 0;
  bool used[64] = {};
  for (int pass = 0; pass < 2; pass++)
    for (int i = 0; i < 64; i++) {
      if (used[i]) continue;
      int m[4], k = 0;
      for (int q = i; q < 64 && k < 4; q++) if (!used[q] && (pass || (key[q] == key[i] && key[i] >= 0))) m[k++] = q;
      if (k == 4) for (int q = 0; q < 4; q++) { used[m[q]] = true; order[n++] = m[q]; }
    }
  for (int i = 0; i < 64; i++) role[order[i]] = (uint8_t)(((i >> 2) & 7) << 3 | (i >> 5) << 2 | (i & 3));
}

}

extern "C" void kernel_launch(void* const* d_in, const int* in_sizes, int n_in, void* d_out, int out_size) {
  (void)in_sizes; (void)n_in; (void)out_size;
  Params P = {};
  P.wqkv = (const __nv_bfloat16*)d_in[1]; P.wo = (const __nv_bfloat16*)d_in[2];
  P.out = (__nv_bfloat16*)d_out; P.zero = 0;
  cudaGetSymbolAddress((void**)&P.scr, g_scr);
  make_roles(P.role);
  void* fnp = nullptr; cudaDriverEntryPointQueryResult qr;
  cudaGetDriverEntryPoint("cuTensorMapEncodeTiled", &fnp, cudaEnableDefault, &qr);
  EncodeFn fn = (EncodeFn)fnp;
  CUtensorMap mx, mg, mu, md;
  { const cuuint64_t dims[3] = {DM, SEQ / 2, 2}, str[2] = {DM * 4, DM * 2}; const cuuint32_t box[3] = {64, 64, 2}; encode(fn, &mx, d_in[0], 3, dims, str, box); }
  { const cuuint64_t dims[2] = {DFF, DM}, str[1] = {DFF * 2}; const cuuint32_t box[2] = {64, 64}; encode(fn, &mg, d_in[4], 2, dims, str, box); encode(fn, &mu, d_in[5], 2, dims, str, box); }
  { const cuuint64_t dims[2] = {DM, DFF}, str[1] = {DM * 2}; const cuuint32_t box[2] = {64, 64}; encode(fn, &md, d_in[6], 2, dims, str, box); }
  cudaFuncSetAttribute(fused_kernel, cudaFuncAttributeMaxDynamicSharedMemorySize, SMEM_BYTES);
  fused_kernel<<<128, 384, SMEM_BYTES, cudaStreamPerThread>>>(P, mx, mg, mu, md);
}
```

```cpp
#include <cuda_runtime.h>
#include <cuda_bf16.h>
#include <cuda.h>
#include <stdint.h>

#define TIMING 0
#define TRACE 0

namespace {

constexpr int SEQ = 2048, DM = 576, DFF = 4608;
constexpr int KV_LEAD = 5;
constexpr int D_KV = 6, D_WO = 3, D_T0 = 5;
constexpr int N_UP = 26, N_WO = 12;
constexpr int PF_AHEAD = 2;
constexpr int CH_LAST = 3;
constexpr uint32_t SB = 1024;
constexpr uint32_t SLOT = 16384;
constexpr uint32_t PSLOT = 13824;
constexpr uint32_t BARS = SB + 14 * SLOT;
constexpr int SMEM_BYTES = 14 * SLOT + 256 + 2560 + (TRACE ? 256 : 0);
__host__ __device__ constexpr uint32_t slot_addr(int s) { return SB + s * SLOT; }
__host__ __device__ constexpr uint32_t bar_full(int s) { return BARS + 8 * s; }
__host__ __device__ constexpr uint32_t bar_empty(int s) { return BARS + 128 + 8 * s; }
enum { NB_ORD0 = 1, NB_ORD1 = 2, NB_WG = 3  , NB_HALO = 5  , NB_FREE = 7  , NB_PUB = 9   };
constexpr uint32_t SM_EPOCH = BARS + 120;
__host__ __device__ constexpr uint32_t ytail(uint32_t k) { return k < 3 ? slot_addr(9) + PSLOT + k * SLOT : BARS + 256; }
constexpr uint32_t KSTG = 9 * 1152;

constexpr uint32_t TILE = 36 * 2048;
constexpr uint32_t OFF_X1 = 0  , OFF_O = TILE, OFF_X2 = 2 * TILE, OFF_ST = 4 * TILE  ;
constexpr uint32_t PSRC = 2 * 16384 + 7 * 1024;
constexpr uint32_t OFF_P = OFF_ST + 3 * 4096, OFF_HALO = OFF_P + 8 * PSRC  , OFF_HINT = OFF_HALO + 2 * 8 * 3072  ,
                   OFF_H = OFF_HINT + 16 * 128  , STRM = OFF_H + 8 * 24576;
constexpr uint32_t OFF_WPACK = 32 * STRM, OFF_FLAGS = OFF_WPACK + 8 * 24 * PSLOT;
__device__ __align__(1024) uint8_t g_scr[OFF_FLAGS + (8 + 64 + 128) * 32];

__device__ __forceinline__ uint32_t smem_u32(const void* p) { return (uint32_t)__cvta_generic_to_shared(p); }
extern __shared__ __align__(1024) uint8_t smem_raw[];
__device__ __forceinline__ uint32_t win() { return (blockIdx.x & 1) << 24; }
#define SA(A, W) ".reg .u32 sa;\nadd.u32 sa, " A ", " W ";\n"
__device__ __forceinline__ void mbar_init(uint32_t bar, uint32_t cnt) { asm volatile("{\n" SA("%0", "%2") "mbarrier.init.shared::cta.b64 [sa], %1;\n}" ::"r"(bar), "r"(cnt), "r"(win())); }
__device__ __forceinline__ void mbar_expect_tx(uint32_t bar, uint32_t bytes) { asm volatile("{\n" SA("%0", "%2") "mbarrier.arrive.expect_tx.shared::cta.b64 _, [sa], %1;\n}" ::"r"(bar), "r"(bytes), "r"(win()) : "memory"); }
__device__ __forceinline__ void mbar_arrive(uint32_t bar) { asm volatile("{\n" SA("%0", "%1") "mbarrier.arrive.shared::cta.b64 _, [sa];\n}" ::"r"(bar), "r"(win()) : "memory"); }
__device__ __forceinline__ uint32_t lds32(uint32_t a) { uint32_t v; asm volatile("{\n" SA("%1", "%2") "ld.shared.u32 %0, [sa];\n}" : "=r"(v) : "r"(a), "r"(win()) : "memory"); return v; }
__device__ __forceinline__ void lds64(uint32_t& x, uint32_t& y, uint32_t a) { asm volatile("{\n" SA("%2", "%3") "ld.shared.v2.u32 {%0,%1}, [sa];\n}" : "=r"(x), "=r"(y) : "r"(a), "r"(win()) : "memory"); }
__device__ __forceinline__ void lds128(uint32_t* v, uint32_t a) {
  asm volatile("{\n" SA("%4", "%5") "ld.shared.v4.u32 {%0,%1,%2,%3}, [sa];\n}" : "=r"(v[0]), "=r"(v[1]), "=r"(v[2]), "=r"(v[3]) : "r"(a), "r"(win()) : "memory");
}
__device__ __forceinline__ void stsm4(uint32_t a, uint32_t x, uint32_t y, uint32_t z, uint32_t w) {
  asm volatile("{\n" SA("%0", "%5") "stmatrix.sync.aligned.m8n8.x4.shared.b16 [sa], {%1,%2,%3,%4};\n}" ::"r"(a), "r"(x), "r"(y), "r"(z), "r"(w), "r"(win()) : "memory");
}
__device__ __forceinline__ void ldsm4(uint32_t* v, uint32_t a) {
  asm volatile("{\n" SA("%4", "%5") "ldmatrix.sync.aligned.m8n8.x4.shared.b16 {%0,%1,%2,%3}, [sa];\n}" : "=r"(v[0]), "=r"(v[1]), "=r"(v[2]), "=r"(v[3]) : "r"(a), "r"(win()) : "memory");
}
__device__ __forceinline__ void ldsm4t(uint32_t* v, uint32_t a) {
  asm volatile("{\n" SA("%4", "%5") "ldmatrix.sync.aligned.m8n8.x4.trans.shared.b16 {%0,%1,%2,%3}, [sa];\n}" : "=r"(v[0]), "=r"(v[1]), "=r"(v[2]), "=r"(v[3]) : "r"(a), "r"(win()) : "memory");
}
__device__ __forceinline__ void sts32(uint32_t a, uint32_t x) { asm volatile("{\n" SA("%0", "%2") "st.shared.u32 [sa], %1;\n}" ::"r"(a), "r"(x), "r"(win()) : "memory"); }
__device__ __forceinline__ void sts64(uint32_t a, uint32_t x, uint32_t y) { asm volatile("{\n" SA("%0", "%3") "st.shared.v2.u32 [sa], {%1,%2};\n}" ::"r"(a), "r"(x), "r"(y), "r"(win()) : "memory"); }
__device__ __forceinline__ void sts128(uint32_t a, uint32_t x, uint32_t y, uint32_t z, uint32_t w) {
  asm volatile("{\n" SA("%0", "%5") "st.shared.v4.u32 [sa], {%1,%2,%3,%4};\n}" ::"r"(a), "r"(x), "r"(y), "r"(z), "r"(w), "r"(win()) : "memory");
}
__device__ __forceinline__ void mbar_wait(uint32_t bar, uint32_t parity) {
  asm volatile("{\n.reg .pred p;\n" SA("%0", "%2") "LAB_WAIT:\nmbarrier.try_wait.parity.shared::cta.b64 p, [sa], %1;\n@!p bra LAB_WAIT;\n}" ::"r"(bar), "r"(parity), "r"(win()) : "memory");
}
__device__ __forceinline__ void timed_wait(uint32_t bar, uint32_t par) {
  asm volatile("{\n.reg .pred p;\n.reg .u64 t0, t1;\nmov.u64 t0, %%globaltimer;\nLAB_WD:\n"
               "mbarrier.try_wait.parity.shared::cta.b64 p, [%0], %1, 100000;\n@p bra LAB_OK;\n"
               "mov.u64 t1, %%globaltimer;\nsub.u64 t1, t1, t0;\nsetp.lt.u64 p, t1, 2000000000;\n@p bra LAB_WD;\ntrap;\nLAB_OK:\n}" ::"r"(bar + win()), "r"(par) : "memory");
}
__device__ __forceinline__ void flag_wait(const unsigned* flag, unsigned target) {
  asm volatile("{\n.reg .pred p;\n.reg .u32 v;\nLAB_WAIT:\nld.acquire.gpu.global.u32 v, [%0];\nsub.u32 v, v, %1;\n"
               "setp.lt.s32 p, v, 0;\nvote.sync.any.pred p, p, 0xffffffff;\n@p nanosleep.u32 100;\n@p bra LAB_WAIT;\n}" ::"l"(flag), "r"(target) : "memory");
}
__device__ __forceinline__ void hint_post(uint8_t* p) {
  __syncwarp();
  asm volatile("{\n.reg .pred p;\nelect.sync _|p, 0xffffffff;\n@p red.relaxed.gpu.global.add.u32 [%0], 1;\n}" ::"l"(p) : "memory");
}
__device__ __forceinline__ void hint_wait(const uint8_t* p, uint32_t target) {
  asm volatile("{\n.reg .pred p;\n.reg .u32 v;\nLAB_WAIT:\nld.relaxed.gpu.global.u32 v, [%0];\nsub.u32 v, v, %1;\n"
               "setp.lt.s32 p, v, 0;\nvote.sync.any.pred p, p, 0xffffffff;\n@p bra LAB_WAIT;\n}" ::"l"(p), "r"(target) : "memory");
}
__device__ __forceinline__ void flag_signal(unsigned* flag) { asm volatile("red.release.gpu.global.add.u32 [%0], 1;" ::"l"(flag) : "memory"); }
struct Rel {
  bool on; uint32_t base;
  uint32_t tr;
  __device__ __forceinline__ void operator()(int s) const {
    if (on) asm volatile("{\n" SA("%0", "%1") "mbarrier.arrive.shared::cluster.b64 _, [sa];\n}" ::"r"(bar_empty(s)), "r"(base) : "memory");
  }
};
__device__ __forceinline__ uint32_t cta_window(uint32_t rank) { uint32_t a; asm("mapa.shared::cluster.u32 %0, %1, %2;" : "=r"(a) : "r"(0), "r"(rank)); return a; }
#define ELECT ".reg .pred e;\nelect.sync _|e, 0xffffffff;\n"
__device__ __forceinline__ void w_expect_tx(uint32_t bar, uint32_t bytes) {
  asm volatile("{\n" ELECT "@e mbarrier.arrive.expect_tx.shared::cta.b64 _, [%0], %1;\n}" ::"r"(bar), "r"(bytes) : "memory");
}
__device__ __forceinline__ void w_tma_2d_mc(uint32_t dst, const CUtensorMap* m, int c0, int c1, uint32_t bar) {
  asm volatile("{\n" ELECT "@e cp.async.bulk.tensor.2d.shared::cluster.global.mbarrier::complete_tx::bytes.multicast::cluster [%0], [%1, {%3, %4}], [%2], %5;\n}"
               ::"r"(dst), "l"(m), "r"(bar), "r"(c0), "r"(c1), "h"((uint16_t)3) : "memory");
}
__device__ __forceinline__ void w_bulk_load_mc(uint32_t dst, const void* src, uint32_t bytes, uint32_t bar) {
  asm volatile("{\n" ELECT "@e cp.async.bulk.shared::cluster.global.mbarrier::complete_tx::bytes.multicast::cluster [%0], [%1], %2, [%3], %4;\n}"
               ::"r"(dst), "l"(src), "r"(bytes), "r"(bar), "h"((uint16_t)3) : "memory");
}
__device__ __forceinline__ void w_bulk_load(uint32_t dst, const void* src, uint32_t bytes, uint32_t bar) {
  asm volatile("{\n" ELECT "@e cp.async.bulk.shared::cluster.global.mbarrier::complete_tx::bytes [%0], [%1], %2, [%3];\n}" ::"r"(dst), "l"(src), "r"(bytes), "r"(bar) : "memory");
}
__device__ __forceinline__ void w_l2_prefetch(const void* src, uint32_t bytes) { asm volatile("{\n" ELECT "@e cp.async.bulk.prefetch.L2.global [%0], %1;\n}" ::"l"(src), "r"(bytes) : "memory"); }
__device__ __forceinline__ void w_tma_prefetch(const CUtensorMap* m, int c0, int c1) {
  asm volatile("{\n" ELECT "@e cp.async.bulk.prefetch.tensor.2d.L2.global [%0, {%1, %2}];\n}" ::"l"(m), "r"(c0), "r"(c1) : "memory");
}
__device__ __forceinline__ void tma_3d(uint32_t dst, const CUtensorMap* m, int c0, int c1, int c2, uint32_t bar) {
  asm volatile("cp.async.bulk.tensor.3d.shared::cluster.global.mbarrier::complete_tx::bytes [%0], [%1, {%3, %4, %5}], [%2];"
               ::"r"(dst), "l"(m), "r"(bar), "r"(c0), "r"(c1), "r"(c2) : "memory");
}
__device__ __forceinline__ void wg_fence() { asm volatile("wgmma.fence.sync.aligned;" ::: "memory"); }
__device__ __forceinline__ void wg_commit() { asm volatile("wgmma.commit_group.sync.aligned;" ::: "memory"); }
template <int N> __device__ __forceinline__ void wg_wait() { asm volatile("wgmma.wait_group.sync.aligned %0;" ::"n"(N) : "memory"); }
__device__ __forceinline__ void bar_sync(int id, int n) { asm volatile("bar.sync %0, %1;" ::"r"(id), "r"(n) : "memory"); }
__device__ __forceinline__ void bar_arrive(int id, int n) { asm volatile("bar.arrive %0, %1;" ::"r"(id), "r"(n) : "memory"); }
__device__ __forceinline__ uint32_t pack_bf16(float lo, float hi) { uint32_t r; asm("cvt.rn.bf16x2.f32 %0, %1, %2;" : "=r"(r) : "f"(hi), "f"(lo)); return r; }
__device__ __forceinline__ float bf_lo(uint32_t w) { return __uint_as_float(w << 16); }
__device__ __forceinline__ float bf_hi(uint32_t w) { return __uint_as_float(w & 0xffff0000u); }
__device__ __forceinline__ float bf_round(float x) { return bf_lo(pack_bf16(x, 0.f)); }
__device__ __forceinline__ uint32_t bf2_sub(uint32_t a, uint32_t b) { uint32_t r; asm("sub.rn.bf16x2 %0, %1, %2;" : "=r"(r) : "r"(a), "r"(b)); return r; }
__device__ __forceinline__ uint32_t bf2_add(uint32_t a, uint32_t b) { uint32_t r; asm("add.rn.bf16x2 %0, %1, %2;" : "=r"(r) : "r"(a), "r"(b)); return r; }
#define GADDR(B, O, I) "cvt.u64.u32 ad, " O ";\nadd.u64 ad, ad, " B ";\nadd.u64 ad, ad, " I ";\n"
__device__ __forceinline__ void ld16(uint32_t* v, const uint8_t* ub, uint32_t off, uint32_t imm) {
  asm volatile("{\n.reg .b128 z;\n.reg .b64 x, y, ad;\n" GADDR("%4", "%5", "%6") "ld.relaxed.gpu.global.b128 z, [ad];\n"
               "mov.b128 {x, y}, z;\nmov.b64 {%0,%1}, x;\nmov.b64 {%2,%3}, y;\n}"
               : "=r"(v[0]), "=r"(v[1]), "=r"(v[2]), "=r"(v[3]) : "l"(ub), "r"(off), "l"((uint64_t)imm) : "memory");
}
__device__ __forceinline__ void ld8(uint32_t* v, const uint8_t* ub, uint32_t off, uint32_t imm) {
  asm volatile("{\n.reg .b64 x, ad;\n" GADDR("%2", "%3", "%4") "ld.relaxed.gpu.global.b64 x, [ad];\nmov.b64 {%0,%1}, x;\n}"
               : "=r"(v[0]), "=r"(v[1]) : "l"(ub), "r"(off), "l"((uint64_t)imm) : "memory");
}
__device__ __forceinline__ void st16(uint8_t* ub, uint32_t off, uint32_t imm, uint32_t a, uint32_t b, uint32_t c, uint32_t d) {
  asm volatile("{\n.reg .b128 z;\n.reg .b64 x, y, ad;\n" GADDR("%0", "%1", "%2") "mov.b64 x, {%3,%4};\nmov.b64 y, {%5,%6};\nmov.b128 z, {x, y};\n"
               "st.relaxed.gpu.global.b128 [ad], z;\n}" ::"l"(ub), "r"(off), "l"((uint64_t)imm), "r"(a), "r"(b), "r"(c), "r"(d) : "memory");
}
__device__ __forceinline__ void st8(uint8_t* ub, uint32_t off, uint32_t imm, uint32_t a, uint32_t b) {
  asm volatile("{\n.reg .b64 x, ad;\n" GADDR("%0", "%1", "%2") "mov.b64 x, {%3,%4};\nst.relaxed.gpu.global.b64 [ad], x;\n}"
               ::"l"(ub), "r"(off), "l"((uint64_t)imm), "r"(a), "r"(b) : "memory");
}
__device__ __forceinline__ void send8(uint8_t* ub, uint32_t off, uint32_t imm, uint32_t sm, int i, int j, uint32_t a, uint32_t b) {
  asm volatile("{\n.reg .pred p, q, e;\n.reg .b64 x, ad;\n" SA("%3", "%8") GADDR("%0", "%1", "%2")
               "setp.lt.s32 p, %4, %5;\nsetp.gt.s32 q, %4, %5;\nsetp.eq.s32 e, %4, %5;\nmov.b64 x, {%6,%7};\n"
               "@p st.relaxed.gpu.global.b64 [ad+-1024], x;\n@q st.relaxed.gpu.global.b64 [ad], x;\n@e st.shared.v2.u32 [sa], {%6,%7};\n}"
               ::"l"(ub), "r"(off), "l"((uint64_t)imm), "r"(sm), "r"(i), "r"(j), "r"(a), "r"(b), "r"(win()) : "memory");
}
__device__ __forceinline__ uint4 ldg_line(const void* p) {
  uint4 v; asm volatile("ld.global.nc.L2::128B.v4.u32 {%0,%1,%2,%3}, [%4];" : "=r"(v.x), "=r"(v.y), "=r"(v.z), "=r"(v.w) : "l"(p)); return v;
}
__device__ __forceinline__ void stg4(void* ub, uint32_t off, uint32_t imm, uint32_t v) {
  asm volatile("{\n.reg .b64 ad;\n" GADDR("%0", "%1", "%2") "st.global.u32 [ad], %3;\n}" ::"l"(ub), "r"(off), "l"((uint64_t)imm), "r"(v) : "memory");
}
__device__ __forceinline__ uint32_t tid_() { uint32_t t; asm volatile("mov.u32 %0, %%tid.x;" : "=r"(t)); return t & 127; }
__device__ __forceinline__ uint32_t token() { uint32_t c; asm volatile("mov.u32 %0, %%clock;" : "=r"(c) :: "memory"); return c | 1; }
__device__ __forceinline__ uint32_t nz(uint32_t w) { return w ? w : 0x8000u; }
__device__ __forceinline__ void mma16816(float (&c)[4], uint32_t a0, uint32_t a1, uint32_t a2, uint32_t a3, uint32_t b0, uint32_t b1) {
  asm("mma.sync.aligned.m16n8k16.row.col.f32.bf16.bf16.f32 {%0,%1,%2,%3}, {%4,%5,%6,%7}, {%8,%9}, {%0,%1,%2,%3};"
               : "+f"(c[0]), "+f"(c[1]), "+f"(c[2]), "+f"(c[3]) : "r"(a0), "r"(a1), "r"(a2), "r"(a3), "r"(b0), "r"(b1));
}
__device__ __forceinline__ void mma1688(float (&c)[4], uint32_t a0, uint32_t a1, uint32_t b0) {
  asm("mma.sync.aligned.m16n8k8.row.col.f32.bf16.bf16.f32 {%0,%1,%2,%3}, {%4,%5}, {%6}, {%0,%1,%2,%3};"
               : "+f"(c[0]), "+f"(c[1]), "+f"(c[2]), "+f"(c[3]) : "r"(a0), "r"(a1), "r"(b0));
}
__device__ __forceinline__ float ex2(float x) { float r; asm("ex2.approx.ftz.f32 %0, %1;" : "=f"(r) : "f"(x)); return r; }
__device__ __forceinline__ float quad_sum(float v) { v += __shfl_xor_sync(0xffffffffu, v, 1); v += __shfl_xor_sync(0xffffffffu, v, 2); return v; }
__device__ __forceinline__ float quad_max(float v) { v = fmaxf(v, __shfl_xor_sync(0xffffffffu, v, 1)); v = fmaxf(v, __shfl_xor_sync(0xffffffffu, v, 2)); return v; }

__device__ __forceinline__ void wgmma_rs_n64(float (&d)[32], uint32_t a0, uint32_t a1, uint32_t a2, uint32_t a3, uint64_t desc, int scale_d) {
  asm volatile("{\n.reg .pred p;\nsetp.ne.b32 p, %37, 0;\n"
    "wgmma.mma_async.sync.aligned.m64n64k16.f32.bf16.bf16 "
    "{%0, %1, %2, %3, %4, %5, %6, %7, %8, %9, %10, %11, %12, %13, %14, %15, %16, %17, %18, %19, %20, %21, %22, %23, %24, %25, %26, %27, %28, %29, %30, %31}, "
    "{%32, %33, %34, %35}, %36, p, 1, 1, 1;\n}\n"
    : "+f"(d[0]), "+f"(d[1]), "+f"(d[2]), "+f"(d[3]), "+f"(d[4]), "+f"(d[5]), "+f"(d[6]), "+f"(d[7]), "+f"(d[8]), "+f"(d[9]), "+f"(d[10]), "+f"(d[11]), "+f"(d[12]), "+f"(d[13]), "+f"(d[14]), "+f"(d[15]), "+f"(d[16]), "+f"(d[17]), "+f"(d[18]), "+f"(d[19]), "+f"(d[20]), "+f"(d[21]), "+f"(d[22]), "+f"(d[23]), "+f"(d[24]), "+f"(d[25]), "+f"(d[26]), "+f"(d[27]), "+f"(d[28]), "+f"(d[29]), "+f"(d[30]), "+f"(d[31])
    : "r"(a0), "r"(a1), "r"(a2), "r"(a3), "l"(desc), "r"(scale_d));
}

__device__ __forceinline__ void wgmma_rs_n72(float (&d)[36], uint32_t a0, uint32_t a1, uint32_t a2, uint32_t a3, uint64_t desc, int scale_d) {
  asm volatile("{\n.reg .pred p;\nsetp.ne.b32 p, %41, 0;\n"
    "wgmma.mma_async.sync.aligned.m64n72k16.f32.bf16.bf16 "
    "{%0, %1, %2, %3, %4, %5, %6, %7, %8, %9, %10, %11, %12, %13, %14, %15, %16, %17, %18, %19, %20, %21, %22, %23, %24, %25, %26, %27, %28, %29, %30, %31, %32, %33, %34, %35}, "
    "{%36, %37, %38, %39}, %40, p, 1, 1, 1;\n}\n"
    : "+f"(d[0]), "+f"(d[1]), "+f"(d[2]), "+f"(d[3]), "+f"(d[4]), "+f"(d[5]), "+f"(d[6]), "+f"(d[7]), "+f"(d[8]), "+f"(d[9]), "+f"(d[10]), "+f"(d[11]), "+f"(d[12]), "+f"(d[13]), "+f"(d[14]), "+f"(d[15]), "+f"(d[16]), "+f"(d[17]), "+f"(d[18]), "+f"(d[19]), "+f"(d[20]), "+f"(d[21]), "+f"(d[22]), "+f"(d[23]), "+f"(d[24]), "+f"(d[25]), "+f"(d[26]), "+f"(d[27]), "+f"(d[28]), "+f"(d[29]), "+f"(d[30]), "+f"(d[31]), "+f"(d[32]), "+f"(d[33]), "+f"(d[34]), "+f"(d[35])
    : "r"(a0), "r"(a1), "r"(a2), "r"(a3), "l"(desc), "r"(scale_d));
}

__device__ __forceinline__ void wgmma_rs_n128(float (&d)[64], uint32_t a0, uint32_t a1, uint32_t a2, uint32_t a3, uint64_t desc, int scale_d) {
  asm volatile("{\n.reg .pred p;\nsetp.ne.b32 p, %69, 0;\n"
    "wgmma.mma_async.sync.aligned.m64n128k16.f32.bf16.bf16 "
    "{%0, %1, %2, %3, %4, %5, %6, %7, %8, %9, %10, %11, %12, %13, %14, %15, %16, %17, %18, %19, %20, %21, %22, %23, %24, %25, %26, %27, %28, %29, %30, %31, %32, %33, %34, %35, %36, %37, %38, %39, %40, %41, %42, %43, %44, %45, %46, %47, %48, %49, %50, %51, %52, %53, %54, %55, %56, %57, %58, %59, %60, %61, %62, %63}, "
    "{%64, %65, %66, %67}, %68, p, 1, 1, 1;\n}\n"
    : "+f"(d[0]), "+f"(d[1]), "+f"(d[2]), "+f"(d[3]), "+f"(d[4]), "+f"(d[5]), "+f"(d[6]), "+f"(d[7]), "+f"(d[8]), "+f"(d[9]), "+f"(d[10]), "+f"(d[11]), "+f"(d[12]), "+f"(d[13]), "+f"(d[14]), "+f"(d[15]), "+f"(d[16]), "+f"(d[17]), "+f"(d[18]), "+f"(d[19]), "+f"(d[20]), "+f"(d[21]), "+f"(d[22]), "+f"(d[23]), "+f"(d[24]), "+f"(d[25]), "+f"(d[26]), "+f"(d[27]), "+f"(d[28]), "+f"(d[29]), "+f"(d[30]), "+f"(d[31]), "+f"(d[32]), "+f"(d[33]), "+f"(d[34]), "+f"(d[35]), "+f"(d[36]), "+f"(d[37]), "+f"(d[38]), "+f"(d[39]), "+f"(d[40]), "+f"(d[41]), "+f"(d[42]), "+f"(d[43]), "+f"(d[44]), "+f"(d[45]), "+f"(d[46]), "+f"(d[47]), "+f"(d[48]), "+f"(d[49]), "+f"(d[50]), "+f"(d[51]), "+f"(d[52]), "+f"(d[53]), "+f"(d[54]), "+f"(d[55]), "+f"(d[56]), "+f"(d[57]), "+f"(d[58]), "+f"(d[59]), "+f"(d[60]), "+f"(d[61]), "+f"(d[62]), "+f"(d[63])
    : "r"(a0), "r"(a1), "r"(a2), "r"(a3), "l"(desc), "r"(scale_d));
}

__device__ __forceinline__ void wgmma_rs_n144(float (&d)[72], uint32_t a0, uint32_t a1, uint32_t a2, uint32_t a3, uint64_t desc, int scale_d) {
  asm volatile("{\n.reg .pred p;\nsetp.ne.b32 p, %77, 0;\n"
    "wgmma.mma_async.sync.aligned.m64n144k16.f32.bf16.bf16 "
    "{%0, %1, %2, %3, %4, %5, %6, %7, %8, %9, %10, %11, %12, %13, %14, %15, %16, %17, %18, %19, %20, %21, %22, %23, %24, %25, %26, %27, %28, %29, %30, %31, %32, %33, %34, %35, %36, %37, %38, %39, %40, %41, %42, %43, %44, %45, %46, %47, %48, %49, %50, %51, %52, %53, %54, %55, %56, %57, %58, %59, %60, %61, %62, %63, %64, %65, %66, %67, %68, %69, %70, %71}, "
    "{%72, %73, %74, %75}, %76, p, 1, 1, 1;\n}\n"
    : "+f"(d[0]), "+f"(d[1]), "+f"(d[2]), "+f"(d[3]), "+f"(d[4]), "+f"(d[5]), "+f"(d[6]), "+f"(d[7]), "+f"(d[8]), "+f"(d[9]), "+f"(d[10]), "+f"(d[11]), "+f"(d[12]), "+f"(d[13]), "+f"(d[14]), "+f"(d[15]), "+f"(d[16]), "+f"(d[17]), "+f"(d[18]), "+f"(d[19]), "+f"(d[20]), "+f"(d[21]), "+f"(d[22]), "+f"(d[23]), "+f"(d[24]), "+f"(d[25]), "+f"(d[26]), "+f"(d[27]), "+f"(d[28]), "+f"(d[29]), "+f"(d[30]), "+f"(d[31]), "+f"(d[32]), "+f"(d[33]), "+f"(d[34]), "+f"(d[35]), "+f"(d[36]), "+f"(d[37]), "+f"(d[38]), "+f"(d[39]), "+f"(d[40]), "+f"(d[41]), "+f"(d[42]), "+f"(d[43]), "+f"(d[44]), "+f"(d[45]), "+f"(d[46]), "+f"(d[47]), "+f"(d[48]), "+f"(d[49]), "+f"(d[50]), "+f"(d[51]), "+f"(d[52]), "+f"(d[53]), "+f"(d[54]), "+f"(d[55]), "+f"(d[56]), "+f"(d[57]), "+f"(d[58]), "+f"(d[59]), "+f"(d[60]), "+f"(d[61]), "+f"(d[62]), "+f"(d[63]), "+f"(d[64]), "+f"(d[65]), "+f"(d[66]), "+f"(d[67]), "+f"(d[68]), "+f"(d[69]), "+f"(d[70]), "+f"(d[71])
    : "r"(a0), "r"(a1), "r"(a2), "r"(a3), "l"(desc), "r"(scale_d));
}

template <int N> struct WG;
template <> struct WG<64>  { static __device__ __forceinline__ void f(float (&d)[32], const uint32_t* a, uint64_t ds, int s) { wgmma_rs_n64(d, a[0], a[1], a[2], a[3], ds, s); } };
template <> struct WG<72>  { static __device__ __forceinline__ void f(float (&d)[36], const uint32_t* a, uint64_t ds, int s) { wgmma_rs_n72(d, a[0], a[1], a[2], a[3], ds, s); } };
template <> struct WG<128> { static __device__ __forceinline__ void f(float (&d)[64], const uint32_t* a, uint64_t ds, int s) { wgmma_rs_n128(d, a[0], a[1], a[2], a[3], ds, s); } };
template <> struct WG<144> { static __device__ __forceinline__ void f(float (&d)[72], const uint32_t* a, uint64_t ds, int s) { wgmma_rs_n144(d, a[0], a[1], a[2], a[3], ds, s); } };

constexpr uint64_t DESC_SW128 = ((uint64_t)(8192 >> 4) << 16) | ((uint64_t)(1024 >> 4) << 32) | (1ull << 62);
constexpr uint64_t DESC_KV = ((uint64_t)(128 >> 4) << 16) | ((uint64_t)(768 >> 4) << 32);
constexpr uint64_t DESC_Q = ((uint64_t)(128 >> 4) << 16) | ((uint64_t)(1536 >> 4) << 32);

template <int V> struct IntC { static constexpr int value = V; };
enum { PS_KV, PS_Q, PS_WO, PS_FF, PS_FFA   };
template <int PS> __host__ __device__ constexpr int pass_slot(int i) {
  return PS == PS_KV ? (i < 3 ? 9 + i : i - 3) : PS == PS_WO ? 6 + i : i;
}

__device__ __forceinline__ void load_frag(uint32_t (&a)[144], int i, const uint8_t* sb, uint32_t uo, uint32_t t) {
  if (i < 32) ld16(&a[4 * i], sb, uo + t * 16, i * 2048);
  else { ld8(&a[4 * i], sb, uo + t * 8, i * 2048); ld8(&a[4 * i + 2], sb, uo + t * 8, i * 2048 + 1024); }
}
__device__ __forceinline__ void store_own(const uint32_t (&y)[18], uint8_t* sb, uint32_t uo, int j, uint32_t t) {
#pragma unroll
  for (int i = 0; i < 4; i++) st16(sb, uo + j * 8192 + t * 16, i * 2048, nz(y[4 * i]), y[4 * i + 1], y[4 * i + 2], y[4 * i + 3]);
  st8(sb, uo + j * 1024 + t * 8, 65536, nz(y[16]), y[17]);
}
__device__ __forceinline__ void load_own(uint32_t* y, const uint8_t* sb, uint32_t uo, int j) {
  const uint32_t t = tid_();
#pragma unroll
  for (int i = 0; i < 4; i++) ld16(&y[4 * i], sb, uo + j * 8192 + t * 16, i * 2048);
  ld8(&y[16], sb, uo + j * 1024 + t * 8, 65536);
}

#define TR(i) do {} while (0)
struct NoTail { __device__ __forceinline__ void operator()() const {} };
template <int N, int PS, int KPS, int KSTEP, int CHK, bool SUB, bool HREL = false, class Tail = NoTail>
__device__ __forceinline__ void mma_pass(float (&acc)[N / 2], uint32_t (&a)[144], uint64_t desc, uint32_t par, const Rel& rel, int bar_id,
                                         const uint8_t* sb = nullptr, uint32_t uo = 0, uint32_t flag = 0, uint32_t m0 = 0, uint32_t m1 = 0, uint32_t park = 0, Tail tail = Tail()) {
  constexpr int NS = 36 / KPS;
  auto check = [&](int lo, int hi, uint32_t m0_) {
    auto missing = [&]() {
      uint32_t u[3] = {m0_, m0_, m0_};
#pragma unroll
      for (int i = hi - 1; i >= lo; i--) {
        u[i % 3] = min(u[i % 3], a[4 * i]);
        if (i >= 32) u[i % 3] = min(u[i % 3], a[4 * i + 2]);
      }
      return __any_sync(0xffffffffu, (min(u[0], min(u[1], u[2])) | flag) == 0);
    };
    if (__builtin_expect(missing(), 0)) {
      do {
        const uint32_t t = tid_();
#pragma unroll
        for (int i = lo; i < hi; i++) load_frag(a, i, sb, uo, t);
      } while (missing());
    }
  };
#pragma unroll
  for (int s = 0; s < NS; s++) {
    const int sl = pass_slot<PS>(s);
    if (CHK && s == 0 && !SUB) check(0, CHK * KPS, ~0u);
    if (CHK && s == CHK) check(CHK * KPS, 36, token());
    if (SUB) {
#pragma unroll
      for (int i = s * KPS * 4; i < (s + 1) * KPS * 4; i += 2) { a[i] = bf2_sub(a[i], m0); a[i + 1] = bf2_sub(a[i + 1], m1); }
    }
    if (PS == PS_KV && s == 0) sts128(park + tid_() * 16, a[0], a[1], a[2], a[3]);
    constexpr int TB = PS == PS_KV ? 0 : PS == PS_Q ? 26 : PS == PS_WO ? 40 : SUB ? 54 : PS == PS_FFA ? 74 : -1;
    if (TB >= 0) TR(TB + 2 * s);
    mbar_wait(bar_full(sl), sl < 9 ? par : par ^ 1);
    if (TB >= 0) TR(TB + 2 * s + 1);
    wg_fence();
#pragma unroll
    for (int kk = 0; kk < KPS; kk++)
      WG<N>::f(acc, &a[(s * KPS + kk) * 4], desc + ((slot_addr(sl) + kk * KSTEP) >> 4), (s | kk) || PS == PS_FFA);
    wg_commit();
    if (CHK && s < 2 && N_UP < 36 && !flag) {
      const uint32_t t = tid_();
#pragma unroll
      for (int i = s ? (N_UP + 36) / 2 : N_UP; i < (s ? 36 : (N_UP + 36) / 2); i++) load_frag(a, i, sb, uo, t);
    }
    if (s == (PS == PS_KV ? KV_LEAD : NS - 1) && bar_id >= 0) bar_arrive(bar_id, 256);
    if (s > 0) {
      wg_wait<1>();
      if (!(PS == PS_WO && s > 3)) rel(pass_slot<PS>(s - 1));
    }
    if (HREL && s == 3 && flag) {
#pragma unroll
      for (int i = 0; i < 12; i++) ld16(&a[4 * i], sb, uo, i * 2048);
    }
  }
  constexpr int TE = PS == PS_KV ? 24 : PS == PS_Q ? 38 : PS == PS_WO ? 52 : SUB ? 72 : PS == PS_FFA ? 92 : -1;
  tail();
  if (TE >= 0) TR(TE);
  wg_wait<0>();
  if (TE >= 0) TR(TE + 1);
  if (PS != PS_WO) rel(pass_slot<PS>(NS - 1));
}

template <int NF, int N0 = 0> __device__ __forceinline__ void load_frags(uint32_t (&a)[144], const uint8_t* sb, uint32_t uo, uint32_t t) {
#pragma unroll
  for (int i = N0; i < NF; i++) load_frag(a, i, sb, uo, t);
}
__device__ __forceinline__ void ln_scalars(float s1, float s2, uint32_t& m, float& var, uint32_t zero) {
  const float mean = s1 * (1.f / DM);
  var = s2 * (1.f / DM) - mean * mean;
  m = pack_bf16(mean, mean) ^ (__float_as_uint(var) & zero);
}
__device__ __forceinline__ float ln_rstd(float var, float after, uint32_t zero) {
  var = __uint_as_float(__float_as_uint(var) ^ (__float_as_uint(after) & zero));
  float sd, r;
  asm("sqrt.approx.ftz.f32 %0, %1;" : "=f"(sd) : "f"(bf_round(bf_round(fmaxf(var, 0.f)) + 1e-5f)));
  asm("rcp.approx.ftz.f32 %0, %1;" : "=f"(r) : "f"(bf_round(sd)));
  return r;
}
template <int NF> __device__ __forceinline__ void gather_ln(uint32_t (&a)[144], const uint8_t* sb, uint32_t uo, uint32_t sto,
                                          uint32_t& m0, uint32_t& m1, float& r0, float& r1, uint32_t zero) {
  uint32_t u[32];
  const uint32_t t = tid_(), so = sto + (t >> 5) * 1024 + (t & 28) * 4;
#pragma unroll
  for (int i = 0; i < 8; i++) ld16(&u[4 * i], sb, so, OFF_ST + i * 128);
  load_frags<N_UP>(a, sb, uo, t);
  while (true) {
    uint32_t m = a[4 * NF - 4];
#pragma unroll
    for (int i = NF - 2; i >= 0; i--) m = min(m, a[4 * i]);
#pragma unroll
    for (int i = 0; i < 8; i++) m = min(m, u[4 * i]);
    if (!__any_sync(0xffffffffu, m == 0)) break;
#pragma unroll
    for (int i = 0; i < 8; i++) ld16(&u[4 * i], sb, so, OFF_ST + i * 128);
    load_frags<NF>(a, sb, uo, t);
  }
  float v[4];
#pragma unroll
  for (int k = 0; k < 4; k++)
    v[k] = ((__uint_as_float(u[k]) + __uint_as_float(u[4 + k])) + (__uint_as_float(u[8 + k]) + __uint_as_float(u[12 + k]))) +
           ((__uint_as_float(u[16 + k]) + __uint_as_float(u[20 + k])) + (__uint_as_float(u[24 + k]) + __uint_as_float(u[28 + k])));
  ln_scalars(v[1], v[0], m0, r0, zero); ln_scalars(v[3], v[2], m1, r1, zero);
}
struct Stats {
  float s[4] = {0, 0, 0, 0}, d0[4] = {0, 0, 0, 0}, d1[4] = {0, 0, 0, 0};
  __device__ __forceinline__ void add16(const uint32_t* f) {
    mma16816(s, f[0], f[1], f[2], f[3], 0x3f803f80u, 0x3f803f80u);
    mma1688(d0, f[0], f[1], f[0]); mma1688(d1, f[0], f[1], f[1]);
    mma1688(d0, f[2], f[3], f[2]); mma1688(d1, f[2], f[3], f[3]);
  }
  __device__ __forceinline__ float sq0(int g) const { return (g & 1) ? d0[1] : d0[0]; }
  __device__ __forceinline__ float sq1(int g) const { return (g & 1) ? d1[3] : d1[2]; }
};
struct RowStats {
  float s[4] = {0, 0, 0, 0}, u[4] = {0, 0, 0, 0};
  template <int N> __device__ __forceinline__ void add(const uint32_t* y) {
#pragma unroll
    for (int i = 0; i < N; i++) {
      const float lo = bf_lo(y[i]), hi = bf_hi(y[i]);
      const int r = (i & 1) * 2;
      s[r] = fmaf(lo, lo, s[r]); u[r] = fmaf(hi, hi, u[r]); s[r + 1] += lo; u[r + 1] += hi;
    }
  }
  __device__ __forceinline__ uint32_t fold() {
    uint32_t x = 0;
#pragma unroll
    for (int i = 0; i < 4; i++) { s[i] += u[i]; u[i] = 0; x |= __float_as_uint(s[i]); }
    return x;
  }
  __device__ __forceinline__ void store(uint8_t* sb, uint32_t sto, uint32_t t) {
    fold();
#pragma unroll
    for (int i = 0; i < 4; i++) s[i] += __shfl_xor_sync(0xffffffffu, s[i], 1);
#pragma unroll
    for (int i = 0; i < 4; i++) s[i] += __shfl_xor_sync(0xffffffffu, s[i], 2);
    if ((t & 3) == 0) st16(sb, sto + (t >> 5) * 1024 + (t & 28) * 4, OFF_ST, __float_as_uint(s[0]) | 1u, __float_as_uint(s[1]), __float_as_uint(s[2]), __float_as_uint(s[3]));
  }
};
template <bool SET> __device__ __forceinline__ void add_piece(float* acc, uint32_t sm) {
#pragma unroll
  for (int i = 0; i < 4; i++) {
    uint32_t v[4];
    lds128(v, sm + i * 2048);
#pragma unroll
    for (int k = 0; k < 4; k++) {
      acc[8 * i + 2 * k] = SET ? bf_lo(v[k]) : acc[8 * i + 2 * k] + bf_lo(v[k]);
      acc[8 * i + 2 * k + 1] = SET ? bf_hi(v[k]) : acc[8 * i + 2 * k + 1] + bf_hi(v[k]);
    }
  }
}

#define TS(i) do {} while (0)
#define TSP(i) do {} while (0)
#define TSH(i) do {} while (0)

__device__ __forceinline__ uint32_t row_off(int rb, int wg, uint32_t t) { return (rb * 128 + wg + ((t >> 5) * 16 + (t & 15)) * 2) * (2 * DM); }

__device__ __forceinline__ const __nv_bfloat16* wo_src(const __nv_bfloat16* wo, int k, int u, int j) {
  const int ko = k < 512 ? (k >> 6) * 72 + (k & 63) : ((k >> 3) & 7) * 72 + 64 + (k & 7);
  return wo + ko * 576 + (u < 8 ? j * 64 + u * 8 : 512 + j * 8);
}

struct Params {
  const __nv_bfloat16* wqkv;
  uint8_t* scr;
  uint8_t role[64];
  const __nv_bfloat16* wo;
  __nv_bfloat16* out;
  uint8_t* times;
  unsigned zero;
};

__cluster_dims__(2, 1, 1)
__global__ void __launch_bounds__(384, 1)
fused_kernel(const __grid_constant__ Params P, const __grid_constant__ CUtensorMap map_x, const __grid_constant__ CUtensorMap map_wg,
             const __grid_constant__ CUtensorMap map_wu, const __grid_constant__ CUtensorMap map_wd) {
  const int wg = __shfl_sync(0xffffffffu, threadIdx.x >> 7, 0);
  const int cta = blockIdx.x, rank = cta & 1, role = P.role[cta >> 1], j = role & 7, rb = (role >> 3) * 2 + rank;
  const uint32_t own = win();
  unsigned* const flags = (unsigned*)(P.scr + OFF_FLAGS);
  if (__shfl_sync(0xffffffffu, threadIdx.x >> 5, 0) == 11) {
    if (threadIdx.x == 352) {
#pragma unroll
      for (int i = 0; i < 14; i++) { mbar_init(bar_full(i), 1); mbar_init(bar_empty(i), i < 12 ? 4 : 2); }
      mbar_init(bar_full(14), 1); mbar_init(bar_empty(14), 1);
      asm volatile("fence.mbarrier_init.release.cluster;" ::: "memory");
      if (smem_u32(smem_raw) != own + SB) asm volatile("trap;");
    }
    __syncwarp();
    bar_arrive(0, 384);
    asm volatile("barrier.cluster.arrive.relaxed.aligned;" ::: "memory");
    if (threadIdx.x == 352) {
#pragma unroll 1
      for (int c = 0; c < 9; c++) {
        mbar_expect_tx(bar_full(c), SLOT);
        tma_3d(own + slot_addr(c), &map_x, c * 64, rb * 64, 0, own + bar_full(c));
      }
    }
  } else {
    const bool on = threadIdx.x < 324;
    const int k = rb * 36 + (on ? threadIdx.x / 36 : 0) * 4 + (threadIdx.x & 3), u = (threadIdx.x % 36) >> 2;
    const uint4* s = (const uint4*)(P.wqkv + k * 1728 + j * 72 + u * 8);
    const uint4 vk = ldg_line(s + 72), vv = ldg_line(s + 144);
    const unsigned ep0 = *(volatile unsigned*)&flags[(72 + cta) * 8];
    asm volatile("barrier.cluster.arrive.relaxed.aligned;" ::: "memory");
    bar_sync(0, 384);
    uint8_t* d = P.scr + OFF_WPACK + j * 24 * PSLOT;
    if (on) {
      const uint32_t dkv = (k / 48) * PSLOT + u * 768 + (k % 48) * 16;
      st16(d, dkv, 0, vk.x, vk.y, vk.z, vk.w);
      st16(d, dkv, 9 * 768, vv.x, vv.y, vv.z, vv.w);
    }
    asm volatile("fence.proxy.async.global;" ::: "memory");
    bar_arrive(NB_PUB + 3, 384);
    if (threadIdx.x == 351) sts32(SM_EPOCH, ep0);
    if (wg == 2) bar_sync(NB_PUB + 1, 96);
  }
  __syncwarp();
  asm volatile("barrier.cluster.wait.acquire.aligned;" ::: "memory");

  if (wg == 2) {
    asm volatile("setmaxnreg.dec.sync.aligned.u32 24;");
    const int pw = __shfl_sync(0xffffffffu, (threadIdx.x >> 5) & 3, 0), lane = threadIdx.x & 31;
    auto tile_col = [](int t, int h, int j) { return t < 9 ? j * 576 + t * 64 : (t == 9 && h) ? 512 : ((j + ((h ? 0x05760 : 0x04123) >> (4 * (t - 9)))) & 7) * 64; };
    auto prefetch_tile = [&](int t) {
#pragma unroll 1
      for (int b = rb; b < 18; b += 16) {
        const int h = b & 1, k = b >> 1;
        if (t < 9) w_tma_prefetch(h ? &map_wu : &map_wg, tile_col(t, h, j), k * 64);
        else if (t != 13 || !h) w_tma_prefetch(&map_wd, tile_col(t, h, j), j * 576 + k * 64);
      }
    };
    if (pw == 0) {
      {
        flag_wait(&flags[j * 8], (lds32(SM_EPOCH) + 1) * 16);
        TSP(7);
        asm volatile("fence.proxy.async.global;" ::: "memory");
        const uint8_t* wp = P.scr + OFF_WPACK + j * 24 * PSLOT;
        wp += rank * (PSLOT / 2);
        auto packed = [&](int sl, uint32_t par, int f) {
          mbar_wait(bar_empty(0) + sl * 8, par);
          w_bulk_load_mc(own + SB + rank * (PSLOT / 2) + sl * SLOT, wp + f * PSLOT, PSLOT / 2, own + bar_full(0) + sl * 8);
          w_expect_tx(own + bar_full(0) + sl * 8, PSLOT);
        };
        const uint32_t half = own + SB + rank * 8192;
#pragma unroll 1
        for (int L = 0; L < 2; L++) {
#pragma unroll 1
          for (int s = L ? 0 : -3; s < 21; s++) {
            if (s == 9 && L == 0) { flag_wait(&flags[(56 + j) * 8], (lds32(SM_EPOCH) + 1) * 16); asm volatile("fence.proxy.async.global;" ::: "memory"); }
            packed(s < 0 ? s + 12 : s < 9 ? s : s - 9, s < 0 || (s >= 9 && s < 18), s + 3);
          }
#pragma unroll 1
          for (int t = 0; t < 14; t++) {
            if (L * 14 + t + PF_AHEAD < 28) prefetch_tile((t + PF_AHEAD) % 14);
            const CUtensorMap* mp = t >= 9 ? &map_wd : rank ? &map_wu : &map_wg;
            const bool nar = t == 13;
            const int col = tile_col(t, nar ? 0 : rank, j);
            const uint32_t dst = nar ? own + SB : half, bytes = nar ? 8192 : SLOT;
            const int ra = t < 9 ? 0 : j * 576 + 320, rbs = t < 9 ? 0 : j * 576 - 192, rc = t < 9 ? 0 : j * 576;
#pragma unroll
            for (int k = 0; k < 9; k++) {
              mbar_wait(bar_empty(k), t & 1);
              if (!nar || rank == (k & 1)) w_tma_2d_mc(dst + k * SLOT, mp, col, (k < 3 ? ra : k < 8 ? rbs : rc) + k * 64, own + bar_full(k));
              w_expect_tx(own + bar_full(k), bytes);
            }
            if (t == 12 && L == 0) {
              w_l2_prefetch(P.scr + OFF_WPACK + j * 24 * PSLOT + rb * (24 * PSLOT / 16), 24 * PSLOT / 16);
#pragma unroll 1
              for (int s = 0; s < 3; s++) packed(9 + s, 1, s);
            }
          }
        }
        flags[(72 + cta) * 8] = lds32(SM_EPOCH) + 1;
      }
    } else if (pw < 3) {
      const int hw = pw - 1;
      const uint32_t ep = __shfl_sync(0xffffffffu, lds32(SM_EPOCH), 0);
      uint8_t* const sb = P.scr + (rb * 2 + hw) * STRM;
      const uint32_t xs = slot_addr(12) + hw * SLOT, fb = bar_full(12) + hw * 8;
      uint32_t hph = 0;
#pragma unroll 1
      for (int L = 0; L < 2; L++) {
        const uint32_t tag = ep * 2 + L + 1;
        bar_sync(NB_FREE + hw, 160);
        if (rb > 0) hint_wait(sb + OFF_HINT + 512 + j * 128, tag);
        uint32_t bad;
        do {
          if (rb > 0) {
            w_bulk_load(own + ytail(hw * 2), sb + OFF_HALO + (L * 8 + j) * 3072, 1536, own + bar_full(14) + hw * 128);
            w_bulk_load(own + ytail(hw * 2 + 1), sb + OFF_HALO + (L * 8 + j) * 3072 + 1536, 1536, own + bar_full(14) + hw * 128);
            w_expect_tx(own + bar_full(14) + hw * 128, 3072);
            mbar_wait(bar_full(14) + hw * 128, hph);
            hph ^= 1;
          }
          bad = 0;
#pragma unroll 1
          for (int c = 0; c < 3; c++) {
            uint32_t u[4] = {tag, 0, 0, 0}, v[4] = {tag, 0, 0, 0};
            if (rb > 0) { lds128(u, ytail(hw * 2) + c * 512 + lane * 16); lds128(v, ytail(hw * 2 + 1) + c * 512 + lane * 16); }
            bad |= (u[0] ^ tag) | (v[0] ^ tag);
#pragma unroll
            for (int i = 0; i < 3; i++) { sts32(xs + KSTG + (c * 3 + i) * 128 + lane * 4, u[i + 1]); sts32(xs + (c * 3 + i) * 128 + lane * 4, v[i + 1]); }
          }
        } while (__any_sync(0xffffffffu, bad != 0));
        bar_arrive(NB_HALO + hw, 160);
#pragma unroll 1
        for (int p = 0; p < 4; p++) {
          if (L == 0 && p == 3) flag_wait(flags + (40 + rb) * 8, (ep + 1) * 8);
          bar_sync(NB_FREE + hw, 160);
          TSH(L * 12 + p * 3);
          hint_wait(sb + OFF_HINT + (lane & 3) * 128, (ep * 13 + L * 7 + p + 3) * 8);
          TSH(L * 12 + p * 3 + 1);
          w_bulk_load(own + xs, sb + OFF_P + j * PSRC + (p & 1) * 16384, p ? 16384 : 8192, own + fb);
          if (p == 0) w_bulk_load(own + xs + 8192, sb + OFF_P + j * PSRC + 32768, 7168, own + fb);
          w_expect_tx(own + fb, p ? 16384 : 15360);
          TSH(L * 12 + p * 3 + 2);
        }
      }
    } else {
      auto clear = [&](int t) {
        const uint32_t so = rb * 2 * STRM + (threadIdx.x & 31) * 16;
#pragma unroll 1
        for (int i = 0; i < 18; i++) {
          st16(P.scr, so + t * TILE + j * 9216 + i * 512, 0, 0, 0, 0, 0);
          st16(P.scr, so + t * TILE + j * 9216 + i * 512, STRM, 0, 0, 0, 0);
          __nanosleep(0);
        }
        if (t != 1) {
          st16(P.scr, so + (t ? t - 1 : 0) * 4096 + j * 512, OFF_ST, 0, 0, 0, 0);
          st16(P.scr, so + (t ? t - 1 : 0) * 4096 + j * 512, OFF_ST + STRM, 0, 0, 0, 0);
        }
      };
      bar_sync(NB_PUB + 3, 384);
      if (lane == 0) flag_signal(&flags[j * 8]);
      TSP(5);
      bar_sync(NB_PUB + 2, 288);
      if (lane == 0) flag_signal(&flags[(56 + j) * 8]);
      TSP(4);
      __syncwarp();
#pragma unroll 1
      for (int t = 0; t < PF_AHEAD; t++) prefetch_tile(t);
#pragma unroll 1
      for (int L = 0; L < 2; L++) {
        timed_wait(bar_empty(13), L);
#pragma unroll 1
        for (int t = L ^ 1; t < 4 - 2 * L; t++) clear(t);
        __syncwarp();
        if (lane == 0 && L == 0) flag_signal(flags + (40 + rb) * 8);
      }
      timed_wait(bar_empty(12), 0);
      asm volatile("barrier.cluster.arrive.relaxed.aligned;\nbarrier.cluster.wait.aligned;" ::: "memory");
    }
  } else {
    asm volatile("setmaxnreg.inc.sync.aligned.u32 240;");
    const int w = __shfl_sync(0xffffffffu, (threadIdx.x >> 5) & 3, 0);
    Rel rel{(threadIdx.x & 95) == 0, cta_window(w & 1), 0};
    uint8_t* const sb = P.scr + (rb * 2 + wg) * STRM;
    uint8_t* const hint = sb + OFF_HINT + w * 128;
    auto hint_target = [](int e) { return (lds32(SM_EPOCH) * 13 + e + 1) * 8; };
    TS(0);
    uint32_t a[144];
#pragma unroll 1
    for (int L = 0; L < 2; L++) {
      uint32_t m0, m1; float r0, r1;
      rel.tr = win() + ytail(3) + 1536 + (L == TRACE - 1 && w == 1 ? wg * 384 : 768);
      if (L == 0) {
        Stats st;
        const int lane = tid_() & 31, g = lane >> 2;
        const int row = w * 16 + (lane & 15);
        const uint32_t ra = SB + wg * 8192 + row * 128;
        const uint32_t pt = tid_(), pu = (pt % 36) >> 2, pk = rb * 36 + (pt < 108 ? pt / 36 : 0) * 4 + (pt & 3);
        uint4 pv[3];
#pragma unroll
        for (int i = 0; i < 3; i++) pv[i] = ldg_line(wg ? wo_src(P.wo, pk + i * 12, pu, j) : P.wqkv + (pk + i * 12) * 1728 + j * 72 + pu * 8);
#pragma unroll
        for (int c = 0; c < 9; c++) {
          mbar_wait(bar_full(c), 0);
          if (c == 0) TS(60); if (c == 8) TS(62);
#pragma unroll
          for (int kk = 0; kk < 4; kk++) ldsm4(&a[c * 16 + kk * 4], ra + (((kk * 2 + (lane >> 4)) ^ (row & 7)) << 4) + c * SLOT);
          if (c == 8) {
            uint32_t y[18], z[4];
#pragma unroll
            for (int i = 0; i < 4; i++) ldsm4(&y[4 * i], ra + (((i * 2 + (lane >> 4)) ^ (row & 7)) << 4) + j * SLOT);
            ldsm4(z, ra + ((j ^ (row & 7)) << 4) + 8 * SLOT);
            y[16] = z[0]; y[17] = z[1];
            bar_sync(NB_WG + wg, 128);
#pragma unroll
            for (int i = 0; i < 9; i++) rel(i);
            if (pt < 108) {
#pragma unroll
              for (int i = 0; i < 3; i++) {
                const uint32_t k = pk + i * 12;
                st16(P.scr, (j * 24 + wg * 6 + k / 96) * PSLOT + pu * 1536 + (k % 96) * 16, OFF_WPACK + 12 * PSLOT, pv[i].x, pv[i].y, pv[i].z, pv[i].w);
              }
            }
            asm volatile("fence.proxy.async.global;" ::: "memory");
            bar_arrive(NB_PUB + 2, 288);
            store_own(y, sb, OFF_X2, j, tid_());
          }
#pragma unroll
          for (int kk = 0; kk < 4; kk++) st.add16(&a[c * 16 + kk * 4]);
        }
        const int dl = (lane & ~3) | (g >> 1);
        ln_scalars(st.s[0], __shfl_sync(0xffffffffu, st.sq0(g), dl), m0, r0, P.zero);
        ln_scalars(st.s[2], __shfl_sync(0xffffffffu, st.sq1(g), dl), m1, r1, P.zero);
      } else {
#pragma unroll
        for (int i = 4 * N_UP; i < 144; i++) a[i] = 0;
        hint_wait(hint, hint_target(6));
        TS(61);
        gather_ln<3 * D_KV>(a, sb, OFF_X2, 8192, m0, m1, r0, r1, P.zero);
      }
      TS(1 + L * 20);
      uint32_t kf[18], qf[18];
      {
        float acc[72];
        if (wg == 1) bar_sync(NB_ORD1, 256);
        mma_pass<144, PS_KV, 3, 256, D_KV, true>(acc, a, DESC_KV, 1, rel, wg == 0 ? NB_ORD1 : -1, sb, OFF_X2, L ^ 1, m0, m1, ytail(wg * 2));
        r0 = ln_rstd(r0, acc[0], P.zero); r1 = ln_rstd(r1, acc[0], P.zero);
        uint32_t vf[18];
#pragma unroll
        for (int c = 0; c < 9; c++) {
          kf[c] = pack_bf16(acc[4 * c] * r0, acc[4 * c + 1] * r0);
          kf[9 + c] = pack_bf16(acc[4 * c + 2] * r1, acc[4 * c + 3] * r1);
          vf[c] = pack_bf16(acc[36 + 4 * c] * r0, acc[36 + 4 * c + 1] * r0);
          vf[9 + c] = pack_bf16(acc[36 + 4 * c + 2] * r1, acc[36 + 4 * c + 3] * r1);
        }
        TS(2 + L * 20);
        const uint32_t l16 = (tid_() & 31) * 16, xs = slot_addr(12) + wg * SLOT + w * 1152;
#pragma unroll
        for (int i = 0; i < 4; i++) stsm4(xs + w * 1152 + 1152 + i * 512 + l16, vf[4 * i], vf[4 * i + 1], vf[4 * i + 2], vf[4 * i + 3]);
        sts32(xs + w * 1152 + 1152 + 2048 + l16 / 4, vf[16]); sts32(xs + w * 1152 + 1152 + 2176 + l16 / 4, vf[17]);
        if (w < 3) {
          stsm4(xs + KSTG + 1152 + l16, kf[9], kf[10], kf[11], kf[12]);
          stsm4(xs + KSTG + 1152 + 512 + l16, kf[13], kf[14], kf[15], kf[16]);
          sts32(xs + KSTG + 1152 + 1024 + l16 / 4, kf[17]);
        } else if (rb < 15) {
          const uint32_t tag = lds32(SM_EPOCH) * 2 + L + 1;
          const uint32_t ho = l16 + (L * 8 + j) * 3072;
#pragma unroll
          for (int c = 0; c < 3; c++) {
            st16(sb, ho, 2 * STRM + OFF_HALO + c * 512, tag, kf[9 + 3 * c], kf[10 + 3 * c], kf[11 + 3 * c]);
            st16(sb, ho, 2 * STRM + OFF_HALO + 1536 + c * 512, tag, vf[9 + 3 * c], vf[10 + 3 * c], vf[11 + 3 * c]);
          }
          hint_post(sb + 2 * STRM + OFF_HINT + 512 + j * 128);
        }
      }
      lds128(a, ytail(wg * 2) + tid_() * 16);
      bar_arrive(NB_FREE + wg, 160);
      uint32_t kh[12], vp[20], v1[12];
      {
        float acc[36];
        if (wg == 1) bar_sync(NB_ORD1, 256);
        mma_pass<72, PS_Q, 6, 256, 0, false, false>(acc, a, DESC_Q, 0, rel, -1, nullptr, 0, 0, 0, 0, 0, [&]() {
          bar_sync(NB_HALO + wg, 160);
#pragma unroll
          for (int i = 0; i < 3; i++) ldsm4(&kh[4 * i], slot_addr(12) + wg * SLOT + w * 640 + tid_() * 16 + KSTG + i * 512);
          const uint32_t l = tid_() & 31, vb = slot_addr(12) + wg * SLOT + w * 2304;
#pragma unroll
          for (int i = 0; i < 5; i++) ldsm4t(&vp[4 * i], vb + (l & 8) * 144 + (l & 16) * 8 + (l & 7) * 16 + i * 256);
#pragma unroll
          for (int i = 0; i < 3; i++) ldsm4t(&v1[4 * i], vb + 2304 + l * 16 + i * 512);
        });
#pragma unroll
        for (int i = 0; i < 18; i++) qf[i] = pack_bf16(acc[2 * i], acc[2 * i + 1]);
      }
      TS(3 + L * 20);
      uint32_t xr[18];
      {
        const int tid = tid_(), g = (tid >> 2) & 7, q = tid & 3;
        const bool nohalo = (rb == 0 && w == 0);
        const bool le0 = 2 * q <= g, le1 = 2 * q + 1 <= g;
        const uint32_t M = (le0 ? 0xffffu : 0u) | (le1 ? 0xffff0000u : 0u);
        const float sc0 = r0 * (0.23570226039551584f * 1.4426950408889634f), sc1 = r1 * (0.23570226039551584f * 1.4426950408889634f);
        float l[16], t[8];
#pragma unroll
        for (int h = 0; h < 4; h++) {
          const uint32_t qa0 = q >= h ? qf[4 * h] : 0u, qa1 = q >= h ? qf[4 * h + 1] : 0u;
          const uint32_t qc0 = q <= h ? qf[4 * h + 4] : 0u, qc1 = q <= h ? qf[4 * h + 5] : 0u;
          float sm[4] = {0, 0, 0, 0}, s0[4] = {0, 0, 0, 0}, s1[4] = {0, 0, 0, 0};
          mma16816(s0, qa0, qa1, qf[4 * h + 2], qf[4 * h + 3], kf[2 * h], kf[2 * h + 1]);
          mma16816(s1, qa0, qa1, qf[4 * h + 2], qf[4 * h + 3], kf[9 + 2 * h], kf[10 + 2 * h]);
          mma16816(sm, qa0, qa1, qf[4 * h + 2], qf[4 * h + 3], kh[2 * h], kh[2 * h + 1]);
          mma1688(s0, qc0, qc1, kf[2 * h + 2]);
          mma1688(s1, qc0, qc1, kf[11 + 2 * h]);
          mma1688(sm, qc0, qc1, kh[2 * h + 2]);
          if (nohalo) sm[0] = sm[1] = -3e38f;
          l[4 * h] = le0 ? s0[0] : sm[0]; l[4 * h + 1] = le1 ? s0[1] : sm[1];
          l[4 * h + 2] = le0 ? s1[2] : s0[2]; l[4 * h + 3] = le1 ? s1[3] : s0[3];
        }
#pragma unroll
        for (int i = 0; i < 8; i++) t[i] = fmaxf(l[2 * i], l[2 * i + 1]);
        TS(14 + L * 20);
#pragma unroll
        for (int i = 0; i < 8; i++) t[i] = fmaxf(t[i], __shfl_xor_sync(0xffffffffu, t[i], 1));
#pragma unroll
        for (int i = 0; i < 8; i++) t[i] = fmaxf(t[i], __shfl_xor_sync(0xffffffffu, t[i], 2)) * ((i & 1) ? sc1 : sc0);
#pragma unroll
        for (int i = 0; i < 8; i++) {
          const float sc = (i & 1) ? sc1 : sc0;
          l[2 * i] = ex2(fmaf(l[2 * i], sc, -t[i])); l[2 * i + 1] = ex2(fmaf(l[2 * i + 1], sc, -t[i])); t[i] = l[2 * i] + l[2 * i + 1];
        }
#pragma unroll
        for (int i = 0; i < 8; i++) t[i] += __shfl_xor_sync(0xffffffffu, t[i], 1);
#pragma unroll
        for (int i = 0; i < 8; i++) t[i] += __shfl_xor_sync(0xffffffffu, t[i], 2);
        uint32_t pf[16], pz[8];
#pragma unroll
        for (int i = 0; i < 8; i++) {
          float r; asm("rcp.approx.ftz.f32 %0, %1;" : "=f"(r) : "f"(t[i]));
          const uint32_t p = pack_bf16(l[2 * i] * r, l[2 * i + 1] * r);
          pf[2 * i] = p & ~M; pf[2 * i + 1] = p & M; pz[i] = p & P.zero;
        }
#pragma unroll
        for (int c = 0; c < 9; c++) {
          const int h = c == 8 ? 3 : c >> 1;
          float o[4] = {0, 0, 0, 0};
          mma16816(o, pf[4 * h], pz[2 * h], pf[4 * h + 1], pf[4 * h + 2], vp[2 * c], vp[2 * c + 1]);
          mma1688(o, pz[2 * h + 1], pf[4 * h + 3], v1[c]);
          if (c == 2 || c == 4 || c == 6) {
            float e[4] = {0, 0, 0, 0};
            mma16816(e, pf[4 * h - 4], pz[2 * h - 2], pf[4 * h - 3], pf[4 * h - 2], vp[2 * c], vp[2 * c + 1]);
            mma1688(e, pz[2 * h - 1], pf[4 * h - 1], v1[c]);
            const uint32_t u = pack_bf16(e[0], e[1]), v = pack_bf16(e[2], e[3]);
            qf[2 * c] = q < h ? u : pack_bf16(o[0], o[1]); qf[2 * c + 1] = q < h ? v : pack_bf16(o[2], o[3]);
          } else {
            qf[2 * c] = pack_bf16(o[0], o[1]); qf[2 * c + 1] = pack_bf16(o[2], o[3]);
          }
        }
        {
          uint32_t x = 0;
#pragma unroll
          for (int i = 0; i < 18; i += 2) x |= qf[i];
          bar_arrive(NB_ORD1 - wg + (x & P.zero), 256);
        }
        store_own(qf, sb, OFF_O, j, tid);
        hint_post(hint);
        load_own(xr, sb, OFF_X2, j);
      }
      TS(4 + L * 20);
      {
        hint_wait(hint, hint_target(L * 7));
        TS(5 + L * 20);
        load_frags<N_WO>(a, sb, OFF_O, tid_());
        float acc[36];
        if (wg == 0) bar_sync(NB_ORD0, 256);
        load_frags<N_UP, N_WO>(a, sb, OFF_O, tid_());
        TS(19 + L * 20);
        mma_pass<72, PS_WO, 6, 256, D_WO, false>(acc, a, DESC_Q, 0, rel, -1, sb, OFF_O);
        TS(6 + L * 20);
#pragma unroll
        for (int c = 0; c < 9; c++) {
          xr[2 * c] = bf2_add(xr[2 * c], pack_bf16(acc[4 * c], acc[4 * c + 1]));
          xr[2 * c + 1] = bf2_add(xr[2 * c + 1], pack_bf16(acc[4 * c + 2], acc[4 * c + 3]));
        }
        store_own(xr, sb, L * 3 * TILE, j, tid_());
        RowStats rs;
        rs.add<18>(xr);
        rs.store(sb, L * 4096 + j * 128, tid_());
        hint_post(hint);
      }
      TS(16 + L * 20);
      hint_wait(hint, hint_target(L * 7 + 1));
      TS(15 + L * 20);
      gather_ln<4 * D_T0>(a, sb, L * 3 * TILE, L * 4096, m0, m1, r0, r1, P.zero);
      TS(7 + L * 20);
      const uint32_t hb = OFF_H + j * 24576;
      {
        float ka0, kb0, kc0, ka1, kb1, kc1;
        float acc[64];
        uint32_t hf[16];
        auto geglu = [&](auto chains, uint32_t hsm) {
          constexpr int CH = decltype(chains)::value & 15;
          float r[32];
#pragma unroll
          for (int e = 0; e < 32; e++) {
            float x = acc[e];
            if (e >= CH) x = __uint_as_float(__float_as_uint(x) ^ (__float_as_uint(r[e - CH]) & P.zero));
            if (decltype(chains)::value > 15 && e < 20) {
              const uint32_t ad = (e < 8 ? slot_addr(12) + e * 2048 + wg * 8192 : slot_addr(7 + (e >> 2)) + (e & 3) * 2048) + hsm;
              lds128(&a[48 + 4 * e], e >= CH ? ad ^ (__float_as_uint(r[e - CH]) & P.zero) : ad);
            }
            const bool hi = e & 2;
            float t = x * fmaf(x * x, hi ? kb1 : kb0, hi ? ka1 : ka0);
            asm("tanh.approx.f32 %0, %0;" : "+f"(t));
            const float u = x * acc[32 + e] * (hi ? kc1 : kc0);
            r[e] = fmaf(u, t, u);
            if (e & 1) hf[e >> 1] = pack_bf16(r[e - 1], r[e]);
          }
        };
        if (wg == 1) bar_sync(NB_ORD1, 256);
        mma_pass<128, PS_FF, 4, 2048, D_T0, true>(acc, a, DESC_SW128, 1, rel, NB_ORD1 - wg, sb, L * 3 * TILE, 0, m0, m1);
        if (tid_() == 0) mbar_arrive(bar_empty(13));
        TS(8 + L * 20);
        r0 = ln_rstd(r0, acc[0], P.zero); r1 = ln_rstd(r1, acc[0], P.zero);
        ka0 = 0.7978845608028654f * r0; kb0 = 0.035677408136300125f * r0 * r0 * r0; kc0 = 0.5f * r0 * r0;
        ka1 = 0.7978845608028654f * r1; kb1 = 0.035677408136300125f * r1 * r1 * r1; kc1 = 0.5f * r1 * r1;
#pragma unroll 1
        for (int t = 0; t < 8; t++) {
          geglu(IntC<2>(), 0);
          const uint32_t t16 = tid_() * 16;
          if (t < 5) {
            const uint32_t d = (t < 2 ? slot_addr(12) + wg * SLOT + t * 8192 : slot_addr(7) + t * SLOT + wg * 8192) + t16;
#pragma unroll
            for (int i = 0; i < 4; i++)
              sts128(d + i * 2048, hf[4 * i], hf[4 * i + 1], hf[4 * i + 2], hf[4 * i + 3]);
            if (t == 4) asm volatile("fence.proxy.async.shared::cta;" ::: "memory");
          } else {
#pragma unroll
            for (int i = 0; i < 4; i++) st16(sb, hb + (t - 5) * 8192 + t16, i * 2048, hf[4 * i], hf[4 * i + 1], hf[4 * i + 2], hf[4 * i + 3]);
          }
          bar_sync(NB_ORD0 + wg, 256);
          mma_pass<128, PS_FF, 4, 2048, 0, false, true>(acc, a, DESC_SW128, t & 1, rel, NB_ORD1 - wg, sb, hb + t16, t == 7);
        }
        TS(9 + L * 20);
        const uint32_t hsm = wg * 8192 + tid_() * 16;
        geglu(IntC<16 + CH_LAST>(), hsm);
#pragma unroll
        for (int i = 0; i < 16; i++) a[128 + i] = hf[i];
      }
      TS(10 + L * 20);
      {
        const uint32_t xs = slot_addr(12) + wg * SLOT;
        auto verify = [&](int p, uint32_t t16) {
          mbar_wait(bar_full(12) + wg * 8, p & 1);
          TS(71 + L * 32 + p * 5);
          const uint32_t ta = p < 2, tb = (p & 1) ? ta : L ^ 1, nb = p ? 4 : 7, sh = p == 0;
          uint32_t m = 0;
#pragma unroll
          for (int s = 0; s < 4; s++) m |= (lds32(xs + s * 2048 + t16) ^ ta) | (lds32(xs + 8192 + ((s * 2048 + t16) >> sh)) ^ tb);
          if (p == 0) {
#pragma unroll
            for (int s = 4; s < 7; s++) m |= lds32(xs + 8192 + s * 1024 + t16 / 2) ^ tb;
          }
          if (__any_sync(0xffffffffu, m & 1)) {
#pragma unroll 1
            for (int s = 0; s < 4 + nb; s++) {
              const bool nar = sh && s >= 4;
              const uint32_t o = nar ? 4096 + s * 1024 + t16 / 2 : s * 2048 + t16;
              uint32_t v[4] = {0, 0, 0, 0};
              do {
                if (nar) ld8(v, sb, j * PSRC + o, OFF_P + 32768 - 8192);
                else ld16(v, sb, j * PSRC + (p & 1) * 16384 + o, OFF_P);
              } while (__any_sync(0xffffffffu, (v[0] ^ (s < 4 ? ta : tb)) & 1));
              sts64(xs + o, v[0], v[1]);
              if (!nar) sts64(xs + o + 8, v[2], v[3]);
            }
            asm volatile("fence.proxy.async.shared::cta;" ::: "memory");
          }
        };
        uint32_t t16 = (a[142] | a[143]) & P.zero;
#pragma unroll 1
        for (int p = 0; p < 4; p++) {
          float acc[64];
          bar_sync(NB_ORD0 + wg + (p ? 0 : t16), 256);
          TS(64 + L * 32 + p * 5);
          if (p == 0) { rel(9); rel(10); rel(11); }
          mma_pass<128, PS_FF, 4, 2048, 0, false, false>(acc, a, DESC_SW128, p & 1, rel, NB_ORD1 - wg, nullptr, 0, 0, 0, 0, 0, [&]() {
            t16 = tid_() * 16;
            if (p) verify(p - 1, t16);
          });
          TS(65 + L * 32 + p * 5);
          if (p == 1 || p == 2) add_piece<false>(acc, xs + t16);
          const uint32_t oa = ((j + (p < 3 ? 1 : 4)) & 7) * PSRC + (p & 1) * 16384 + t16;
#pragma unroll
          for (int i = 0; i < 4; i++)
            st16(sb, oa, OFF_P + i * 2048, (pack_bf16(acc[8 * i], acc[8 * i + 1]) & ~1u) | (p < 2), pack_bf16(acc[8 * i + 2], acc[8 * i + 3]),
                 pack_bf16(acc[8 * i + 4], acc[8 * i + 5]), pack_bf16(acc[8 * i + 6], acc[8 * i + 7]));
          if (p == 0) {
#pragma unroll
            for (int i = 0; i < 8; i++)
              send8(sb, j * 1024 + t16 / 2, OFF_P + 32768 + i * PSRC, xs + 15360 + t16 / 2, i, j,
                    (pack_bf16(acc[32 + 4 * i], acc[33 + 4 * i]) & ~1u) | (L ^ 1), pack_bf16(acc[34 + 4 * i], acc[35 + 4 * i]));
          } else {
            if (p == 2) add_piece<false>(acc + 32, xs + 8192 + t16);
            const uint32_t ob = ((j + (p < 3 ? 7 : 5)) & 7) * PSRC + (p & 1) * 16384 + t16, tb = p == 2 ? L ^ 1 : p < 2;
#pragma unroll
            for (int i = 4; i < 8; i++)
              st16(sb, ob, OFF_P + i * 2048, (pack_bf16(acc[8 * i], acc[8 * i + 1]) & ~1u) | tb, pack_bf16(acc[8 * i + 2], acc[8 * i + 3]),
                   pack_bf16(acc[8 * i + 4], acc[8 * i + 5]), pack_bf16(acc[8 * i + 6], acc[8 * i + 7]));
          }
          hint_post(hint);
          TS(68 + L * 32 + p * 5);
          if (p == 1) {
            float s0 = 0.f, s1 = 0.f, s2 = 0.f, s3 = 0.f;
#pragma unroll
            for (int s = 0; s < 8; s++) {
              uint32_t u, v;
              lds64(u, v, xs + 8192 + s * 1024 + t16 / 2);
              s0 += bf_lo(u); s1 += bf_hi(u); s2 += bf_lo(v); s3 += bf_hi(v);
            }
            sts64(ytail(wg * 2) + t16 / 2, pack_bf16(s0, s1), pack_bf16(s2, s3));
          }
          if (p < 3) bar_arrive(NB_FREE + wg, 160);
          TS(67 + L * 32 + p * 5);
        }
        float acc[32];
        add_piece<true>(acc, xs + t16);
        add_piece<false>(acc, xs + 8192 + t16);
        bar_arrive(NB_FREE + wg, 160);
        load_own(xr, sb, L * 3 * TILE, j);
        bar_sync(NB_ORD0 + wg, 256);
        TS(84 + L * 32);
        uint32_t t, yn[2];
        mma_pass<64, PS_FFA, 4, 2048, 0, false, false>(acc, a, DESC_SW128, 0, rel, wg ? -1 : NB_ORD1, nullptr, 0, 0, 0, 0, 0, [&]() {
          t = tid_();
          lds64(yn[0], yn[1], ytail(wg * 2) + t * 8);
          mbar_wait(bar_full(12) + wg * 8, 1);
#pragma unroll
          for (int i = 0; i < 8; i++) lds128(&a[4 * i], xs + i * 2048 + t * 16);
        });
        TS(11 + L * 20);
        while (true) {
          uint32_t m = 0;
#pragma unroll
          for (int i = 0; i < 8; i++) m |= a[4 * i];
          if (!__any_sync(0xffffffffu, m & 1)) break;
#pragma unroll
          for (int i = 0; i < 8; i++) ld16(&a[4 * i], sb, j * PSRC + t * 16, OFF_P + 16384 + i * 2048);
        }
        TS(12 + L * 20);
#pragma unroll
        for (int i = 0; i < 18; i++)
          xr[i] = bf2_add(xr[i], i < 16 ? pack_bf16(acc[2 * i] + (bf_lo(a[i]) + bf_lo(a[16 + i])), acc[2 * i + 1] + (bf_hi(a[i]) + bf_hi(a[16 + i]))) : yn[i - 16]);
        TS(18 + L * 20);
        if (L == 0) {
          store_own(xr, sb, OFF_X2, j, t);
          RowStats rs;
          rs.add<18>(xr);
          rs.store(sb, 8192 + j * 128, t);
          hint_post(hint);
        } else {
          const uint32_t l = t & 31, wb = xs + w * 512;
          __syncwarp();
#pragma unroll
          for (int i = 0; i < 4; i++) stsm4(wb + i * 2048 + (l & 24) * 16 + (((l & 7) ^ (i * 2 + (l >> 4))) << 4), xr[4 * i], xr[4 * i + 1], xr[4 * i + 2], xr[4 * i + 3]);
          stsm4(wb + 8192 + l * 16, xr[16], xr[17], 0, 0);
          __syncwarp();
          uint8_t* op = (uint8_t*)P.out + row_off(rb, wg, w * 32 + (l >> 3)) + j * 128 + (l & 7) * 16;
#pragma unroll
          for (int i = 0; i < 4; i++) {
            uint32_t r[4];
            lds128(r, wb + ((l & 6) << 10) + ((l & 1) * 2 + (i >> 1)) * 128 + (((((i & 1) * 4 + (l >> 3)) ^ l) & 7) << 4));
            *(uint4*)(op + i * 16 * DM) = make_uint4(r[0], r[1], r[2], r[3]);
          }
          uint32_t r[4];
          lds128(r, wb + 8192 + l * 16);
          if (l < 16) *(uint4*)((uint8_t*)P.out + row_off(rb, wg, t) + 1024 + j * 16) = make_uint4(r[0], r[1], r[2], r[3]);
        }
      }
      TS(13 + L * 20);
    }
    bar_sync(NB_WG + wg, 128);
    if (tid_() == 0) mbar_arrive(bar_empty(12));
  }
}

typedef CUresult (*EncodeFn)(CUtensorMap*, CUtensorMapDataType, cuuint32_t, void*, const cuuint64_t*, const cuuint64_t*, const cuuint32_t*,
                             const cuuint32_t*, CUtensorMapInterleave, CUtensorMapSwizzle, CUtensorMapL2promotion, CUtensorMapFloatOOBfill);

void encode(EncodeFn fn, CUtensorMap* m, const void* p, int rank, const cuuint64_t* dims, const cuuint64_t* str, const cuuint32_t* box) {
  const cuuint32_t es[3] = {1, 1, 1};
  fn(m, CU_TENSOR_MAP_DATA_TYPE_BFLOAT16, rank, const_cast<void*>(p), dims, str, box, es, CU_TENSOR_MAP_INTERLEAVE_NONE,
     CU_TENSOR_MAP_SWIZZLE_128B, CU_TENSOR_MAP_L2_PROMOTION_L2_256B, CU_TENSOR_MAP_FLOAT_OOB_FILL_NONE);
}

__global__ void probe_kernel() {}

void make_roles(uint8_t* role) {
  int cnt[8];
  cudaFuncSetAttribute(probe_kernel, cudaFuncAttributeMaxDynamicSharedMemorySize, SMEM_BYTES);
  cudaFuncSetAttribute(probe_kernel, cudaFuncAttributeNonPortableClusterSizeAllowed, 1);
  for (int r = 7; r >= 0; r--) {
    int n = 0;
    cudaLaunchConfig_t cfg = {};
    cudaLaunchAttribute at;
    at.id = cudaLaunchAttributeClusterDimension; at.val.clusterDim.x = 2 * (r < 3 ? 4 : r + 1); at.val.clusterDim.y = at.val.clusterDim.z = 1;
    cfg.gridDim = dim3(at.val.clusterDim.x); cfg.blockDim = dim3(384); cfg.dynamicSmemBytes = SMEM_BYTES; cfg.attrs = &at; cfg.numAttrs = 1;
    if (cudaOccupancyMaxActiveClusters(&n, probe_kernel, &cfg) != cudaSuccess) { cudaGetLastError(); n = r > 3 ? 8 : 8 + cnt[7]; }
    cnt[r] = r > 3 ? n : n - cnt[7];
  }
  int key[64], c = 0, total = 0, seg = 0;
  for (int r = 0; r < 8; r++) total += cnt[r];
  for (; c < 64 - total; c++) key[c] = -1;
  for (int r = 0; r < 8; r++) {
    if (r && cnt[r] != cnt[r - 1]) seg++;
    for (int i = 0; i < cnt[r] && c < 64; i++) key[c++] = seg * 16 + i;
  }
  int order[64], n = 0;
  bool used[64] = {};
  for (int pass = 0; pass < 2; pass++)
    for (int i = 0; i < 64; i++) {
      if (used[i]) continue;
      int m[4], k = 0;
      for (int q = i; q < 64 && k < 4; q++) if (!used[q] && (pass || (key[q] == key[i] && key[i] >= 0))) m[k++] = q;
      if (k == 4) for (int q = 0; q < 4; q++) { used[m[q]] = true; order[n++] = m[q]; }
    }
  for (int i = 0; i < 64; i++) role[order[i]] = (uint8_t)(((i >> 2) & 7) << 3 | (i >> 5) << 2 | (i & 3));
}

}

extern "C" void kernel_launch(void* const* d_in, const int* in_sizes, int n_in, void* d_out, int out_size) {
  (void)in_sizes; (void)n_in; (void)out_size;
  Params P = {};
  P.wqkv = (const __nv_bfloat16*)d_in[1]; P.wo = (const __nv_bfloat16*)d_in[2];
  P.out = (__nv_bfloat16*)d_out; P.zero = 0;
  cudaGetSymbolAddress((void**)&P.scr, g_scr);
  make_roles(P.role);
  void* fnp = nullptr; cudaDriverEntryPointQueryResult qr;
  cudaGetDriverEntryPoint("cuTensorMapEncodeTiled", &fnp, cudaEnableDefault, &qr);
  EncodeFn fn = (EncodeFn)fnp;
  CUtensorMap mx, mg, mu, md;
  { const cuuint64_t dims[3] = {DM, SEQ / 2, 2}, str[2] = {DM * 4, DM * 2}; const cuuint32_t box[3] = {64, 64, 2}; encode(fn, &mx, d_in[0], 3, dims, str, box); }
  { const cuuint64_t dims[2] = {DFF, DM}, str[1] = {DFF * 2}; const cuuint32_t box[2] = {64, 64}; encode(fn, &mg, d_in[4], 2, dims, str, box); encode(fn, &mu, d_in[5], 2, dims, str, box); }
  { const cuuint64_t dims[2] = {DM, DFF}, str[1] = {DM * 2}; const cuuint32_t box[2] = {64, 64}; encode(fn, &md, d_in[6], 2, dims, str, box); }
  cudaFuncSetAttribute(fused_kernel, cudaFuncAttributeMaxDynamicSharedMemorySize, SMEM_BYTES);
  fused_kernel<<<128, 384, SMEM_BYTES, cudaStreamPerThread>>>(P, mx, mg, mu, md);
}
```

```cpp
#include <cuda_runtime.h>
#include <cuda_bf16.h>
#include <cuda.h>
#include <stdint.h>

#define TIMING 0
#define TRACE 0

namespace {

constexpr int SEQ = 2048, DM = 576, DFF = 4608;
constexpr int KV_LEAD = 5;
constexpr int D_KV = 6, D_WO = 3, D_T0 = 5;
constexpr int N_UP = 26, N_WO = 12;
constexpr int PF_AHEAD = 2;
constexpr int CH_LAST = 3;
constexpr uint32_t SB = 1024;
constexpr uint32_t SLOT = 16384;
constexpr uint32_t PSLOT = 13824;
constexpr uint32_t BARS = SB + 14 * SLOT;
constexpr int SMEM_BYTES = 14 * SLOT + 256 + 2560 + (TRACE ? 256 : 0);
__host__ __device__ constexpr uint32_t slot_addr(int s) { return SB + s * SLOT; }
__host__ __device__ constexpr uint32_t bar_full(int s) { return BARS + 8 * s; }
__host__ __device__ constexpr uint32_t bar_empty(int s) { return BARS + 128 + 8 * s; }
enum { NB_ORD0 = 1, NB_ORD1 = 2, NB_WG = 3  , NB_HALO = 5  , NB_FREE = 7  , NB_PUB = 9   };
constexpr uint32_t SM_EPOCH = BARS + 120;
__host__ __device__ constexpr uint32_t ytail(uint32_t k) { return k < 3 ? slot_addr(9) + PSLOT + k * SLOT : BARS + 256; }
constexpr uint32_t KSTG = 9 * 1152;

constexpr uint32_t TILE = 36 * 2048;
constexpr uint32_t OFF_X1 = 0  , OFF_O = TILE, OFF_X2 = 2 * TILE, OFF_ST = 4 * TILE  ;
constexpr uint32_t PSRC = 2 * 16384 + 7 * 1024;
constexpr uint32_t OFF_P = OFF_ST + 3 * 4096, OFF_HALO = OFF_P + 8 * PSRC  , OFF_HINT = OFF_HALO + 2 * 8 * 3072  ,
                   OFF_H = OFF_HINT + 16 * 128  , STRM = OFF_H + 8 * 24576;
constexpr uint32_t OFF_WPACK = 32 * STRM, OFF_FLAGS = OFF_WPACK + 8 * 24 * PSLOT;
__device__ __align__(1024) uint8_t g_scr[OFF_FLAGS + (8 + 64 + 128) * 32];

__device__ __forceinline__ uint32_t smem_u32(const void* p) { return (uint32_t)__cvta_generic_to_shared(p); }
extern __shared__ __align__(1024) uint8_t smem_raw[];
__device__ __forceinline__ uint32_t win() { return (blockIdx.x & 1) << 24; }
#define SA(A, W) ".reg .u32 sa;\nadd.u32 sa, " A ", " W ";\n"
__device__ __forceinline__ void mbar_init(uint32_t bar, uint32_t cnt) { asm volatile("{\n" SA("%0", "%2") "mbarrier.init.shared::cta.b64 [sa], %1;\n}" ::"r"(bar), "r"(cnt), "r"(win())); }
__device__ __forceinline__ void mbar_expect_tx(uint32_t bar, uint32_t bytes) { asm volatile("{\n" SA("%0", "%2") "mbarrier.arrive.expect_tx.shared::cta.b64 _, [sa], %1;\n}" ::"r"(bar), "r"(bytes), "r"(win()) : "memory"); }
__device__ __forceinline__ void mbar_arrive(uint32_t bar) { asm volatile("{\n" SA("%0", "%1") "mbarrier.arrive.shared::cta.b64 _, [sa];\n}" ::"r"(bar), "r"(win()) : "memory"); }
__device__ __forceinline__ uint32_t lds32(uint32_t a) { uint32_t v; asm volatile("{\n" SA("%1", "%2") "ld.shared.u32 %0, [sa];\n}" : "=r"(v) : "r"(a), "r"(win()) : "memory"); return v; }
__device__ __forceinline__ void lds64(uint32_t& x, uint32_t& y, uint32_t a) { asm volatile("{\n" SA("%2", "%3") "ld.shared.v2.u32 {%0,%1}, [sa];\n}" : "=r"(x), "=r"(y) : "r"(a), "r"(win()) : "memory"); }
__device__ __forceinline__ void lds128(uint32_t* v, uint32_t a) {
  asm volatile("{\n" SA("%4", "%5") "ld.shared.v4.u32 {%0,%1,%2,%3}, [sa];\n}" : "=r"(v[0]), "=r"(v[1]), "=r"(v[2]), "=r"(v[3]) : "r"(a), "r"(win()) : "memory");
}
__device__ __forceinline__ void stsm4(uint32_t a, uint32_t x, uint32_t y, uint32_t z, uint32_t w) {
  asm volatile("{\n" SA("%0", "%5") "stmatrix.sync.aligned.m8n8.x4.shared.b16 [sa], {%1,%2,%3,%4};\n}" ::"r"(a), "r"(x), "r"(y), "r"(z), "r"(w), "r"(win()) : "memory");
}
__device__ __forceinline__ void ldsm4(uint32_t* v, uint32_t a) {
  asm volatile("{\n" SA("%4", "%5") "ldmatrix.sync.aligned.m8n8.x4.shared.b16 {%0,%1,%2,%3}, [sa];\n}" : "=r"(v[0]), "=r"(v[1]), "=r"(v[2]), "=r"(v[3]) : "r"(a), "r"(win()) : "memory");
}
__device__ __forceinline__ void ldsm4t(uint32_t* v, uint32_t a) {
  asm volatile("{\n" SA("%4", "%5") "ldmatrix.sync.aligned.m8n8.x4.trans.shared.b16 {%0,%1,%2,%3}, [sa];\n}" : "=r"(v[0]), "=r"(v[1]), "=r"(v[2]), "=r"(v[3]) : "r"(a), "r"(win()) : "memory");
}
__device__ __forceinline__ void sts32(uint32_t a, uint32_t x) { asm volatile("{\n" SA("%0", "%2") "st.shared.u32 [sa], %1;\n}" ::"r"(a), "r"(x), "r"(win()) : "memory"); }
__device__ __forceinline__ void sts64(uint32_t a, uint32_t x, uint32_t y) { asm volatile("{\n" SA("%0", "%3") "st.shared.v2.u32 [sa], {%1,%2};\n}" ::"r"(a), "r"(x), "r"(y), "r"(win()) : "memory"); }
__device__ __forceinline__ void sts128(uint32_t a, uint32_t x, uint32_t y, uint32_t z, uint32_t w) {
  asm volatile("{\n" SA("%0", "%5") "st.shared.v4.u32 [sa], {%1,%2,%3,%4};\n}" ::"r"(a), "r"(x), "r"(y), "r"(z), "r"(w), "r"(win()) : "memory");
}
__device__ __forceinline__ void mbar_wait(uint32_t bar, uint32_t parity) {
  asm volatile("{\n.reg .pred p;\n" SA("%0", "%2") "LAB_WAIT:\nmbarrier.try_wait.parity.shared::cta.b64 p, [sa], %1;\n@!p bra LAB_WAIT;\n}" ::"r"(bar), "r"(parity), "r"(win()) : "memory");
}
__device__ __forceinline__ void timed_wait(uint32_t bar, uint32_t par) {
  asm volatile("{\n.reg .pred p;\n.reg .u64 t0, t1;\nmov.u64 t0, %%globaltimer;\nLAB_WD:\n"
               "mbarrier.try_wait.parity.shared::cta.b64 p, [%0], %1, 100000;\n@p bra LAB_OK;\n"
               "mov.u64 t1, %%globaltimer;\nsub.u64 t1, t1, t0;\nsetp.lt.u64 p, t1, 2000000000;\n@p bra LAB_WD;\ntrap;\nLAB_OK:\n}" ::"r"(bar + win()), "r"(par) : "memory");
}
__device__ __forceinline__ void flag_wait(const unsigned* flag, unsigned target) {
  asm volatile("{\n.reg .pred p;\n.reg .u32 v;\nLAB_WAIT:\nld.acquire.gpu.global.u32 v, [%0];\nsub.u32 v, v, %1;\n"
               "setp.lt.s32 p, v, 0;\nvote.sync.any.pred p, p, 0xffffffff;\n@p nanosleep.u32 100;\n@p bra LAB_WAIT;\n}" ::"l"(flag), "r"(target) : "memory");
}
__device__ __forceinline__ void hint_post(uint8_t* p) {
  __syncwarp();
  asm volatile("{\n.reg .pred p;\nelect.sync _|p, 0xffffffff;\n@p red.relaxed.gpu.global.add.u32 [%0], 1;\n}" ::"l"(p) : "memory");
}
__device__ __forceinline__ void hint_wait(const uint8_t* p, uint32_t target) {
  asm volatile("{\n.reg .pred p;\n.reg .u32 v;\nLAB_WAIT:\nld.relaxed.gpu.global.u32 v, [%0];\nsub.u32 v, v, %1;\n"
               "setp.lt.s32 p, v, 0;\nvote.sync.any.pred p, p, 0xffffffff;\n@p bra LAB_WAIT;\n}" ::"l"(p), "r"(target) : "memory");
}
__device__ __forceinline__ void flag_signal(unsigned* flag) { asm volatile("red.release.gpu.global.add.u32 [%0], 1;" ::"l"(flag) : "memory"); }
struct Rel {
  bool on; uint32_t base;
  uint32_t tr;
  __device__ __forceinline__ void operator()(int s) const {
    if (on) asm volatile("{\n" SA("%0", "%1") "mbarrier.arrive.shared::cluster.b64 _, [sa];\n}" ::"r"(bar_empty(s)), "r"(base) : "memory");
  }
};
__device__ __forceinline__ uint32_t cta_window(uint32_t rank) { uint32_t a; asm("mapa.shared::cluster.u32 %0, %1, %2;" : "=r"(a) : "r"(0), "r"(rank)); return a; }
#define ELECT ".reg .pred e;\nelect.sync _|e, 0xffffffff;\n"
__device__ __forceinline__ void w_expect_tx(uint32_t bar, uint32_t bytes) {
  asm volatile("{\n" ELECT "@e mbarrier.arrive.expect_tx.shared::cta.b64 _, [%0], %1;\n}" ::"r"(bar), "r"(bytes) : "memory");
}
__device__ __forceinline__ void w_tma_2d_mc(uint32_t dst, const CUtensorMap* m, int c0, int c1, uint32_t bar) {
  asm volatile("{\n" ELECT "@e cp.async.bulk.tensor.2d.shared::cluster.global.mbarrier::complete_tx::bytes.multicast::cluster [%0], [%1, {%3, %4}], [%2], %5;\n}"
               ::"r"(dst), "l"(m), "r"(bar), "r"(c0), "r"(c1), "h"((uint16_t)3) : "memory");
}
__device__ __forceinline__ void w_bulk_load_mc(uint32_t dst, const void* src, uint32_t bytes, uint32_t bar) {
  asm volatile("{\n" ELECT "@e cp.async.bulk.shared::cluster.global.mbarrier::complete_tx::bytes.multicast::cluster [%0], [%1], %2, [%3], %4;\n}"
               ::"r"(dst), "l"(src), "r"(bytes), "r"(bar), "h"((uint16_t)3) : "memory");
}
__device__ __forceinline__ void w_bulk_load(uint32_t dst, const void* src, uint32_t bytes, uint32_t bar) {
  asm volatile("{\n" ELECT "@e cp.async.bulk.shared::cluster.global.mbarrier::complete_tx::bytes [%0], [%1], %2, [%3];\n}" ::"r"(dst), "l"(src), "r"(bytes), "r"(bar) : "memory");
}
__device__ __forceinline__ void w_l2_prefetch(const void* src, uint32_t bytes) { asm volatile("{\n" ELECT "@e cp.async.bulk.prefetch.L2.global [%0], %1;\n}" ::"l"(src), "r"(bytes) : "memory"); }
__device__ __forceinline__ void w_tma_prefetch(const CUtensorMap* m, int c0, int c1) {
  asm volatile("{\n" ELECT "@e cp.async.bulk.prefetch.tensor.2d.L2.global [%0, {%1, %2}];\n}" ::"l"(m), "r"(c0), "r"(c1) : "memory");
}
__device__ __forceinline__ void tma_3d(uint32_t dst, const CUtensorMap* m, int c0, int c1, int c2, uint32_t bar) {
  asm volatile("cp.async.bulk.tensor.3d.shared::cluster.global.mbarrier::complete_tx::bytes [%0], [%1, {%3, %4, %5}], [%2];"
               ::"r"(dst), "l"(m), "r"(bar), "r"(c0), "r"(c1), "r"(c2) : "memory");
}
__device__ __forceinline__ void wg_fence() { asm volatile("wgmma.fence.sync.aligned;" ::: "memory"); }
__device__ __forceinline__ void wg_commit() { asm volatile("wgmma.commit_group.sync.aligned;" ::: "memory"); }
template <int N> __device__ __forceinline__ void wg_wait() { asm volatile("wgmma.wait_group.sync.aligned %0;" ::"n"(N) : "memory"); }
__device__ __forceinline__ void bar_sync(int id, int n) { asm volatile("bar.sync %0, %1;" ::"r"(id), "r"(n) : "memory"); }
__device__ __forceinline__ void bar_arrive(int id, int n) { asm volatile("bar.arrive %0, %1;" ::"r"(id), "r"(n) : "memory"); }
__device__ __forceinline__ uint32_t pack_bf16(float lo, float hi) { uint32_t r; asm("cvt.rn.bf16x2.f32 %0, %1, %2;" : "=r"(r) : "f"(hi), "f"(lo)); return r; }
__device__ __forceinline__ float bf_lo(uint32_t w) { return __uint_as_float(w << 16); }
__device__ __forceinline__ float bf_hi(uint32_t w) { return __uint_as_float(w & 0xffff0000u); }
__device__ __forceinline__ float bf_round(float x) { return bf_lo(pack_bf16(x, 0.f)); }
__device__ __forceinline__ uint32_t bf2_sub(uint32_t a, uint32_t b) { uint32_t r; asm("sub.rn.bf16x2 %0, %1, %2;" : "=r"(r) : "r"(a), "r"(b)); return r; }
__device__ __forceinline__ uint32_t bf2_add(uint32_t a, uint32_t b) { uint32_t r; asm("add.rn.bf16x2 %0, %1, %2;" : "=r"(r) : "r"(a), "r"(b)); return r; }
#define GADDR(B, O, I) "cvt.u64.u32 ad, " O ";\nadd.u64 ad, ad, " B ";\nadd.u64 ad, ad, " I ";\n"
__device__ __forceinline__ void ld16(uint32_t* v, const uint8_t* ub, uint32_t off, uint32_t imm) {
  asm volatile("{\n.reg .b128 z;\n.reg .b64 x, y, ad;\n" GADDR("%4", "%5", "%6") "ld.relaxed.gpu.global.b128 z, [ad];\n"
               "mov.b128 {x, y}, z;\nmov.b64 {%0,%1}, x;\nmov.b64 {%2,%3}, y;\n}"
               : "=r"(v[0]), "=r"(v[1]), "=r"(v[2]), "=r"(v[3]) : "l"(ub), "r"(off), "l"((uint64_t)imm) : "memory");
}
__device__ __forceinline__ void ld8(uint32_t* v, const uint8_t* ub, uint32_t off, uint32_t imm) {
  asm volatile("{\n.reg .b64 x, ad;\n" GADDR("%2", "%3", "%4") "ld.relaxed.gpu.global.b64 x, [ad];\nmov.b64 {%0,%1}, x;\n}"
               : "=r"(v[0]), "=r"(v[1]) : "l"(ub), "r"(off), "l"((uint64_t)imm) : "memory");
}
__device__ __forceinline__ void st16(uint8_t* ub, uint32_t off, uint32_t imm, uint32_t a, uint32_t b, uint32_t c, uint32_t d) {
  asm volatile("{\n.reg .b128 z;\n.reg .b64 x, y, ad;\n" GADDR("%0", "%1", "%2") "mov.b64 x, {%3,%4};\nmov.b64 y, {%5,%6};\nmov.b128 z, {x, y};\n"
               "st.relaxed.gpu.global.b128 [ad], z;\n}" ::"l"(ub), "r"(off), "l"((uint64_t)imm), "r"(a), "r"(b), "r"(c), "r"(d) : "memory");
}
__device__ __forceinline__ void st8(uint8_t* ub, uint32_t off, uint32_t imm, uint32_t a, uint32_t b) {
  asm volatile("{\n.reg .b64 x, ad;\n" GADDR("%0", "%1", "%2") "mov.b64 x, {%3,%4};\nst.relaxed.gpu.global.b64 [ad], x;\n}"
               ::"l"(ub), "r"(off), "l"((uint64_t)imm), "r"(a), "r"(b) : "memory");
}
__device__ __forceinline__ void send8(uint8_t* ub, uint32_t off, uint32_t imm, uint32_t sm, int i, int j, uint32_t a, uint32_t b) {
  asm volatile("{\n.reg .pred p, q, e;\n.reg .b64 x, ad;\n" SA("%3", "%8") GADDR("%0", "%1", "%2")
               "setp.lt.s32 p, %4, %5;\nsetp.gt.s32 q, %4, %5;\nsetp.eq.s32 e, %4, %5;\nmov.b64 x, {%6,%7};\n"
               "@p st.relaxed.gpu.global.b64 [ad+-1024], x;\n@q st.relaxed.gpu.global.b64 [ad], x;\n@e st.shared.v2.u32 [sa], {%6,%7};\n}"
               ::"l"(ub), "r"(off), "l"((uint64_t)imm), "r"(sm), "r"(i), "r"(j), "r"(a), "r"(b), "r"(win()) : "memory");
}
__device__ __forceinline__ uint4 ldg_line(const void* p) {
  uint4 v; asm volatile("ld.global.nc.L2::128B.v4.u32 {%0,%1,%2,%3}, [%4];" : "=r"(v.x), "=r"(v.y), "=r"(v.z), "=r"(v.w) : "l"(p)); return v;
}
__device__ __forceinline__ void stg4(void* ub, uint32_t off, uint32_t imm, uint32_t v) {
  asm volatile("{\n.reg .b64 ad;\n" GADDR("%0", "%1", "%2") "st.global.u32 [ad], %3;\n}" ::"l"(ub), "r"(off), "l"((uint64_t)imm), "r"(v) : "memory");
}
__device__ __forceinline__ uint32_t tid_() { uint32_t t; asm volatile("mov.u32 %0, %%tid.x;" : "=r"(t)); return t & 127; }
__device__ __forceinline__ uint32_t token() { uint32_t c; asm volatile("mov.u32 %0, %%clock;" : "=r"(c) :: "memory"); return c | 1; }
__device__ __forceinline__ uint32_t nz(uint32_t w) { return w ? w : 0x8000u; }
__device__ __forceinline__ void mma16816(float (&c)[4], uint32_t a0, uint32_t a1, uint32_t a2, uint32_t a3, uint32_t b0, uint32_t b1) {
  asm("mma.sync.aligned.m16n8k16.row.col.f32.bf16.bf16.f32 {%0,%1,%2,%3}, {%4,%5,%6,%7}, {%8,%9}, {%0,%1,%2,%3};"
               : "+f"(c[0]), "+f"(c[1]), "+f"(c[2]), "+f"(c[3]) : "r"(a0), "r"(a1), "r"(a2), "r"(a3), "r"(b0), "r"(b1));
}
__device__ __forceinline__ void mma1688(float (&c)[4], uint32_t a0, uint32_t a1, uint32_t b0) {
  asm("mma.sync.aligned.m16n8k8.row.col.f32.bf16.bf16.f32 {%0,%1,%2,%3}, {%4,%5}, {%6}, {%0,%1,%2,%3};"
               : "+f"(c[0]), "+f"(c[1]), "+f"(c[2]), "+f"(c[3]) : "r"(a0), "r"(a1), "r"(b0));
}
__device__ __forceinline__ float ex2(float x) { float r; asm("ex2.approx.ftz.f32 %0, %1;" : "=f"(r) : "f"(x)); return r; }
__device__ __forceinline__ float quad_sum(float v) { v += __shfl_xor_sync(0xffffffffu, v, 1); v += __shfl_xor_sync(0xffffffffu, v, 2); return v; }
__device__ __forceinline__ float quad_max(float v) { v = fmaxf(v, __shfl_xor_sync(0xffffffffu, v, 1)); v = fmaxf(v, __shfl_xor_sync(0xffffffffu, v, 2)); return v; }

__device__ __forceinline__ void wgmma_rs_n64(float (&d)[32], uint32_t a0, uint32_t a1, uint32_t a2, uint32_t a3, uint64_t desc, int scale_d) {
  asm volatile("{\n.reg .pred p;\nsetp.ne.b32 p, %37, 0;\n"
    "wgmma.mma_async.sync.aligned.m64n64k16.f32.bf16.bf16 "
    "{%0, %1, %2, %3, %4, %5, %6, %7, %8, %9, %10, %11, %12, %13, %14, %15, %16, %17, %18, %19, %20, %21, %22, %23, %24, %25, %26, %27, %28, %29, %30, %31}, "
    "{%32, %33, %34, %35}, %36, p, 1, 1, 1;\n}\n"
    : "+f"(d[0]), "+f"(d[1]), "+f"(d[2]), "+f"(d[3]), "+f"(d[4]), "+f"(d[5]), "+f"(d[6]), "+f"(d[7]), "+f"(d[8]), "+f"(d[9]), "+f"(d[10]), "+f"(d[11]), "+f"(d[12]), "+f"(d[13]), "+f"(d[14]), "+f"(d[15]), "+f"(d[16]), "+f"(d[17]), "+f"(d[18]), "+f"(d[19]), "+f"(d[20]), "+f"(d[21]), "+f"(d[22]), "+f"(d[23]), "+f"(d[24]), "+f"(d[25]), "+f"(d[26]), "+f"(d[27]), "+f"(d[28]), "+f"(d[29]), "+f"(d[30]), "+f"(d[31])
    : "r"(a0), "r"(a1), "r"(a2), "r"(a3), "l"(desc), "r"(scale_d));
}

__device__ __forceinline__ void wgmma_rs_n72(float (&d)[36], uint32_t a0, uint32_t a1, uint32_t a2, uint32_t a3, uint64_t desc, int scale_d) {
  asm volatile("{\n.reg .pred p;\nsetp.ne.b32 p, %41, 0;\n"
    "wgmma.mma_async.sync.aligned.m64n72k16.f32.bf16.bf16 "
    "{%0, %1, %2, %3, %4, %5, %6, %7, %8, %9, %10, %11, %12, %13, %14, %15, %16, %17, %18, %19, %20, %21, %22, %23, %24, %25, %26, %27, %28, %29, %30, %31, %32, %33, %34, %35}, "
    "{%36, %37, %38, %39}, %40, p, 1, 1, 1;\n}\n"
    : "+f"(d[0]), "+f"(d[1]), "+f"(d[2]), "+f"(d[3]), "+f"(d[4]), "+f"(d[5]), "+f"(d[6]), "+f"(d[7]), "+f"(d[8]), "+f"(d[9]), "+f"(d[10]), "+f"(d[11]), "+f"(d[12]), "+f"(d[13]), "+f"(d[14]), "+f"(d[15]), "+f"(d[16]), "+f"(d[17]), "+f"(d[18]), "+f"(d[19]), "+f"(d[20]), "+f"(d[21]), "+f"(d[22]), "+f"(d[23]), "+f"(d[24]), "+f"(d[25]), "+f"(d[26]), "+f"(d[27]), "+f"(d[28]), "+f"(d[29]), "+f"(d[30]), "+f"(d[31]), "+f"(d[32]), "+f"(d[33]), "+f"(d[34]), "+f"(d[35])
    : "r"(a0), "r"(a1), "r"(a2), "r"(a3), "l"(desc), "r"(scale_d));
}

__device__ __forceinline__ void wgmma_rs_n128(float (&d)[64], uint32_t a0, uint32_t a1, uint32_t a2, uint32_t a3, uint64_t desc, int scale_d) {
  asm volatile("{\n.reg .pred p;\nsetp.ne.b32 p, %69, 0;\n"
    "wgmma.mma_async.sync.aligned.m64n128k16.f32.bf16.bf16 "
    "{%0, %1, %2, %3, %4, %5, %6, %7, %8, %9, %10, %11, %12, %13, %14, %15, %16, %17, %18, %19, %20, %21, %22, %23, %24, %25, %26, %27, %28, %29, %30, %31, %32, %33, %34, %35, %36, %37, %38, %39, %40, %41, %42, %43, %44, %45, %46, %47, %48, %49, %50, %51, %52, %53, %54, %55, %56, %57, %58, %59, %60, %61, %62, %63}, "
    "{%64, %65, %66, %67}, %68, p, 1, 1, 1;\n}\n"
    : "+f"(d[0]), "+f"(d[1]), "+f"(d[2]), "+f"(d[3]), "+f"(d[4]), "+f"(d[5]), "+f"(d[6]), "+f"(d[7]), "+f"(d[8]), "+f"(d[9]), "+f"(d[10]), "+f"(d[11]), "+f"(d[12]), "+f"(d[13]), "+f"(d[14]), "+f"(d[15]), "+f"(d[16]), "+f"(d[17]), "+f"(d[18]), "+f"(d[19]), "+f"(d[20]), "+f"(d[21]), "+f"(d[22]), "+f"(d[23]), "+f"(d[24]), "+f"(d[25]), "+f"(d[26]), "+f"(d[27]), "+f"(d[28]), "+f"(d[29]), "+f"(d[30]), "+f"(d[31]), "+f"(d[32]), "+f"(d[33]), "+f"(d[34]), "+f"(d[35]), "+f"(d[36]), "+f"(d[37]), "+f"(d[38]), "+f"(d[39]), "+f"(d[40]), "+f"(d[41]), "+f"(d[42]), "+f"(d[43]), "+f"(d[44]), "+f"(d[45]), "+f"(d[46]), "+f"(d[47]), "+f"(d[48]), "+f"(d[49]), "+f"(d[50]), "+f"(d[51]), "+f"(d[52]), "+f"(d[53]), "+f"(d[54]), "+f"(d[55]), "+f"(d[56]), "+f"(d[57]), "+f"(d[58]), "+f"(d[59]), "+f"(d[60]), "+f"(d[61]), "+f"(d[62]), "+f"(d[63])
    : "r"(a0), "r"(a1), "r"(a2), "r"(a3), "l"(desc), "r"(scale_d));
}

__device__ __forceinline__ void wgmma_rs_n144(float (&d)[72], uint32_t a0, uint32_t a1, uint32_t a2, uint32_t a3, uint64_t desc, int scale_d) {
  asm volatile("{\n.reg .pred p;\nsetp.ne.b32 p, %77, 0;\n"
    "wgmma.mma_async.sync.aligned.m64n144k16.f32.bf16.bf16 "
    "{%0, %1, %2, %3, %4, %5, %6, %7, %8, %9, %10, %11, %12, %13, %14, %15, %16, %17, %18, %19, %20, %21, %22, %23, %24, %25, %26, %27, %28, %29, %30, %31, %32, %33, %34, %35, %36, %37, %38, %39, %40, %41, %42, %43, %44, %45, %46, %47, %48, %49, %50, %51, %52, %53, %54, %55, %56, %57, %58, %59, %60, %61, %62, %63, %64, %65, %66, %67, %68, %69, %70, %71}, "
    "{%72, %73, %74, %75}, %76, p, 1, 1, 1;\n}\n"
    : "+f"(d[0]), "+f"(d[1]), "+f"(d[2]), "+f"(d[3]), "+f"(d[4]), "+f"(d[5]), "+f"(d[6]), "+f"(d[7]), "+f"(d[8]), "+f"(d[9]), "+f"(d[10]), "+f"(d[11]), "+f"(d[12]), "+f"(d[13]), "+f"(d[14]), "+f"(d[15]), "+f"(d[16]), "+f"(d[17]), "+f"(d[18]), "+f"(d[19]), "+f"(d[20]), "+f"(d[21]), "+f"(d[22]), "+f"(d[23]), "+f"(d[24]), "+f"(d[25]), "+f"(d[26]), "+f"(d[27]), "+f"(d[28]), "+f"(d[29]), "+f"(d[30]), "+f"(d[31]), "+f"(d[32]), "+f"(d[33]), "+f"(d[34]), "+f"(d[35]), "+f"(d[36]), "+f"(d[37]), "+f"(d[38]), "+f"(d[39]), "+f"(d[40]), "+f"(d[41]), "+f"(d[42]), "+f"(d[43]), "+f"(d[44]), "+f"(d[45]), "+f"(d[46]), "+f"(d[47]), "+f"(d[48]), "+f"(d[49]), "+f"(d[50]), "+f"(d[51]), "+f"(d[52]), "+f"(d[53]), "+f"(d[54]), "+f"(d[55]), "+f"(d[56]), "+f"(d[57]), "+f"(d[58]), "+f"(d[59]), "+f"(d[60]), "+f"(d[61]), "+f"(d[62]), "+f"(d[63]), "+f"(d[64]), "+f"(d[65]), "+f"(d[66]), "+f"(d[67]), "+f"(d[68]), "+f"(d[69]), "+f"(d[70]), "+f"(d[71])
    : "r"(a0), "r"(a1), "r"(a2), "r"(a3), "l"(desc), "r"(scale_d));
}

template <int N> struct WG;
template <> struct WG<64>  { static __device__ __forceinline__ void f(float (&d)[32], const uint32_t* a, uint64_t ds, int s) { wgmma_rs_n64(d, a[0], a[1], a[2], a[3], ds, s); } };
template <> struct WG<72>  { static __device__ __forceinline__ void f(float (&d)[36], const uint32_t* a, uint64_t ds, int s) { wgmma_rs_n72(d, a[0], a[1], a[2], a[3], ds, s); } };
template <> struct WG<128> { static __device__ __forceinline__ void f(float (&d)[64], const uint32_t* a, uint64_t ds, int s) { wgmma_rs_n128(d, a[0], a[1], a[2], a[3], ds, s); } };
template <> struct WG<144> { static __device__ __forceinline__ void f(float (&d)[72], const uint32_t* a, uint64_t ds, int s) { wgmma_rs_n144(d, a[0], a[1], a[2], a[3], ds, s); } };

constexpr uint64_t DESC_SW128 = ((uint64_t)(8192 >> 4) << 16) | ((uint64_t)(1024 >> 4) << 32) | (1ull << 62);
constexpr uint64_t DESC_KV = ((uint64_t)(128 >> 4) << 16) | ((uint64_t)(768 >> 4) << 32);
constexpr uint64_t DESC_Q = ((uint64_t)(128 >> 4) << 16) | ((uint64_t)(1536 >> 4) << 32);

template <int V> struct IntC { static constexpr int value = V; };
enum { PS_KV, PS_Q, PS_WO, PS_FF, PS_FFA   };
template <int PS> __host__ __device__ constexpr int pass_slot(int i) {
  return PS == PS_KV ? (i < 3 ? 9 + i : i - 3) : PS == PS_WO ? 6 + i : i;
}

__device__ __forceinline__ void load_frag(uint32_t (&a)[144], int i, const uint8_t* sb, uint32_t uo, uint32_t t) {
  if (i < 32) ld16(&a[4 * i], sb, uo + t * 16, i * 2048);
  else { ld8(&a[4 * i], sb, uo + t * 8, i * 2048); ld8(&a[4 * i + 2], sb, uo + t * 8, i * 2048 + 1024); }
}
__device__ __forceinline__ void store_own(const uint32_t (&y)[18], uint8_t* sb, uint32_t uo, int j, uint32_t t) {
#pragma unroll
  for (int i = 0; i < 4; i++) st16(sb, uo + j * 8192 + t * 16, i * 2048, nz(y[4 * i]), y[4 * i + 1], y[4 * i + 2], y[4 * i + 3]);
  st8(sb, uo + j * 1024 + t * 8, 65536, nz(y[16]), y[17]);
}
__device__ __forceinline__ void load_own(uint32_t* y, const uint8_t* sb, uint32_t uo, int j) {
  const uint32_t t = tid_();
#pragma unroll
  for (int i = 0; i < 4; i++) ld16(&y[4 * i], sb, uo + j * 8192 + t * 16, i * 2048);
  ld8(&y[16], sb, uo + j * 1024 + t * 8, 65536);
}

#define TR(i) do {} while (0)
struct NoTail { __device__ __forceinline__ void operator()() const {} };
template <int N, int PS, int KPS, int KSTEP, int CHK, bool SUB, bool HREL = false, class Tail = NoTail>
__device__ __forceinline__ void mma_pass(float (&acc)[N / 2], uint32_t (&a)[144], uint64_t desc, uint32_t par, const Rel& rel, int bar_id,
                                         const uint8_t* sb = nullptr, uint32_t uo = 0, uint32_t flag = 0, uint32_t m0 = 0, uint32_t m1 = 0, uint32_t park = 0, Tail tail = Tail()) {
  constexpr int NS = 36 / KPS;
  auto check = [&](int lo, int hi, uint32_t m0_) {
    auto missing = [&]() {
      uint32_t u[3] = {m0_, m0_, m0_};
#pragma unroll
      for (int i = hi - 1; i >= lo; i--) {
        u[i % 3] = min(u[i % 3], a[4 * i]);
        if (i >= 32) u[i % 3] = min(u[i % 3], a[4 * i + 2]);
      }
      return __any_sync(0xffffffffu, (min(u[0], min(u[1], u[2])) | flag) == 0);
    };
    if (__builtin_expect(missing(), 0)) {
      do {
        const uint32_t t = tid_();
#pragma unroll
        for (int i = lo; i < hi; i++) load_frag(a, i, sb, uo, t);
      } while (missing());
    }
  };
#pragma unroll
  for (int s = 0; s < NS; s++) {
    const int sl = pass_slot<PS>(s);
    if (CHK && s == 0 && !SUB) check(0, CHK * KPS, ~0u);
    if (CHK && s == CHK) check(CHK * KPS, 36, token());
    if (SUB) {
#pragma unroll
      for (int i = s * KPS * 4; i < (s + 1) * KPS * 4; i += 2) { a[i] = bf2_sub(a[i], m0); a[i + 1] = bf2_sub(a[i + 1], m1); }
    }
    if (PS == PS_KV && s == 0) sts128(park + tid_() * 16, a[0], a[1], a[2], a[3]);
    constexpr int TB = PS == PS_KV ? 0 : PS == PS_Q ? 26 : PS == PS_WO ? 40 : SUB ? 54 : PS == PS_FFA ? 74 : -1;
    if (TB >= 0) TR(TB + 2 * s);
    mbar_wait(bar_full(sl), sl < 9 ? par : par ^ 1);
    if (TB >= 0) TR(TB + 2 * s + 1);
    wg_fence();
#pragma unroll
    for (int kk = 0; kk < KPS; kk++)
      WG<N>::f(acc, &a[(s * KPS + kk) * 4], desc + ((slot_addr(sl) + kk * KSTEP) >> 4), (s | kk) || PS == PS_FFA);
    wg_commit();
    if (CHK && s < 2 && N_UP < 36 && !flag) {
      const uint32_t t = tid_();
#pragma unroll
      for (int i = s ? (N_UP + 36) / 2 : N_UP; i < (s ? 36 : (N_UP + 36) / 2); i++) load_frag(a, i, sb, uo, t);
    }
    if (s == (PS == PS_KV ? KV_LEAD : NS - 1) && bar_id >= 0) bar_arrive(bar_id, 256);
    if (s > 0) {
      wg_wait<1>();
      if (!(PS == PS_WO && s > 3)) rel(pass_slot<PS>(s - 1));
    }
    if (HREL && s == 3 && flag) {
#pragma unroll
      for (int i = 0; i < 12; i++) ld16(&a[4 * i], sb, uo, i * 2048);
    }
  }
  constexpr int TE = PS == PS_KV ? 24 : PS == PS_Q ? 38 : PS == PS_WO ? 52 : SUB ? 72 : PS == PS_FFA ? 92 : -1;
  tail();
  if (TE >= 0) TR(TE);
  wg_wait<0>();
  if (TE >= 0) TR(TE + 1);
  if (PS != PS_WO) rel(pass_slot<PS>(NS - 1));
}

template <int NF, int N0 = 0> __device__ __forceinline__ void load_frags(uint32_t (&a)[144], const uint8_t* sb, uint32_t uo, uint32_t t) {
#pragma unroll
  for (int i = N0; i < NF; i++) load_frag(a, i, sb, uo, t);
}
__device__ __forceinline__ void ln_scalars(float s1, float s2, uint32_t& m, float& var, uint32_t zero) {
  const float mean = s1 * (1.f / DM);
  var = s2 * (1.f / DM) - mean * mean;
  m = pack_bf16(mean, mean) ^ (__float_as_uint(var) & zero);
}
__device__ __forceinline__ float ln_rstd(float var, float after, uint32_t zero) {
  var = __uint_as_float(__float_as_uint(var) ^ (__float_as_uint(after) & zero));
  float sd, r;
  asm("sqrt.approx.ftz.f32 %0, %1;" : "=f"(sd) : "f"(bf_round(bf_round(fmaxf(var, 0.f)) + 1e-5f)));
  asm("rcp.approx.ftz.f32 %0, %1;" : "=f"(r) : "f"(bf_round(sd)));
  return r;
}
template <int NF> __device__ __forceinline__ void gather_ln(uint32_t (&a)[144], const uint8_t* sb, uint32_t uo, uint32_t sto,
                                          uint32_t& m0, uint32_t& m1, float& r0, float& r1, uint32_t zero) {
  uint32_t u[32];
  const uint32_t t = tid_(), so = sto + (t >> 5) * 1024 + (t & 28) * 4;
#pragma unroll
  for (int i = 0; i < 8; i++) ld16(&u[4 * i], sb, so, OFF_ST + i * 128);
  load_frags<N_UP>(a, sb, uo, t);
  while (true) {
    uint32_t m = a[4 * NF - 4];
#pragma unroll
    for (int i = NF - 2; i >= 0; i--) m = min(m, a[4 * i]);
#pragma unroll
    for (int i = 0; i < 8; i++) m = min(m, u[4 * i]);
    if (!__any_sync(0xffffffffu, m == 0)) break;
#pragma unroll
    for (int i = 0; i < 8; i++) ld16(&u[4 * i], sb, so, OFF_ST + i * 128);
    load_frags<NF>(a, sb, uo, t);
  }
  float v[4];
#pragma unroll
  for (int k = 0; k < 4; k++)
    v[k] = ((__uint_as_float(u[k]) + __uint_as_float(u[4 + k])) + (__uint_as_float(u[8 + k]) + __uint_as_float(u[12 + k]))) +
           ((__uint_as_float(u[16 + k]) + __uint_as_float(u[20 + k])) + (__uint_as_float(u[24 + k]) + __uint_as_float(u[28 + k])));
  ln_scalars(v[1], v[0], m0, r0, zero); ln_scalars(v[3], v[2], m1, r1, zero);
}
struct Stats {
  float s[4] = {0, 0, 0, 0}, d0[4] = {0, 0, 0, 0}, d1[4] = {0, 0, 0, 0};
  __device__ __forceinline__ void add16(const uint32_t* f) {
    mma16816(s, f[0], f[1], f[2], f[3], 0x3f803f80u, 0x3f803f80u);
    mma1688(d0, f[0], f[1], f[0]); mma1688(d1, f[0], f[1], f[1]);
    mma1688(d0, f[2], f[3], f[2]); mma1688(d1, f[2], f[3], f[3]);
  }
  __device__ __forceinline__ float sq0(int g) const { return (g & 1) ? d0[1] : d0[0]; }
  __device__ __forceinline__ float sq1(int g) const { return (g & 1) ? d1[3] : d1[2]; }
};
struct RowStats {
  float s[4] = {0, 0, 0, 0}, u[4] = {0, 0, 0, 0};
  template <int N> __device__ __forceinline__ void add(const uint32_t* y) {
#pragma unroll
    for (int i = 0; i < N; i++) {
      const float lo = bf_lo(y[i]), hi = bf_hi(y[i]);
      const int r = (i & 1) * 2;
      s[r] = fmaf(lo, lo, s[r]); u[r] = fmaf(hi, hi, u[r]); s[r + 1] += lo; u[r + 1] += hi;
    }
  }
  __device__ __forceinline__ uint32_t fold() {
    uint32_t x = 0;
#pragma unroll
    for (int i = 0; i < 4; i++) { s[i] += u[i]; u[i] = 0; x |= __float_as_uint(s[i]); }
    return x;
  }
  __device__ __forceinline__ void store(uint8_t* sb, uint32_t sto, uint32_t t) {
    fold();
#pragma unroll
    for (int i = 0; i < 4; i++) s[i] += __shfl_xor_sync(0xffffffffu, s[i], 1);
#pragma unroll
    for (int i = 0; i < 4; i++) s[i] += __shfl_xor_sync(0xffffffffu, s[i], 2);
    if ((t & 3) == 0) st16(sb, sto + (t >> 5) * 1024 + (t & 28) * 4, OFF_ST, __float_as_uint(s[0]) | 1u, __float_as_uint(s[1]), __float_as_uint(s[2]), __float_as_uint(s[3]));
  }
};
template <bool SET> __device__ __forceinline__ void add_piece(float* acc, uint32_t sm) {
#pragma unroll
  for (int i = 0; i < 4; i++) {
    uint32_t v[4];
    lds128(v, sm + i * 2048);
#pragma unroll
    for (int k = 0; k < 4; k++) {
      acc[8 * i + 2 * k] = SET ? bf_lo(v[k]) : acc[8 * i + 2 * k] + bf_lo(v[k]);
      acc[8 * i + 2 * k + 1] = SET ? bf_hi(v[k]) : acc[8 * i + 2 * k + 1] + bf_hi(v[k]);
    }
  }
}

#define TS(i) do {} while (0)
#define TSP(i) do {} while (0)
#define TSH(i) do {} while (0)

__device__ __forceinline__ uint32_t row_off(int rb, int wg, uint32_t t) { return (rb * 128 + wg + ((t >> 5) * 16 + (t & 15)) * 2) * (2 * DM); }

__device__ __forceinline__ const __nv_bfloat16* wo_src(const __nv_bfloat16* wo, int k, int u, int j) {
  const int ko = k < 512 ? (k >> 6) * 72 + (k & 63) : ((k >> 3) & 7) * 72 + 64 + (k & 7);
  return wo + ko * 576 + (u < 8 ? j * 64 + u * 8 : 512 + j * 8);
}

struct Params {
  const __nv_bfloat16* wqkv;
  uint8_t* scr;
  uint8_t role[64];
  const __nv_bfloat16* wo;
  __nv_bfloat16* out;
  uint8_t* times;
  unsigned zero;
};

__cluster_dims__(2, 1, 1)
__global__ void __launch_bounds__(384, 1)
fused_kernel(const __grid_constant__ Params P, const __grid_constant__ CUtensorMap map_x, const __grid_constant__ CUtensorMap map_wg,
             const __grid_constant__ CUtensorMap map_wu, const __grid_constant__ CUtensorMap map_wd) {
  const int wg = __shfl_sync(0xffffffffu, threadIdx.x >> 7, 0);
  const int cta = blockIdx.x, rank = cta & 1, role = P.role[cta >> 1], j = role & 7, rb = (role >> 3) * 2 + rank;
  const uint32_t own = win();
  unsigned* const flags = (unsigned*)(P.scr + OFF_FLAGS);
  if (__shfl_sync(0xffffffffu, threadIdx.x >> 5, 0) == 11) {
    if (threadIdx.x == 352) {
#pragma unroll
      for (int i = 0; i < 14; i++) { mbar_init(bar_full(i), 1); mbar_init(bar_empty(i), i < 12 ? 4 : i == 12 ? 8 : 2); }
      mbar_init(bar_full(14), 1); mbar_init(bar_empty(14), 1);
      asm volatile("fence.mbarrier_init.release.cluster;" ::: "memory");
      if (smem_u32(smem_raw) != own + SB) asm volatile("trap;");
    }
    __syncwarp();
    bar_arrive(0, 384);
    asm volatile("barrier.cluster.arrive.relaxed.aligned;" ::: "memory");
    if (threadIdx.x == 352) {
#pragma unroll 1
      for (int c = 0; c < 9; c++) {
        mbar_expect_tx(bar_full(c), SLOT);
        tma_3d(own + slot_addr(c), &map_x, c * 64, rb * 64, 0, own + bar_full(c));
      }
    }
  } else {
    const bool on = threadIdx.x < 324;
    const int k = rb * 36 + (on ? threadIdx.x / 36 : 0) * 4 + (threadIdx.x & 3), u = (threadIdx.x % 36) >> 2;
    const uint4* s = (const uint4*)(P.wqkv + k * 1728 + j * 72 + u * 8);
    const uint4 vk = ldg_line(s + 72), vv = ldg_line(s + 144);
    const unsigned ep0 = *(volatile unsigned*)&flags[(72 + cta) * 8];
    asm volatile("barrier.cluster.arrive.relaxed.aligned;" ::: "memory");
    bar_sync(0, 384);
    uint8_t* d = P.scr + OFF_WPACK + j * 24 * PSLOT;
    if (on) {
      const uint32_t dkv = (k / 48) * PSLOT + u * 768 + (k % 48) * 16;
      st16(d, dkv, 0, vk.x, vk.y, vk.z, vk.w);
      st16(d, dkv, 9 * 768, vv.x, vv.y, vv.z, vv.w);
    }
    asm volatile("fence.proxy.async.global;" ::: "memory");
    bar_arrive(NB_PUB + 3, 384);
    if (threadIdx.x == 351) sts32(SM_EPOCH, ep0);
    if (wg == 2) bar_sync(NB_PUB + 1, 96);
  }
  __syncwarp();
  asm volatile("barrier.cluster.wait.acquire.aligned;" ::: "memory");

  if (wg == 2) {
    asm volatile("setmaxnreg.dec.sync.aligned.u32 24;");
    const int pw = __shfl_sync(0xffffffffu, (threadIdx.x >> 5) & 3, 0), lane = threadIdx.x & 31;
    auto tile_col = [](int t, int h, int j) { return t < 9 ? j * 576 + t * 64 : (t == 9 && h) ? 512 : ((j + ((h ? 0x05760 : 0x04123) >> (4 * (t - 9)))) & 7) * 64; };
    auto prefetch_tile = [&](int t) {
#pragma unroll 1
      for (int b = rb; b < 18; b += 16) {
        const int h = b & 1, k = b >> 1;
        if (t < 9) w_tma_prefetch(h ? &map_wu : &map_wg, tile_col(t, h, j), k * 64);
        else if (t != 13 || !h) w_tma_prefetch(&map_wd, tile_col(t, h, j), j * 576 + k * 64);
      }
    };
    if (pw == 0) {
      {
        flag_wait(&flags[j * 8], (lds32(SM_EPOCH) + 1) * 16);
        TSP(7);
        asm volatile("fence.proxy.async.global;" ::: "memory");
        const uint8_t* wp = P.scr + OFF_WPACK + j * 24 * PSLOT;
        wp += rank * (PSLOT / 2);
        auto packed = [&](int sl, uint32_t par, int f) {
          mbar_wait(bar_empty(0) + sl * 8, par);
          w_bulk_load_mc(own + SB + rank * (PSLOT / 2) + sl * SLOT, wp + f * PSLOT, PSLOT / 2, own + bar_full(0) + sl * 8);
          w_expect_tx(own + bar_full(0) + sl * 8, PSLOT);
        };
        const uint32_t half = own + SB + rank * 8192;
#pragma unroll 1
        for (int L = 0; L < 2; L++) {
#pragma unroll 1
          for (int s = L ? 0 : -3; s < 21; s++) {
            if (s == 9 && L == 0) { flag_wait(&flags[(56 + j) * 8], (lds32(SM_EPOCH) + 1) * 16); asm volatile("fence.proxy.async.global;" ::: "memory"); }
            packed(s < 0 ? s + 12 : s < 9 ? s : s - 9, s < 0 || (s >= 9 && s < 18), s + 3);
          }
#pragma unroll 1
          for (int t = 0; t < 14; t++) {
            if (L * 14 + t + PF_AHEAD < 28) prefetch_tile((t + PF_AHEAD) % 14);
            const CUtensorMap* mp = t >= 9 ? &map_wd : rank ? &map_wu : &map_wg;
            const bool nar = t == 13;
            const int col = tile_col(t, nar ? 0 : rank, j);
            const uint32_t dst = nar ? own + SB : half, bytes = nar ? 8192 : SLOT;
            const int ra = t < 9 ? 0 : j * 576 + 320, rbs = t < 9 ? 0 : j * 576 - 192, rc = t < 9 ? 0 : j * 576;
#pragma unroll
            for (int k = 0; k < 9; k++) {
              mbar_wait(bar_empty(k), t & 1);
              if (!nar || rank == (k & 1)) w_tma_2d_mc(dst + k * SLOT, mp, col, (k < 3 ? ra : k < 8 ? rbs : rc) + k * 64, own + bar_full(k));
              w_expect_tx(own + bar_full(k), bytes);
            }
            if (t == 12 && L == 0) {
              w_l2_prefetch(P.scr + OFF_WPACK + j * 24 * PSLOT + rb * (24 * PSLOT / 16), 24 * PSLOT / 16);
#pragma unroll 1
              for (int s = 0; s < 3; s++) packed(9 + s, 1, s);
            }
          }
        }
        flags[(72 + cta) * 8] = lds32(SM_EPOCH) + 1;
      }
    } else if (pw < 3) {
      const int hw = pw - 1;
      const uint32_t ep = __shfl_sync(0xffffffffu, lds32(SM_EPOCH), 0);
      uint8_t* const sb = P.scr + (rb * 2 + hw) * STRM;
      const uint32_t xs = slot_addr(12) + hw * SLOT, fb = bar_full(12) + hw * 8;
      uint32_t hph = 0;
#pragma unroll 1
      for (int L = 0; L < 2; L++) {
        const uint32_t tag = ep * 2 + L + 1;
        bar_sync(NB_FREE + hw, 160);
        if (rb > 0) hint_wait(sb + OFF_HINT + 512 + j * 128, tag);
        uint32_t bad;
        do {
          if (rb > 0) {
            w_bulk_load(own + ytail(hw * 2), sb + OFF_HALO + (L * 8 + j) * 3072, 1536, own + bar_full(14) + hw * 128);
            w_bulk_load(own + ytail(hw * 2 + 1), sb + OFF_HALO + (L * 8 + j) * 3072 + 1536, 1536, own + bar_full(14) + hw * 128);
            w_expect_tx(own + bar_full(14) + hw * 128, 3072);
            mbar_wait(bar_full(14) + hw * 128, hph);
            hph ^= 1;
          }
          bad = 0;
#pragma unroll 1
          for (int c = 0; c < 3; c++) {
            uint32_t u[4] = {tag, 0, 0, 0}, v[4] = {tag, 0, 0, 0};
            if (rb > 0) { lds128(u, ytail(hw * 2) + c * 512 + lane * 16); lds128(v, ytail(hw * 2 + 1) + c * 512 + lane * 16); }
            bad |= (u[0] ^ tag) | (v[0] ^ tag);
#pragma unroll
            for (int i = 0; i < 3; i++) { sts32(xs + KSTG + (c * 3 + i) * 128 + lane * 4, u[i + 1]); sts32(xs + (c * 3 + i) * 128 + lane * 4, v[i + 1]); }
          }
        } while (__any_sync(0xffffffffu, bad != 0));
        bar_arrive(NB_HALO + hw, 160);
#pragma unroll 1
        for (int p = 0; p < 4; p++) {
          if (L == 0 && p == 3) flag_wait(flags + (40 + rb) * 8, (ep + 1) * 8);
          bar_sync(NB_FREE + hw, 160);
          TSH(L * 12 + p * 3);
          hint_wait(sb + OFF_HINT + (lane & 3) * 128, (ep * 13 + L * 7 + p + 3) * 8);
          TSH(L * 12 + p * 3 + 1);
          w_bulk_load(own + xs, sb + OFF_P + j * PSRC + (p & 1) * 16384, p ? 16384 : 8192, own + fb);
          if (p == 0) w_bulk_load(own + xs + 8192, sb + OFF_P + j * PSRC + 32768, 7168, own + fb);
          w_expect_tx(own + fb, p ? 16384 : 15360);
          TSH(L * 12 + p * 3 + 2);
        }
      }
    } else {
      auto clear = [&](int t) {
        const uint32_t so = rb * 2 * STRM + (threadIdx.x & 31) * 16;
#pragma unroll 1
        for (int i = 0; i < 18; i++) {
          st16(P.scr, so + t * TILE + j * 9216 + i * 512, 0, 0, 0, 0, 0);
          st16(P.scr, so + t * TILE + j * 9216 + i * 512, STRM, 0, 0, 0, 0);
          __nanosleep(0);
        }
        if (t != 1) {
          st16(P.scr, so + (t ? t - 1 : 0) * 4096 + j * 512, OFF_ST, 0, 0, 0, 0);
          st16(P.scr, so + (t ? t - 1 : 0) * 4096 + j * 512, OFF_ST + STRM, 0, 0, 0, 0);
        }
      };
      bar_sync(NB_PUB + 3, 384);
      if (lane == 0) flag_signal(&flags[j * 8]);
      TSP(5);
      bar_sync(NB_PUB + 2, 288);
      if (lane == 0) flag_signal(&flags[(56 + j) * 8]);
      TSP(4);
      __syncwarp();
#pragma unroll 1
      for (int t = 0; t < PF_AHEAD; t++) prefetch_tile(t);
#pragma unroll 1
      for (int L = 0; L < 2; L++) {
        timed_wait(bar_empty(13), L);
#pragma unroll 1
        for (int t = L ^ 1; t < 4 - 2 * L; t++) clear(t);
        __syncwarp();
        if (lane == 0 && L == 0) flag_signal(flags + (40 + rb) * 8);
      }
      timed_wait(bar_empty(12), 0);
      asm volatile("barrier.cluster.arrive.relaxed.aligned;\nbarrier.cluster.wait.aligned;" ::: "memory");
    }
  } else {
    asm volatile("setmaxnreg.inc.sync.aligned.u32 240;");
    const int w = __shfl_sync(0xffffffffu, (threadIdx.x >> 5) & 3, 0);
    Rel rel{(threadIdx.x & 95) == 0, cta_window(w & 1), 0};
    uint8_t* const sb = P.scr + (rb * 2 + wg) * STRM;
    uint8_t* const hint = sb + OFF_HINT + w * 128;
    auto hint_target = [](int e) { return (lds32(SM_EPOCH) * 13 + e + 1) * 8; };
    TS(0);
    uint32_t a[144];
#pragma unroll 1
    for (int L = 0; L < 2; L++) {
      uint32_t m0, m1; float r0, r1;
      rel.tr = win() + ytail(3) + 1536 + (L == TRACE - 1 && w == 1 ? wg * 384 : 768);
      if (L == 0) {
        Stats st;
        const int lane = tid_() & 31, g = lane >> 2;
        const int row = w * 16 + (lane & 15);
        const uint32_t ra = SB + wg * 8192 + row * 128;
        const uint32_t pt = tid_(), pu = (pt % 36) >> 2, pk = rb * 36 + (pt < 108 ? pt / 36 : 0) * 4 + (pt & 3);
        uint4 pv[3];
#pragma unroll
        for (int i = 0; i < 3; i++) pv[i] = ldg_line(wg ? wo_src(P.wo, pk + i * 12, pu, j) : P.wqkv + (pk + i * 12) * 1728 + j * 72 + pu * 8);
#pragma unroll
        for (int c = 0; c < 9; c++) {
          mbar_wait(bar_full(c), 0);
          if (c == 0) TS(60); if (c == 8) TS(62);
#pragma unroll
          for (int kk = 0; kk < 4; kk++) ldsm4(&a[c * 16 + kk * 4], ra + (((kk * 2 + (lane >> 4)) ^ (row & 7)) << 4) + c * SLOT);
          if (c == 8) {
            uint32_t y[18], z[4];
#pragma unroll
            for (int i = 0; i < 4; i++) ldsm4(&y[4 * i], ra + (((i * 2 + (lane >> 4)) ^ (row & 7)) << 4) + j * SLOT);
            ldsm4(z, ra + ((j ^ (row & 7)) << 4) + 8 * SLOT);
            y[16] = z[0]; y[17] = z[1];
            bar_sync(NB_WG + wg, 128);
#pragma unroll
            for (int i = 0; i < 9; i++) rel(i);
            if (pt < 108) {
#pragma unroll
              for (int i = 0; i < 3; i++) {
                const uint32_t k = pk + i * 12;
                st16(P.scr, (j * 24 + wg * 6 + k / 96) * PSLOT + pu * 1536 + (k % 96) * 16, OFF_WPACK + 12 * PSLOT, pv[i].x, pv[i].y, pv[i].z, pv[i].w);
              }
            }
            asm volatile("fence.proxy.async.global;" ::: "memory");
            bar_arrive(NB_PUB + 2, 288);
            store_own(y, sb, OFF_X2, j, tid_());
          }
#pragma unroll
          for (int kk = 0; kk < 4; kk++) st.add16(&a[c * 16 + kk * 4]);
        }
        const int dl = (lane & ~3) | (g >> 1);
        ln_scalars(st.s[0], __shfl_sync(0xffffffffu, st.sq0(g), dl), m0, r0, P.zero);
        ln_scalars(st.s[2], __shfl_sync(0xffffffffu, st.sq1(g), dl), m1, r1, P.zero);
      } else {
#pragma unroll
        for (int i = 4 * N_UP; i < 144; i++) a[i] = 0;
        hint_wait(hint, hint_target(6));
        TS(61);
        gather_ln<3 * D_KV>(a, sb, OFF_X2, 8192, m0, m1, r0, r1, P.zero);
      }
      TS(1 + L * 20);
      uint32_t kf[18], qf[18];
      {
        float acc[72];
        if (wg == 1) bar_sync(NB_ORD1, 256);
        mma_pass<144, PS_KV, 3, 256, D_KV, true>(acc, a, DESC_KV, 1, rel, wg == 0 ? NB_ORD1 : -1, sb, OFF_X2, L ^ 1, m0, m1, ytail(wg * 2));
        r0 = ln_rstd(r0, acc[0], P.zero); r1 = ln_rstd(r1, acc[0], P.zero);
        uint32_t vf[18];
#pragma unroll
        for (int c = 0; c < 9; c++) {
          kf[c] = pack_bf16(acc[4 * c] * r0, acc[4 * c + 1] * r0);
          kf[9 + c] = pack_bf16(acc[4 * c + 2] * r1, acc[4 * c + 3] * r1);
          vf[c] = pack_bf16(acc[36 + 4 * c] * r0, acc[36 + 4 * c + 1] * r0);
          vf[9 + c] = pack_bf16(acc[36 + 4 * c + 2] * r1, acc[36 + 4 * c + 3] * r1);
        }
        TS(2 + L * 20);
        const uint32_t l16 = (tid_() & 31) * 16, xs = slot_addr(12) + wg * SLOT + w * 1152;
#pragma unroll
        for (int i = 0; i < 4; i++) stsm4(xs + w * 1152 + 1152 + i * 512 + l16, vf[4 * i], vf[4 * i + 1], vf[4 * i + 2], vf[4 * i + 3]);
        sts32(xs + w * 1152 + 1152 + 2048 + l16 / 4, vf[16]); sts32(xs + w * 1152 + 1152 + 2176 + l16 / 4, vf[17]);
        if (w < 3) {
          stsm4(xs + KSTG + 1152 + l16, kf[9], kf[10], kf[11], kf[12]);
          stsm4(xs + KSTG + 1152 + 512 + l16, kf[13], kf[14], kf[15], kf[16]);
          sts32(xs + KSTG + 1152 + 1024 + l16 / 4, kf[17]);
        } else if (rb < 15) {
          const uint32_t tag = lds32(SM_EPOCH) * 2 + L + 1;
          const uint32_t ho = l16 + (L * 8 + j) * 3072;
#pragma unroll
          for (int c = 0; c < 3; c++) {
            st16(sb, ho, 2 * STRM + OFF_HALO + c * 512, tag, kf[9 + 3 * c], kf[10 + 3 * c], kf[11 + 3 * c]);
            st16(sb, ho, 2 * STRM + OFF_HALO + 1536 + c * 512, tag, vf[9 + 3 * c], vf[10 + 3 * c], vf[11 + 3 * c]);
          }
          hint_post(sb + 2 * STRM + OFF_HINT + 512 + j * 128);
        }
      }
      lds128(a, ytail(wg * 2) + tid_() * 16);
      bar_arrive(NB_FREE + wg, 160);
      uint32_t kh[12], vp[20], v1[12];
      {
        float acc[36];
        if (wg == 1) bar_sync(NB_ORD1, 256);
        mma_pass<72, PS_Q, 6, 256, 0, false, false>(acc, a, DESC_Q, 0, rel, -1, nullptr, 0, 0, 0, 0, 0, [&]() {
          bar_sync(NB_HALO + wg, 160);
#pragma unroll
          for (int i = 0; i < 3; i++) ldsm4(&kh[4 * i], slot_addr(12) + wg * SLOT + w * 640 + tid_() * 16 + KSTG + i * 512);
          const uint32_t l = tid_() & 31, vb = slot_addr(12) + wg * SLOT + w * 2304;
#pragma unroll
          for (int i = 0; i < 5; i++) ldsm4t(&vp[4 * i], vb + (l & 8) * 144 + (l & 16) * 8 + (l & 7) * 16 + i * 256);
#pragma unroll
          for (int i = 0; i < 3; i++) ldsm4t(&v1[4 * i], vb + 2304 + l * 16 + i * 512);
        });
#pragma unroll
        for (int i = 0; i < 18; i++) qf[i] = pack_bf16(acc[2 * i], acc[2 * i + 1]);
      }
      TS(3 + L * 20);
      uint32_t xr[18];
      {
        const int tid = tid_(), g = (tid >> 2) & 7, q = tid & 3;
        const bool nohalo = (rb == 0 && w == 0);
        const bool le0 = 2 * q <= g, le1 = 2 * q + 1 <= g;
        const uint32_t M = (le0 ? 0xffffu : 0u) | (le1 ? 0xffff0000u : 0u);
        const float sc0 = r0 * (0.23570226039551584f * 1.4426950408889634f), sc1 = r1 * (0.23570226039551584f * 1.4426950408889634f);
        float l[16], t[8];
#pragma unroll
        for (int h = 0; h < 4; h++) {
          const uint32_t qa0 = q >= h ? qf[4 * h] : 0u, qa1 = q >= h ? qf[4 * h + 1] : 0u;
          const uint32_t qc0 = q <= h ? qf[4 * h + 4] : 0u, qc1 = q <= h ? qf[4 * h + 5] : 0u;
          float sm[4] = {0, 0, 0, 0}, s0[4] = {0, 0, 0, 0}, s1[4] = {0, 0, 0, 0};
          mma16816(s0, qa0, qa1, qf[4 * h + 2], qf[4 * h + 3], kf[2 * h], kf[2 * h + 1]);
          mma16816(s1, qa0, qa1, qf[4 * h + 2], qf[4 * h + 3], kf[9 + 2 * h], kf[10 + 2 * h]);
          mma16816(sm, qa0, qa1, qf[4 * h + 2], qf[4 * h + 3], kh[2 * h], kh[2 * h + 1]);
          mma1688(s0, qc0, qc1, kf[2 * h + 2]);
          mma1688(s1, qc0, qc1, kf[11 + 2 * h]);
          mma1688(sm, qc0, qc1, kh[2 * h + 2]);
          if (nohalo) sm[0] = sm[1] = -3e38f;
          l[4 * h] = le0 ? s0[0] : sm[0]; l[4 * h + 1] = le1 ? s0[1] : sm[1];
          l[4 * h + 2] = le0 ? s1[2] : s0[2]; l[4 * h + 3] = le1 ? s1[3] : s0[3];
        }
#pragma unroll
        for (int i = 0; i < 8; i++) t[i] = fmaxf(l[2 * i], l[2 * i + 1]);
        TS(14 + L * 20);
#pragma unroll
        for (int i = 0; i < 8; i++) t[i] = fmaxf(t[i], __shfl_xor_sync(0xffffffffu, t[i], 1));
#pragma unroll
        for (int i = 0; i < 8; i++) t[i] = fmaxf(t[i], __shfl_xor_sync(0xffffffffu, t[i], 2)) * ((i & 1) ? sc1 : sc0);
#pragma unroll
        for (int i = 0; i < 8; i++) {
          const float sc = (i & 1) ? sc1 : sc0;
          l[2 * i] = ex2(fmaf(l[2 * i], sc, -t[i])); l[2 * i + 1] = ex2(fmaf(l[2 * i + 1], sc, -t[i])); t[i] = l[2 * i] + l[2 * i + 1];
        }
#pragma unroll
        for (int i = 0; i < 8; i++) t[i] += __shfl_xor_sync(0xffffffffu, t[i], 1);
#pragma unroll
        for (int i = 0; i < 8; i++) t[i] += __shfl_xor_sync(0xffffffffu, t[i], 2);
        uint32_t pf[16], pz[8];
#pragma unroll
        for (int i = 0; i < 8; i++) {
          float r; asm("rcp.approx.ftz.f32 %0, %1;" : "=f"(r) : "f"(t[i]));
          const uint32_t p = pack_bf16(l[2 * i] * r, l[2 * i + 1] * r);
          pf[2 * i] = p & ~M; pf[2 * i + 1] = p & M; pz[i] = p & P.zero;
        }
#pragma unroll
        for (int c = 0; c < 9; c++) {
          const int h = c == 8 ? 3 : c >> 1;
          float o[4] = {0, 0, 0, 0};
          mma16816(o, pf[4 * h], pz[2 * h], pf[4 * h + 1], pf[4 * h + 2], vp[2 * c], vp[2 * c + 1]);
          mma1688(o, pz[2 * h + 1], pf[4 * h + 3], v1[c]);
          if (c == 2 || c == 4 || c == 6) {
            float e[4] = {0, 0, 0, 0};
            mma16816(e, pf[4 * h - 4], pz[2 * h - 2], pf[4 * h - 3], pf[4 * h - 2], vp[2 * c], vp[2 * c + 1]);
            mma1688(e, pz[2 * h - 1], pf[4 * h - 1], v1[c]);
            const uint32_t u = pack_bf16(e[0], e[1]), v = pack_bf16(e[2], e[3]);
            qf[2 * c] = q < h ? u : pack_bf16(o[0], o[1]); qf[2 * c + 1] = q < h ? v : pack_bf16(o[2], o[3]);
          } else {
            qf[2 * c] = pack_bf16(o[0], o[1]); qf[2 * c + 1] = pack_bf16(o[2], o[3]);
          }
        }
        {
          uint32_t x = 0;
#pragma unroll
          for (int i = 0; i < 18; i += 2) x |= qf[i];
          bar_arrive(NB_ORD1 - wg + (x & P.zero), 256);
        }
        store_own(qf, sb, OFF_O, j, tid);
        hint_post(hint);
        load_own(xr, sb, OFF_X2, j);
      }
      TS(4 + L * 20);
      {
        hint_wait(hint, hint_target(L * 7));
        TS(5 + L * 20);
        load_frags<N_WO>(a, sb, OFF_O, tid_());
        float acc[36];
        if (wg == 0) bar_sync(NB_ORD0, 256);
        load_frags<N_UP, N_WO>(a, sb, OFF_O, tid_());
        TS(19 + L * 20);
        mma_pass<72, PS_WO, 6, 256, D_WO, false>(acc, a, DESC_Q, 0, rel, -1, sb, OFF_O);
        TS(6 + L * 20);
#pragma unroll
        for (int c = 0; c < 9; c++) {
          xr[2 * c] = bf2_add(xr[2 * c], pack_bf16(acc[4 * c], acc[4 * c + 1]));
          xr[2 * c + 1] = bf2_add(xr[2 * c + 1], pack_bf16(acc[4 * c + 2], acc[4 * c + 3]));
        }
        store_own(xr, sb, L * 3 * TILE, j, tid_());
        RowStats rs;
        rs.add<18>(xr);
        rs.store(sb, L * 4096 + j * 128, tid_());
        hint_post(hint);
      }
      TS(16 + L * 20);
      hint_wait(hint, hint_target(L * 7 + 1));
      TS(15 + L * 20);
      gather_ln<4 * D_T0>(a, sb, L * 3 * TILE, L * 4096, m0, m1, r0, r1, P.zero);
      TS(7 + L * 20);
      const uint32_t hb = OFF_H + j * 24576;
      {
        float ka0, kb0, kc0, ka1, kb1, kc1;
        float acc[64];
        uint32_t hf[16];
        auto geglu = [&](auto chains, uint32_t hsm) {
          constexpr int CH = decltype(chains)::value & 15;
          float r[32];
#pragma unroll
          for (int e = 0; e < 32; e++) {
            float x = acc[e];
            if (e >= CH) x = __uint_as_float(__float_as_uint(x) ^ (__float_as_uint(r[e - CH]) & P.zero));
            if (decltype(chains)::value > 15 && e < 20) {
              const uint32_t ad = (e < 8 ? slot_addr(12) + e * 2048 + wg * 8192 : slot_addr(7 + (e >> 2)) + (e & 3) * 2048) + hsm;
              lds128(&a[48 + 4 * e], e >= CH ? ad ^ (__float_as_uint(r[e - CH]) & P.zero) : ad);
            }
            const bool hi = e & 2;
            float t = x * fmaf(x * x, hi ? kb1 : kb0, hi ? ka1 : ka0);
            asm("tanh.approx.f32 %0, %0;" : "+f"(t));
            const float u = x * acc[32 + e] * (hi ? kc1 : kc0);
            r[e] = fmaf(u, t, u);
            if (e & 1) hf[e >> 1] = pack_bf16(r[e - 1], r[e]);
          }
        };
        if (wg == 1) bar_sync(NB_ORD1, 256);
        mma_pass<128, PS_FF, 4, 2048, D_T0, true>(acc, a, DESC_SW128, 1, rel, NB_ORD1 - wg, sb, L * 3 * TILE, 0, m0, m1);
        if (tid_() == 0) mbar_arrive(bar_empty(13));
        TS(8 + L * 20);
        r0 = ln_rstd(r0, acc[0], P.zero); r1 = ln_rstd(r1, acc[0], P.zero);
        ka0 = 0.7978845608028654f * r0; kb0 = 0.035677408136300125f * r0 * r0 * r0; kc0 = 0.5f * r0 * r0;
        ka1 = 0.7978845608028654f * r1; kb1 = 0.035677408136300125f * r1 * r1 * r1; kc1 = 0.5f * r1 * r1;
#pragma unroll 1
        for (int t = 0; t < 8; t++) {
          geglu(IntC<2>(), 0);
          const uint32_t t16 = tid_() * 16;
          if (t < 5) {
            const uint32_t d = (t < 2 ? slot_addr(12) + wg * SLOT + t * 8192 : slot_addr(7) + t * SLOT + wg * 8192) + t16;
#pragma unroll
            for (int i = 0; i < 4; i++)
              sts128(d + i * 2048, hf[4 * i], hf[4 * i + 1], hf[4 * i + 2], hf[4 * i + 3]);
            if (t == 4) asm volatile("fence.proxy.async.shared::cta;" ::: "memory");
          } else {
#pragma unroll
            for (int i = 0; i < 4; i++) st16(sb, hb + (t - 5) * 8192 + t16, i * 2048, hf[4 * i], hf[4 * i + 1], hf[4 * i + 2], hf[4 * i + 3]);
          }
          bar_sync(NB_ORD0 + wg, 256);
          mma_pass<128, PS_FF, 4, 2048, 0, false, true>(acc, a, DESC_SW128, t & 1, rel, NB_ORD1 - wg, sb, hb + t16, t == 7);
        }
        TS(9 + L * 20);
        const uint32_t hsm = wg * 8192 + tid_() * 16;
        geglu(IntC<16 + CH_LAST>(), hsm);
#pragma unroll
        for (int i = 0; i < 16; i++) a[128 + i] = hf[i];
      }
      TS(10 + L * 20);
      {
        const uint32_t xs = slot_addr(12) + wg * SLOT;
        auto verify = [&](int p, uint32_t t16) {
          mbar_wait(bar_full(12) + wg * 8, p & 1);
          TS(71 + L * 32 + p * 5);
          const uint32_t ta = p < 2, tb = (p & 1) ? ta : L ^ 1, nb = p ? 4 : 7, sh = p == 0;
          uint32_t m = 0;
#pragma unroll
          for (int s = 0; s < 4; s++) m |= (lds32(xs + s * 2048 + t16) ^ ta) | (lds32(xs + 8192 + ((s * 2048 + t16) >> sh)) ^ tb);
          if (p == 0) {
#pragma unroll
            for (int s = 4; s < 7; s++) m |= lds32(xs + 8192 + s * 1024 + t16 / 2) ^ tb;
          }
          if (__any_sync(0xffffffffu, m & 1)) {
#pragma unroll 1
            for (int s = 0; s < 4 + nb; s++) {
              const bool nar = sh && s >= 4;
              const uint32_t o = nar ? 4096 + s * 1024 + t16 / 2 : s * 2048 + t16;
              uint32_t v[4] = {0, 0, 0, 0};
              do {
                if (nar) ld8(v, sb, j * PSRC + o, OFF_P + 32768 - 8192);
                else ld16(v, sb, j * PSRC + (p & 1) * 16384 + o, OFF_P);
              } while (__any_sync(0xffffffffu, (v[0] ^ (s < 4 ? ta : tb)) & 1));
              sts64(xs + o, v[0], v[1]);
              if (!nar) sts64(xs + o + 8, v[2], v[3]);
            }
            asm volatile("fence.proxy.async.shared::cta;" ::: "memory");
          }
        };
        uint32_t t16 = (a[142] | a[143]) & P.zero;
#pragma unroll 1
        for (int p = 0; p < 4; p++) {
          float acc[64];
          bar_sync(NB_ORD0 + wg + (p ? 0 : t16), 256);
          TS(64 + L * 32 + p * 5);
          if (p == 0) { rel(9); rel(10); rel(11); }
          mma_pass<128, PS_FF, 4, 2048, 0, false, false>(acc, a, DESC_SW128, p & 1, rel, NB_ORD1 - wg, nullptr, 0, 0, 0, 0, 0, [&]() {
            t16 = tid_() * 16;
            if (p) verify(p - 1, t16);
          });
          TS(65 + L * 32 + p * 5);
          if (p == 1 || p == 2) add_piece<false>(acc, xs + t16);
          const uint32_t oa = ((j + (p < 3 ? 1 : 4)) & 7) * PSRC + (p & 1) * 16384 + t16;
#pragma unroll
          for (int i = 0; i < 4; i++)
            st16(sb, oa, OFF_P + i * 2048, (pack_bf16(acc[8 * i], acc[8 * i + 1]) & ~1u) | (p < 2), pack_bf16(acc[8 * i + 2], acc[8 * i + 3]),
                 pack_bf16(acc[8 * i + 4], acc[8 * i + 5]), pack_bf16(acc[8 * i + 6], acc[8 * i + 7]));
          if (p == 0) {
#pragma unroll
            for (int i = 0; i < 8; i++)
              send8(sb, j * 1024 + t16 / 2, OFF_P + 32768 + i * PSRC, xs + 15360 + t16 / 2, i, j,
                    (pack_bf16(acc[32 + 4 * i], acc[33 + 4 * i]) & ~1u) | (L ^ 1), pack_bf16(acc[34 + 4 * i], acc[35 + 4 * i]));
          } else {
            if (p == 2) add_piece<false>(acc + 32, xs + 8192 + t16);
            const uint32_t ob = ((j + (p < 3 ? 7 : 5)) & 7) * PSRC + (p & 1) * 16384 + t16, tb = p == 2 ? L ^ 1 : p < 2;
#pragma unroll
            for (int i = 4; i < 8; i++)
              st16(sb, ob, OFF_P + i * 2048, (pack_bf16(acc[8 * i], acc[8 * i + 1]) & ~1u) | tb, pack_bf16(acc[8 * i + 2], acc[8 * i + 3]),
                   pack_bf16(acc[8 * i + 4], acc[8 * i + 5]), pack_bf16(acc[8 * i + 6], acc[8 * i + 7]));
          }
          hint_post(hint);
          TS(68 + L * 32 + p * 5);
          if (p == 1) {
            float s0 = 0.f, s1 = 0.f, s2 = 0.f, s3 = 0.f;
#pragma unroll
            for (int s = 0; s < 8; s++) {
              uint32_t u, v;
              lds64(u, v, xs + 8192 + s * 1024 + t16 / 2);
              s0 += bf_lo(u); s1 += bf_hi(u); s2 += bf_lo(v); s3 += bf_hi(v);
            }
            sts64(ytail(wg * 2) + t16, pack_bf16(s0, s1), pack_bf16(s2, s3));
          }
          if (p < 3) bar_arrive(NB_FREE + wg, 160);
          TS(67 + L * 32 + p * 5);
        }
        float acc[32];
        add_piece<true>(acc, xs + t16);
        add_piece<false>(acc, xs + 8192 + t16);
        bar_arrive(NB_FREE + wg, 160);
        load_own(xr, sb, L * 3 * TILE, j);
        bar_sync(NB_ORD0 + wg, 256);
        TS(84 + L * 32);
        uint32_t t, yn[2];
        mma_pass<64, PS_FFA, 4, 2048, 0, false, false>(acc, a, DESC_SW128, 0, rel, wg ? -1 : NB_ORD1, nullptr, 0, 0, 0, 0, 0, [&]() {
          t = tid_();
          lds64(yn[0], yn[1], ytail(wg * 2) + t * 16);
          mbar_wait(bar_full(12) + wg * 8, 1);
#pragma unroll
          for (int i = 0; i < 8; i++) lds128(&a[4 * i], xs + i * 2048 + t * 16);
        });
        TS(11 + L * 20);
        while (true) {
          uint32_t m = 0;
#pragma unroll
          for (int i = 0; i < 8; i++) m |= a[4 * i];
          if (!__any_sync(0xffffffffu, m & 1)) break;
#pragma unroll
          for (int i = 0; i < 8; i++) ld16(&a[4 * i], sb, j * PSRC + t * 16, OFF_P + 16384 + i * 2048);
        }
        TS(12 + L * 20);
#pragma unroll
        for (int i = 0; i < 18; i++)
          xr[i] = bf2_add(xr[i], i < 16 ? pack_bf16(acc[2 * i] + (bf_lo(a[i]) + bf_lo(a[16 + i])), acc[2 * i + 1] + (bf_hi(a[i]) + bf_hi(a[16 + i]))) : yn[i - 16]);
        TS(18 + L * 20);
        if (L == 0) {
          store_own(xr, sb, OFF_X2, j, t);
          RowStats rs;
          rs.add<18>(xr);
          rs.store(sb, 8192 + j * 128, t);
          hint_post(hint);
        } else {
          const uint32_t l = t & 31, wb = xs + w * 512;
          if (l == 0) mbar_arrive(bar_empty(12));
          __syncwarp();
          asm volatile("barrier.cluster.arrive.relaxed.aligned;" ::: "memory");
#pragma unroll
          for (int i = 0; i < 4; i++) stsm4(wb + i * 2048 + (l & 24) * 16 + (((l & 7) ^ (i * 2 + (l >> 4))) << 4), xr[4 * i], xr[4 * i + 1], xr[4 * i + 2], xr[4 * i + 3]);
          stsm4(wb + 8192 + l * 16, xr[16], xr[17], 0, 0);
          __syncwarp();
          uint8_t* op = (uint8_t*)P.out + row_off(rb, wg, w * 32 + (l >> 3)) + j * 128 + (l & 7) * 16;
#pragma unroll
          for (int i = 0; i < 4; i++) {
            uint32_t r[4];
            lds128(r, wb + ((l & 6) << 10) + ((l & 1) * 2 + (i >> 1)) * 128 + (((((i & 1) * 4 + (l >> 3)) ^ l) & 7) << 4));
            *(uint4*)(op + i * 16 * DM) = make_uint4(r[0], r[1], r[2], r[3]);
          }
          uint32_t r[4];
          lds128(r, wb + 8192 + l * 16);
          if (l < 16) *(uint4*)((uint8_t*)P.out + row_off(rb, wg, t) + 1024 + j * 16) = make_uint4(r[0], r[1], r[2], r[3]);
        }
      }
      TS(13 + L * 20);
    }
  }
}

typedef CUresult (*EncodeFn)(CUtensorMap*, CUtensorMapDataType, cuuint32_t, void*, const cuuint64_t*, const cuuint64_t*, const cuuint32_t*,
                             const cuuint32_t*, CUtensorMapInterleave, CUtensorMapSwizzle, CUtensorMapL2promotion, CUtensorMapFloatOOBfill);

void encode(EncodeFn fn, CUtensorMap* m, const void* p, int rank, const cuuint64_t* dims, const cuuint64_t* str, const cuuint32_t* box) {
  const cuuint32_t es[3] = {1, 1, 1};
  fn(m, CU_TENSOR_MAP_DATA_TYPE_BFLOAT16, rank, const_cast<void*>(p), dims, str, box, es, CU_TENSOR_MAP_INTERLEAVE_NONE,
     CU_TENSOR_MAP_SWIZZLE_128B, CU_TENSOR_MAP_L2_PROMOTION_L2_256B, CU_TENSOR_MAP_FLOAT_OOB_FILL_NONE);
}

__global__ void probe_kernel() {}

void make_roles(uint8_t* role) {
  int cnt[8];
  cudaFuncSetAttribute(probe_kernel, cudaFuncAttributeMaxDynamicSharedMemorySize, SMEM_BYTES);
  cudaFuncSetAttribute(probe_kernel, cudaFuncAttributeNonPortableClusterSizeAllowed, 1);
  for (int r = 7; r >= 0; r--) {
    int n = 0;
    cudaLaunchConfig_t cfg = {};
    cudaLaunchAttribute at;
    at.id = cudaLaunchAttributeClusterDimension; at.val.clusterDim.x = 2 * (r < 3 ? 4 : r + 1); at.val.clusterDim.y = at.val.clusterDim.z = 1;
    cfg.gridDim = dim3(at.val.clusterDim.x); cfg.blockDim = dim3(384); cfg.dynamicSmemBytes = SMEM_BYTES; cfg.attrs = &at; cfg.numAttrs = 1;
    if (cudaOccupancyMaxActiveClusters(&n, probe_kernel, &cfg) != cudaSuccess) { cudaGetLastError(); n = r > 3 ? 8 : 8 + cnt[7]; }
    cnt[r] = r > 3 ? n : n - cnt[7];
  }
  int key[64], c = 0, total = 0, seg = 0;
  for (int r = 0; r < 8; r++) total += cnt[r];
  for (; c < 64 - total; c++) key[c] = -1;
  for (int r = 0; r < 8; r++) {
    if (r && cnt[r] != cnt[r - 1]) seg++;
    for (int i = 0; i < cnt[r] && c < 64; i++) key[c++] = seg * 16 + i;
  }
  int order[64], n = 0;
  bool used[64] = {};
  for (int pass = 0; pass < 2; pass++)
    for (int i = 0; i < 64; i++) {
      if (used[i]) continue;
      int m[4], k = 0;
      for (int q = i; q < 64 && k < 4; q++) if (!used[q] && (pass || (key[q] == key[i] && key[i] >= 0))) m[k++] = q;
      if (k == 4) for (int q = 0; q < 4; q++) { used[m[q]] = true; order[n++] = m[q]; }
    }
  for (int i = 0; i < 64; i++) role[order[i]] = (uint8_t)(((i >> 2) & 7) << 3 | (i >> 5) << 2 | (i & 3));
}

}

extern "C" void kernel_launch(void* const* d_in, const int* in_sizes, int n_in, void* d_out, int out_size) {
  (void)in_sizes; (void)n_in; (void)out_size;
  Params P = {};
  P.wqkv = (const __nv_bfloat16*)d_in[1]; P.wo = (const __nv_bfloat16*)d_in[2];
  P.out = (__nv_bfloat16*)d_out; P.zero = 0;
  cudaGetSymbolAddress((void**)&P.scr, g_scr);
  make_roles(P.role);
  void* fnp = nullptr; cudaDriverEntryPointQueryResult qr;
  cudaGetDriverEntryPoint("cuTensorMapEncodeTiled", &fnp, cudaEnableDefault, &qr);
  EncodeFn fn = (EncodeFn)fnp;
  CUtensorMap mx, mg, mu, md;
  { const cuuint64_t dims[3] = {DM, SEQ / 2, 2}, str[2] = {DM * 4, DM * 2}; const cuuint32_t box[3] = {64, 64, 2}; encode(fn, &mx, d_in[0], 3, dims, str, box); }
  { const cuuint64_t dims[2] = {DFF, DM}, str[1] = {DFF * 2}; const cuuint32_t box[2] = {64, 64}; encode(fn, &mg, d_in[4], 2, dims, str, box); encode(fn, &mu, d_in[5], 2, dims, str, box); }
  { const cuuint64_t dims[2] = {DM, DFF}, str[1] = {DM * 2}; const cuuint32_t box[2] = {64, 64}; encode(fn, &md, d_in[6], 2, dims, str, box); }
  cudaFuncSetAttribute(fused_kernel, cudaFuncAttributeMaxDynamicSharedMemorySize, SMEM_BYTES);
  fused_kernel<<<128, 384, SMEM_BYTES, cudaStreamPerThread>>>(P, mx, mg, mu, md);
}
```

```cpp
#include <cuda_runtime.h>
#include <cuda_bf16.h>
#include <cuda.h>
#include <stdint.h>

#define TIMING 0
#define KV_S1 4
#define TRACE 0

namespace {

constexpr int SEQ = 2048, DM = 576, DFF = 4608;
constexpr int KV_LEAD = 5;
constexpr int D_KV = 6, D_WO = 3, D_T0 = 5;
constexpr int N_UP = 26, N_WO = 12;
constexpr int PF_AHEAD = 2;
constexpr int CH_LAST = 3;
constexpr uint32_t SB = 1024;
constexpr uint32_t SLOT = 16384;
constexpr uint32_t PSLOT = 13824;
constexpr uint32_t BARS = SB + 14 * SLOT;
constexpr int SMEM_BYTES = 14 * SLOT + 256 + 2560 + (TRACE ? 256 : 0);
__host__ __device__ constexpr uint32_t slot_addr(int s) { return SB + s * SLOT; }
__host__ __device__ constexpr uint32_t bar_full(int s) { return BARS + 8 * s; }
__host__ __device__ constexpr uint32_t bar_empty(int s) { return BARS + 128 + 8 * s; }
enum { NB_ORD0 = 1, NB_ORD1 = 2, NB_WG = 3  , NB_HALO = 5  , NB_FREE = 7  , NB_PUB = 9   };
constexpr uint32_t SM_EPOCH = BARS + 120;
__host__ __device__ constexpr uint32_t ytail(uint32_t k) { return k < 3 ? slot_addr(9) + PSLOT + k * SLOT : BARS + 256; }
constexpr uint32_t KSTG = 9 * 1152;

constexpr uint32_t TILE = 36 * 2048;
constexpr uint32_t OFF_X1 = 0  , OFF_O = TILE, OFF_X2 = 2 * TILE, OFF_ST = 4 * TILE  ;
constexpr uint32_t PSRC = 2 * 16384 + 7 * 1024;
constexpr uint32_t OFF_P = OFF_ST + 3 * 4096, OFF_HALO = OFF_P + 8 * PSRC  , OFF_HINT = OFF_HALO + 2 * 8 * 3072  ,
                   OFF_H = OFF_HINT + 16 * 128  , STRM = OFF_H + 8 * 24576;
constexpr uint32_t OFF_WPACK = 32 * STRM, OFF_FLAGS = OFF_WPACK + 8 * 24 * PSLOT;
__device__ __align__(1024) uint8_t g_scr[OFF_FLAGS + (8 + 64 + 128) * 32];

__device__ __forceinline__ uint32_t smem_u32(const void* p) { return (uint32_t)__cvta_generic_to_shared(p); }
extern __shared__ __align__(1024) uint8_t smem_raw[];
__device__ __forceinline__ uint32_t win() { return (blockIdx.x & 1) << 24; }
#define SA(A, W) ".reg .u32 sa;\nadd.u32 sa, " A ", " W ";\n"
__device__ __forceinline__ void mbar_init(uint32_t bar, uint32_t cnt) { asm volatile("{\n" SA("%0", "%2") "mbarrier.init.shared::cta.b64 [sa], %1;\n}" ::"r"(bar), "r"(cnt), "r"(win())); }
__device__ __forceinline__ void mbar_expect_tx(uint32_t bar, uint32_t bytes) { asm volatile("{\n" SA("%0", "%2") "mbarrier.arrive.expect_tx.shared::cta.b64 _, [sa], %1;\n}" ::"r"(bar), "r"(bytes), "r"(win()) : "memory"); }
__device__ __forceinline__ void mbar_arrive(uint32_t bar) { asm volatile("{\n" SA("%0", "%1") "mbarrier.arrive.shared::cta.b64 _, [sa];\n}" ::"r"(bar), "r"(win()) : "memory"); }
__device__ __forceinline__ uint32_t lds32(uint32_t a) { uint32_t v; asm volatile("{\n" SA("%1", "%2") "ld.shared.u32 %0, [sa];\n}" : "=r"(v) : "r"(a), "r"(win()) : "memory"); return v; }
__device__ __forceinline__ void lds64(uint32_t& x, uint32_t& y, uint32_t a) { asm volatile("{\n" SA("%2", "%3") "ld.shared.v2.u32 {%0,%1}, [sa];\n}" : "=r"(x), "=r"(y) : "r"(a), "r"(win()) : "memory"); }
__device__ __forceinline__ void lds128(uint32_t* v, uint32_t a) {
  asm volatile("{\n" SA("%4", "%5") "ld.shared.v4.u32 {%0,%1,%2,%3}, [sa];\n}" : "=r"(v[0]), "=r"(v[1]), "=r"(v[2]), "=r"(v[3]) : "r"(a), "r"(win()) : "memory");
}
__device__ __forceinline__ void stsm4(uint32_t a, uint32_t x, uint32_t y, uint32_t z, uint32_t w) {
  asm volatile("{\n" SA("%0", "%5") "stmatrix.sync.aligned.m8n8.x4.shared.b16 [sa], {%1,%2,%3,%4};\n}" ::"r"(a), "r"(x), "r"(y), "r"(z), "r"(w), "r"(win()) : "memory");
}
__device__ __forceinline__ void ldsm4(uint32_t* v, uint32_t a) {
  asm volatile("{\n" SA("%4", "%5") "ldmatrix.sync.aligned.m8n8.x4.shared.b16 {%0,%1,%2,%3}, [sa];\n}" : "=r"(v[0]), "=r"(v[1]), "=r"(v[2]), "=r"(v[3]) : "r"(a), "r"(win()) : "memory");
}
__device__ __forceinline__ void ldsm4t(uint32_t* v, uint32_t a) {
  asm volatile("{\n" SA("%4", "%5") "ldmatrix.sync.aligned.m8n8.x4.trans.shared.b16 {%0,%1,%2,%3}, [sa];\n}" : "=r"(v[0]), "=r"(v[1]), "=r"(v[2]), "=r"(v[3]) : "r"(a), "r"(win()) : "memory");
}
__device__ __forceinline__ void sts32(uint32_t a, uint32_t x) { asm volatile("{\n" SA("%0", "%2") "st.shared.u32 [sa], %1;\n}" ::"r"(a), "r"(x), "r"(win()) : "memory"); }
__device__ __forceinline__ void sts64(uint32_t a, uint32_t x, uint32_t y) { asm volatile("{\n" SA("%0", "%3") "st.shared.v2.u32 [sa], {%1,%2};\n}" ::"r"(a), "r"(x), "r"(y), "r"(win()) : "memory"); }
__device__ __forceinline__ void sts128(uint32_t a, uint32_t x, uint32_t y, uint32_t z, uint32_t w) {
  asm volatile("{\n" SA("%0", "%5") "st.shared.v4.u32 [sa], {%1,%2,%3,%4};\n}" ::"r"(a), "r"(x), "r"(y), "r"(z), "r"(w), "r"(win()) : "memory");
}
__device__ __forceinline__ void mbar_wait(uint32_t bar, uint32_t parity) {
  asm volatile("{\n.reg .pred p;\n" SA("%0", "%2") "LAB_WAIT:\nmbarrier.try_wait.parity.shared::cta.b64 p, [sa], %1;\n@!p bra LAB_WAIT;\n}" ::"r"(bar), "r"(parity), "r"(win()) : "memory");
}
__device__ __forceinline__ void timed_wait(uint32_t bar, uint32_t par) {
  asm volatile("{\n.reg .pred p;\n.reg .u64 t0, t1;\nmov.u64 t0, %%globaltimer;\nLAB_WD:\n"
               "mbarrier.try_wait.parity.shared::cta.b64 p, [%0], %1, 100000;\n@p bra LAB_OK;\n"
               "mov.u64 t1, %%globaltimer;\nsub.u64 t1, t1, t0;\nsetp.lt.u64 p, t1, 2000000000;\n@p bra LAB_WD;\ntrap;\nLAB_OK:\n}" ::"r"(bar + win()), "r"(par) : "memory");
}
__device__ __forceinline__ void flag_wait(const unsigned* flag, unsigned target) {
  asm volatile("{\n.reg .pred p;\n.reg .u32 v;\nLAB_WAIT:\nld.acquire.gpu.global.u32 v, [%0];\nsub.u32 v, v, %1;\n"
               "setp.lt.s32 p, v, 0;\nvote.sync.any.pred p, p, 0xffffffff;\n@p nanosleep.u32 100;\n@p bra LAB_WAIT;\n}" ::"l"(flag), "r"(target) : "memory");
}
__device__ __forceinline__ void hint_post(uint8_t* p) {
  __syncwarp();
  asm volatile("{\n.reg .pred p;\nelect.sync _|p, 0xffffffff;\n@p red.relaxed.gpu.global.add.u32 [%0], 1;\n}" ::"l"(p) : "memory");
}
__device__ __forceinline__ void hint_wait(const uint8_t* p, uint32_t target) {
  asm volatile("{\n.reg .pred p;\n.reg .u32 v;\nLAB_WAIT:\nld.relaxed.gpu.global.u32 v, [%0];\nsub.u32 v, v, %1;\n"
               "setp.lt.s32 p, v, 0;\nvote.sync.any.pred p, p, 0xffffffff;\n@p bra LAB_WAIT;\n}" ::"l"(p), "r"(target) : "memory");
}
__device__ __forceinline__ void flag_signal(unsigned* flag) { asm volatile("red.release.gpu.global.add.u32 [%0], 1;" ::"l"(flag) : "memory"); }
struct Rel {
  bool on; uint32_t base;
  uint32_t tr;
  __device__ __forceinline__ void operator()(int s) const {
    if (on) asm volatile("{\n" SA("%0", "%1") "mbarrier.arrive.shared::cluster.b64 _, [sa];\n}" ::"r"(bar_empty(s)), "r"(base) : "memory");
  }
};
__device__ __forceinline__ uint32_t cta_window(uint32_t rank) { uint32_t a; asm("mapa.shared::cluster.u32 %0, %1, %2;" : "=r"(a) : "r"(0), "r"(rank)); return a; }
#define ELECT ".reg .pred e;\nelect.sync _|e, 0xffffffff;\n"
__device__ __forceinline__ void w_expect_tx(uint32_t bar, uint32_t bytes) {
  asm volatile("{\n" ELECT "@e mbarrier.arrive.expect_tx.shared::cta.b64 _, [%0], %1;\n}" ::"r"(bar), "r"(bytes) : "memory");
}
__device__ __forceinline__ void w_tma_2d_mc(uint32_t dst, const CUtensorMap* m, int c0, int c1, uint32_t bar) {
  asm volatile("{\n" ELECT "@e cp.async.bulk.tensor.2d.shared::cluster.global.mbarrier::complete_tx::bytes.multicast::cluster [%0], [%1, {%3, %4}], [%2], %5;\n}"
               ::"r"(dst), "l"(m), "r"(bar), "r"(c0), "r"(c1), "h"((uint16_t)3) : "memory");
}
__device__ __forceinline__ void w_bulk_load_mc(uint32_t dst, const void* src, uint32_t bytes, uint32_t bar) {
  asm volatile("{\n" ELECT "@e cp.async.bulk.shared::cluster.global.mbarrier::complete_tx::bytes.multicast::cluster [%0], [%1], %2, [%3], %4;\n}"
               ::"r"(dst), "l"(src), "r"(bytes), "r"(bar), "h"((uint16_t)3) : "memory");
}
__device__ __forceinline__ void w_bulk_load(uint32_t dst, const void* src, uint32_t bytes, uint32_t bar) {
  asm volatile("{\n" ELECT "@e cp.async.bulk.shared::cluster.global.mbarrier::complete_tx::bytes [%0], [%1], %2, [%3];\n}" ::"r"(dst), "l"(src), "r"(bytes), "r"(bar) : "memory");
}
__device__ __forceinline__ void w_l2_prefetch(const void* src, uint32_t bytes) { asm volatile("{\n" ELECT "@e cp.async.bulk.prefetch.L2.global [%0], %1;\n}" ::"l"(src), "r"(bytes) : "memory"); }
__device__ __forceinline__ void w_tma_prefetch(const CUtensorMap* m, int c0, int c1) {
  asm volatile("{\n" ELECT "@e cp.async.bulk.prefetch.tensor.2d.L2.global [%0, {%1, %2}];\n}" ::"l"(m), "r"(c0), "r"(c1) : "memory");
}
__device__ __forceinline__ void w_tma_3d(uint32_t dst, const CUtensorMap* m, int c0, int c1, int c2, uint32_t bar) {
  asm volatile("{\n" ELECT "@e cp.async.bulk.tensor.3d.shared::cluster.global.mbarrier::complete_tx::bytes [%0], [%1, {%3, %4, %5}], [%2];\n}"
               ::"r"(dst), "l"(m), "r"(bar), "r"(c0), "r"(c1), "r"(c2) : "memory");
}
__device__ __forceinline__ void wg_fence() { asm volatile("wgmma.fence.sync.aligned;" ::: "memory"); }
__device__ __forceinline__ void wg_commit() { asm volatile("wgmma.commit_group.sync.aligned;" ::: "memory"); }
template <int N> __device__ __forceinline__ void wg_wait() { asm volatile("wgmma.wait_group.sync.aligned %0;" ::"n"(N) : "memory"); }
__device__ __forceinline__ void bar_sync(int id, int n) { asm volatile("bar.sync %0, %1;" ::"r"(id), "r"(n) : "memory"); }
__device__ __forceinline__ void bar_arrive(int id, int n) { asm volatile("bar.arrive %0, %1;" ::"r"(id), "r"(n) : "memory"); }
__device__ __forceinline__ uint32_t pack_bf16(float lo, float hi) { uint32_t r; asm("cvt.rn.bf16x2.f32 %0, %1, %2;" : "=r"(r) : "f"(hi), "f"(lo)); return r; }
__device__ __forceinline__ float bf_lo(uint32_t w) { return __uint_as_float(w << 16); }
__device__ __forceinline__ float bf_hi(uint32_t w) { return __uint_as_float(w & 0xffff0000u); }
__device__ __forceinline__ float bf_round(float x) { return bf_lo(pack_bf16(x, 0.f)); }
__device__ __forceinline__ uint32_t bf2_sub(uint32_t a, uint32_t b) { uint32_t r; asm("sub.rn.bf16x2 %0, %1, %2;" : "=r"(r) : "r"(a), "r"(b)); return r; }
__device__ __forceinline__ uint32_t bf2_add(uint32_t a, uint32_t b) { uint32_t r; asm("add.rn.bf16x2 %0, %1, %2;" : "=r"(r) : "r"(a), "r"(b)); return r; }
#define GADDR(B, O, I) "cvt.u64.u32 ad, " O ";\nadd.u64 ad, ad, " B ";\nadd.u64 ad, ad, " I ";\n"
__device__ __forceinline__ void ld16(uint32_t* v, const uint8_t* ub, uint32_t off, uint32_t imm) {
  asm volatile("{\n.reg .b128 z;\n.reg .b64 x, y, ad;\n" GADDR("%4", "%5", "%6") "ld.relaxed.gpu.global.b128 z, [ad];\n"
               "mov.b128 {x, y}, z;\nmov.b64 {%0,%1}, x;\nmov.b64 {%2,%3}, y;\n}"
               : "=r"(v[0]), "=r"(v[1]), "=r"(v[2]), "=r"(v[3]) : "l"(ub), "r"(off), "l"((uint64_t)imm) : "memory");
}
__device__ __forceinline__ void ld8(uint32_t* v, const uint8_t* ub, uint32_t off, uint32_t imm) {
  asm volatile("{\n.reg .b64 x, ad;\n" GADDR("%2", "%3", "%4") "ld.relaxed.gpu.global.b64 x, [ad];\nmov.b64 {%0,%1}, x;\n}"
               : "=r"(v[0]), "=r"(v[1]) : "l"(ub), "r"(off), "l"((uint64_t)imm) : "memory");
}
__device__ __forceinline__ void st16(uint8_t* ub, uint32_t off, uint32_t imm, uint32_t a, uint32_t b, uint32_t c, uint32_t d) {
  asm volatile("{\n.reg .b128 z;\n.reg .b64 x, y, ad;\n" GADDR("%0", "%1", "%2") "mov.b64 x, {%3,%4};\nmov.b64 y, {%5,%6};\nmov.b128 z, {x, y};\n"
               "st.relaxed.gpu.global.b128 [ad], z;\n}" ::"l"(ub), "r"(off), "l"((uint64_t)imm), "r"(a), "r"(b), "r"(c), "r"(d) : "memory");
}
__device__ __forceinline__ void st8(uint8_t* ub, uint32_t off, uint32_t imm, uint32_t a, uint32_t b) {
  asm volatile("{\n.reg .b64 x, ad;\n" GADDR("%0", "%1", "%2") "mov.b64 x, {%3,%4};\nst.relaxed.gpu.global.b64 [ad], x;\n}"
               ::"l"(ub), "r"(off), "l"((uint64_t)imm), "r"(a), "r"(b) : "memory");
}
__device__ __forceinline__ void send8(uint8_t* ub, uint32_t off, uint32_t imm, uint32_t sm, int i, int j, uint32_t a, uint32_t b) {
  asm volatile("{\n.reg .pred p, q, e;\n.reg .b64 x, ad;\n" SA("%3", "%8") GADDR("%0", "%1", "%2")
               "setp.lt.s32 p, %4, %5;\nsetp.gt.s32 q, %4, %5;\nsetp.eq.s32 e, %4, %5;\nmov.b64 x, {%6,%7};\n"
               "@p st.relaxed.gpu.global.b64 [ad+-1024], x;\n@q st.relaxed.gpu.global.b64 [ad], x;\n@e st.shared.v2.u32 [sa], {%6,%7};\n}"
               ::"l"(ub), "r"(off), "l"((uint64_t)imm), "r"(sm), "r"(i), "r"(j), "r"(a), "r"(b), "r"(win()) : "memory");
}
__device__ __forceinline__ uint4 ldg_line(const void* p) {
  uint4 v; asm volatile("ld.global.nc.L2::128B.v4.u32 {%0,%1,%2,%3}, [%4];" : "=r"(v.x), "=r"(v.y), "=r"(v.z), "=r"(v.w) : "l"(p)); return v;
}
__device__ __forceinline__ void stg4(void* ub, uint32_t off, uint32_t imm, uint32_t v) {
  asm volatile("{\n.reg .b64 ad;\n" GADDR("%0", "%1", "%2") "st.global.u32 [ad], %3;\n}" ::"l"(ub), "r"(off), "l"((uint64_t)imm), "r"(v) : "memory");
}
__device__ __forceinline__ uint32_t tid_() { uint32_t t; asm volatile("mov.u32 %0, %%tid.x;" : "=r"(t)); return t & 127; }
__device__ __forceinline__ uint32_t token() { uint32_t c; asm volatile("mov.u32 %0, %%clock;" : "=r"(c) :: "memory"); return c | 1; }
__device__ __forceinline__ uint32_t nz(uint32_t w) { return w ? w : 0x8000u; }
__device__ __forceinline__ void mma16816(float (&c)[4], uint32_t a0, uint32_t a1, uint32_t a2, uint32_t a3, uint32_t b0, uint32_t b1) {
  asm("mma.sync.aligned.m16n8k16.row.col.f32.bf16.bf16.f32 {%0,%1,%2,%3}, {%4,%5,%6,%7}, {%8,%9}, {%0,%1,%2,%3};"
               : "+f"(c[0]), "+f"(c[1]), "+f"(c[2]), "+f"(c[3]) : "r"(a0), "r"(a1), "r"(a2), "r"(a3), "r"(b0), "r"(b1));
}
__device__ __forceinline__ void mma1688(float (&c)[4], uint32_t a0, uint32_t a1, uint32_t b0) {
  asm("mma.sync.aligned.m16n8k8.row.col.f32.bf16.bf16.f32 {%0,%1,%2,%3}, {%4,%5}, {%6}, {%0,%1,%2,%3};"
               : "+f"(c[0]), "+f"(c[1]), "+f"(c[2]), "+f"(c[3]) : "r"(a0), "r"(a1), "r"(b0));
}
__device__ __forceinline__ float ex2(float x) { float r; asm("ex2.approx.ftz.f32 %0, %1;" : "=f"(r) : "f"(x)); return r; }
__device__ __forceinline__ float quad_sum(float v) { v += __shfl_xor_sync(0xffffffffu, v, 1); v += __shfl_xor_sync(0xffffffffu, v, 2); return v; }
__device__ __forceinline__ float quad_max(float v) { v = fmaxf(v, __shfl_xor_sync(0xffffffffu, v, 1)); v = fmaxf(v, __shfl_xor_sync(0xffffffffu, v, 2)); return v; }

__device__ __forceinline__ void wgmma_rs_n64(float (&d)[32], uint32_t a0, uint32_t a1, uint32_t a2, uint32_t a3, uint64_t desc, int scale_d) {
  asm volatile("{\n.reg .pred p;\nsetp.ne.b32 p, %37, 0;\n"
    "wgmma.mma_async.sync.aligned.m64n64k16.f32.bf16.bf16 "
    "{%0, %1, %2, %3, %4, %5, %6, %7, %8, %9, %10, %11, %12, %13, %14, %15, %16, %17, %18, %19, %20, %21, %22, %23, %24, %25, %26, %27, %28, %29, %30, %31}, "
    "{%32, %33, %34, %35}, %36, p, 1, 1, 1;\n}\n"
    : "+f"(d[0]), "+f"(d[1]), "+f"(d[2]), "+f"(d[3]), "+f"(d[4]), "+f"(d[5]), "+f"(d[6]), "+f"(d[7]), "+f"(d[8]), "+f"(d[9]), "+f"(d[10]), "+f"(d[11]), "+f"(d[12]), "+f"(d[13]), "+f"(d[14]), "+f"(d[15]), "+f"(d[16]), "+f"(d[17]), "+f"(d[18]), "+f"(d[19]), "+f"(d[20]), "+f"(d[21]), "+f"(d[22]), "+f"(d[23]), "+f"(d[24]), "+f"(d[25]), "+f"(d[26]), "+f"(d[27]), "+f"(d[28]), "+f"(d[29]), "+f"(d[30]), "+f"(d[31])
    : "r"(a0), "r"(a1), "r"(a2), "r"(a3), "l"(desc), "r"(scale_d));
}

__device__ __forceinline__ void wgmma_rs_n72(float (&d)[36], uint32_t a0, uint32_t a1, uint32_t a2, uint32_t a3, uint64_t desc, int scale_d) {
  asm volatile("{\n.reg .pred p;\nsetp.ne.b32 p, %41, 0;\n"
    "wgmma.mma_async.sync.aligned.m64n72k16.f32.bf16.bf16 "
    "{%0, %1, %2, %3, %4, %5, %6, %7, %8, %9, %10, %11, %12, %13, %14, %15, %16, %17, %18, %19, %20, %21, %22, %23, %24, %25, %26, %27, %28, %29, %30, %31, %32, %33, %34, %35}, "
    "{%36, %37, %38, %39}, %40, p, 1, 1, 1;\n}\n"
    : "+f"(d[0]), "+f"(d[1]), "+f"(d[2]), "+f"(d[3]), "+f"(d[4]), "+f"(d[5]), "+f"(d[6]), "+f"(d[7]), "+f"(d[8]), "+f"(d[9]), "+f"(d[10]), "+f"(d[11]), "+f"(d[12]), "+f"(d[13]), "+f"(d[14]), "+f"(d[15]), "+f"(d[16]), "+f"(d[17]), "+f"(d[18]), "+f"(d[19]), "+f"(d[20]), "+f"(d[21]), "+f"(d[22]), "+f"(d[23]), "+f"(d[24]), "+f"(d[25]), "+f"(d[26]), "+f"(d[27]), "+f"(d[28]), "+f"(d[29]), "+f"(d[30]), "+f"(d[31]), "+f"(d[32]), "+f"(d[33]), "+f"(d[34]), "+f"(d[35])
    : "r"(a0), "r"(a1), "r"(a2), "r"(a3), "l"(desc), "r"(scale_d));
}

__device__ __forceinline__ void wgmma_rs_n128(float (&d)[64], uint32_t a0, uint32_t a1, uint32_t a2, uint32_t a3, uint64_t desc, int scale_d) {
  asm volatile("{\n.reg .pred p;\nsetp.ne.b32 p, %69, 0;\n"
    "wgmma.mma_async.sync.aligned.m64n128k16.f32.bf16.bf16 "
    "{%0, %1, %2, %3, %4, %5, %6, %7, %8, %9, %10, %11, %12, %13, %14, %15, %16, %17, %18, %19, %20, %21, %22, %23, %24, %25, %26, %27, %28, %29, %30, %31, %32, %33, %34, %35, %36, %37, %38, %39, %40, %41, %42, %43, %44, %45, %46, %47, %48, %49, %50, %51, %52, %53, %54, %55, %56, %57, %58, %59, %60, %61, %62, %63}, "
    "{%64, %65, %66, %67}, %68, p, 1, 1, 1;\n}\n"
    : "+f"(d[0]), "+f"(d[1]), "+f"(d[2]), "+f"(d[3]), "+f"(d[4]), "+f"(d[5]), "+f"(d[6]), "+f"(d[7]), "+f"(d[8]), "+f"(d[9]), "+f"(d[10]), "+f"(d[11]), "+f"(d[12]), "+f"(d[13]), "+f"(d[14]), "+f"(d[15]), "+f"(d[16]), "+f"(d[17]), "+f"(d[18]), "+f"(d[19]), "+f"(d[20]), "+f"(d[21]), "+f"(d[22]), "+f"(d[23]), "+f"(d[24]), "+f"(d[25]), "+f"(d[26]), "+f"(d[27]), "+f"(d[28]), "+f"(d[29]), "+f"(d[30]), "+f"(d[31]), "+f"(d[32]), "+f"(d[33]), "+f"(d[34]), "+f"(d[35]), "+f"(d[36]), "+f"(d[37]), "+f"(d[38]), "+f"(d[39]), "+f"(d[40]), "+f"(d[41]), "+f"(d[42]), "+f"(d[43]), "+f"(d[44]), "+f"(d[45]), "+f"(d[46]), "+f"(d[47]), "+f"(d[48]), "+f"(d[49]), "+f"(d[50]), "+f"(d[51]), "+f"(d[52]), "+f"(d[53]), "+f"(d[54]), "+f"(d[55]), "+f"(d[56]), "+f"(d[57]), "+f"(d[58]), "+f"(d[59]), "+f"(d[60]), "+f"(d[61]), "+f"(d[62]), "+f"(d[63])
    : "r"(a0), "r"(a1), "r"(a2), "r"(a3), "l"(desc), "r"(scale_d));
}

__device__ __forceinline__ void wgmma_rs_n144(float (&d)[72], uint32_t a0, uint32_t a1, uint32_t a2, uint32_t a3, uint64_t desc, int scale_d) {
  asm volatile("{\n.reg .pred p;\nsetp.ne.b32 p, %77, 0;\n"
    "wgmma.mma_async.sync.aligned.m64n144k16.f32.bf16.bf16 "
    "{%0, %1, %2, %3, %4, %5, %6, %7, %8, %9, %10, %11, %12, %13, %14, %15, %16, %17, %18, %19, %20, %21, %22, %23, %24, %25, %26, %27, %28, %29, %30, %31, %32, %33, %34, %35, %36, %37, %38, %39, %40, %41, %42, %43, %44, %45, %46, %47, %48, %49, %50, %51, %52, %53, %54, %55, %56, %57, %58, %59, %60, %61, %62, %63, %64, %65, %66, %67, %68, %69, %70, %71}, "
    "{%72, %73, %74, %75}, %76, p, 1, 1, 1;\n}\n"
    : "+f"(d[0]), "+f"(d[1]), "+f"(d[2]), "+f"(d[3]), "+f"(d[4]), "+f"(d[5]), "+f"(d[6]), "+f"(d[7]), "+f"(d[8]), "+f"(d[9]), "+f"(d[10]), "+f"(d[11]), "+f"(d[12]), "+f"(d[13]), "+f"(d[14]), "+f"(d[15]), "+f"(d[16]), "+f"(d[17]), "+f"(d[18]), "+f"(d[19]), "+f"(d[20]), "+f"(d[21]), "+f"(d[22]), "+f"(d[23]), "+f"(d[24]), "+f"(d[25]), "+f"(d[26]), "+f"(d[27]), "+f"(d[28]), "+f"(d[29]), "+f"(d[30]), "+f"(d[31]), "+f"(d[32]), "+f"(d[33]), "+f"(d[34]), "+f"(d[35]), "+f"(d[36]), "+f"(d[37]), "+f"(d[38]), "+f"(d[39]), "+f"(d[40]), "+f"(d[41]), "+f"(d[42]), "+f"(d[43]), "+f"(d[44]), "+f"(d[45]), "+f"(d[46]), "+f"(d[47]), "+f"(d[48]), "+f"(d[49]), "+f"(d[50]), "+f"(d[51]), "+f"(d[52]), "+f"(d[53]), "+f"(d[54]), "+f"(d[55]), "+f"(d[56]), "+f"(d[57]), "+f"(d[58]), "+f"(d[59]), "+f"(d[60]), "+f"(d[61]), "+f"(d[62]), "+f"(d[63]), "+f"(d[64]), "+f"(d[65]), "+f"(d[66]), "+f"(d[67]), "+f"(d[68]), "+f"(d[69]), "+f"(d[70]), "+f"(d[71])
    : "r"(a0), "r"(a1), "r"(a2), "r"(a3), "l"(desc), "r"(scale_d));
}

template <int N> struct WG;
template <> struct WG<64>  { static __device__ __forceinline__ void f(float (&d)[32], const uint32_t* a, uint64_t ds, int s) { wgmma_rs_n64(d, a[0], a[1], a[2], a[3], ds, s); } };
template <> struct WG<72>  { static __device__ __forceinline__ void f(float (&d)[36], const uint32_t* a, uint64_t ds, int s) { wgmma_rs_n72(d, a[0], a[1], a[2], a[3], ds, s); } };
template <> struct WG<128> { static __device__ __forceinline__ void f(float (&d)[64], const uint32_t* a, uint64_t ds, int s) { wgmma_rs_n128(d, a[0], a[1], a[2], a[3], ds, s); } };
template <> struct WG<144> { static __device__ __forceinline__ void f(float (&d)[72], const uint32_t* a, uint64_t ds, int s) { wgmma_rs_n144(d, a[0], a[1], a[2], a[3], ds, s); } };

constexpr uint64_t DESC_SW128 = ((uint64_t)(8192 >> 4) << 16) | ((uint64_t)(1024 >> 4) << 32) | (1ull << 62);
constexpr uint64_t DESC_KV = ((uint64_t)(128 >> 4) << 16) | ((uint64_t)(768 >> 4) << 32);
constexpr uint64_t DESC_Q = ((uint64_t)(128 >> 4) << 16) | ((uint64_t)(1536 >> 4) << 32);

template <int V> struct IntC { static constexpr int value = V; };
enum { PS_KV, PS_Q, PS_WO, PS_FF, PS_FFA   };
template <int PS> __host__ __device__ constexpr int pass_slot(int i) {
  return PS == PS_KV ? (i < 3 ? 9 + i : i - 3) : PS == PS_WO ? 6 + i : i;
}

__device__ __forceinline__ void load_frag(uint32_t (&a)[144], int i, const uint8_t* sb, uint32_t uo, uint32_t t) {
  if (i < 32) ld16(&a[4 * i], sb, uo + t * 16, i * 2048);
  else { ld8(&a[4 * i], sb, uo + t * 8, i * 2048); ld8(&a[4 * i + 2], sb, uo + t * 8, i * 2048 + 1024); }
}
__device__ __forceinline__ void store_own(const uint32_t (&y)[18], uint8_t* sb, uint32_t uo, int j, uint32_t t) {
#pragma unroll
  for (int i = 0; i < 4; i++) st16(sb, uo + j * 8192 + t * 16, i * 2048, nz(y[4 * i]), y[4 * i + 1], y[4 * i + 2], y[4 * i + 3]);
  st8(sb, uo + j * 1024 + t * 8, 65536, nz(y[16]), y[17]);
}
__device__ __forceinline__ void load_own(uint32_t* y, const uint8_t* sb, uint32_t uo, int j) {
  const uint32_t t = tid_();
#pragma unroll
  for (int i = 0; i < 4; i++) ld16(&y[4 * i], sb, uo + j * 8192 + t * 16, i * 2048);
  ld8(&y[16], sb, uo + j * 1024 + t * 8, 65536);
}

#define TR(i) do {} while (0)
struct NoTail { __device__ __forceinline__ void operator()() const {} };
template <int N, int PS, int KPS, int KSTEP, int CHK, bool SUB, bool HREL = false, class Tail = NoTail>
__device__ __forceinline__ void mma_pass(float (&acc)[N / 2], uint32_t (&a)[144], uint64_t desc, uint32_t par, const Rel& rel, int bar_id,
                                         const uint8_t* sb = nullptr, uint32_t uo = 0, uint32_t flag = 0, uint32_t m0 = 0, uint32_t m1 = 0, uint32_t park = 0, Tail tail = Tail()) {
  constexpr int NS = 36 / KPS;
  auto check = [&](int lo, int hi, uint32_t m0_) {
    auto missing = [&]() {
      uint32_t u[3] = {m0_, m0_, m0_};
#pragma unroll
      for (int i = hi - 1; i >= lo; i--) {
        u[i % 3] = min(u[i % 3], a[4 * i]);
        if (i >= 32) u[i % 3] = min(u[i % 3], a[4 * i + 2]);
      }
      return __any_sync(0xffffffffu, (min(u[0], min(u[1], u[2])) | flag) == 0);
    };
    if (__builtin_expect(missing(), 0)) {
      do {
        const uint32_t t = tid_();
#pragma unroll
        for (int i = lo; i < hi; i++) load_frag(a, i, sb, uo, t);
      } while (missing());
    }
  };
#pragma unroll
  for (int s = 0; s < NS; s++) {
    const int sl = pass_slot<PS>(s);
    if (CHK && s == 0 && !SUB) check(0, CHK * KPS, ~0u);
    if (CHK && s == CHK) check(CHK * KPS, 36, token());
    if (SUB) {
#pragma unroll
      for (int i = s * KPS * 4; i < (s + 1) * KPS * 4; i += 2) { a[i] = bf2_sub(a[i], m0); a[i + 1] = bf2_sub(a[i + 1], m1); }
    }
    if (PS == PS_KV && bar_id < 0 && (s == 0 || s == KV_S1) && (s == (flag ? KV_S1 : 0))) bar_sync(NB_ORD1, 256);
    if (PS == PS_KV && s == 0) sts128(park + tid_() * 16, a[0], a[1], a[2], a[3]);
    constexpr int TB = PS == PS_KV ? 0 : PS == PS_Q ? 26 : PS == PS_WO ? 40 : SUB ? 54 : PS == PS_FFA ? 74 : -1;
    if (TB >= 0) TR(TB + 2 * s);
    mbar_wait(bar_full(sl), sl < 9 ? par : par ^ 1);
    if (TB >= 0) TR(TB + 2 * s + 1);
    wg_fence();
#pragma unroll
    for (int kk = 0; kk < KPS; kk++)
      WG<N>::f(acc, &a[(s * KPS + kk) * 4], desc + ((slot_addr(sl) + kk * KSTEP) >> 4), (s | kk) || PS == PS_FFA);
    wg_commit();
    if (CHK && s < 2 && N_UP < 36 && !flag) {
      const uint32_t t = tid_();
#pragma unroll
      for (int i = s ? (N_UP + 36) / 2 : N_UP; i < (s ? 36 : (N_UP + 36) / 2); i++) load_frag(a, i, sb, uo, t);
    }
    if (PS == PS_KV ? (s == KV_LEAD || s == KV_S1 + KV_LEAD) && s == (flag ? KV_S1 : 0) + KV_LEAD : s == NS - 1)
      if (bar_id >= 0) bar_arrive(bar_id, 256);
    if (s > 0) {
      wg_wait<1>();
      if (!(PS == PS_WO && s > 3)) rel(pass_slot<PS>(s - 1));
    }
    if (HREL && s == 3 && flag) {
#pragma unroll
      for (int i = 0; i < 12; i++) ld16(&a[4 * i], sb, uo, i * 2048);
    }
  }
  constexpr int TE = PS == PS_KV ? 24 : PS == PS_Q ? 38 : PS == PS_WO ? 52 : SUB ? 72 : PS == PS_FFA ? 92 : -1;
  tail();
  if (TE >= 0) TR(TE);
  wg_wait<0>();
  if (TE >= 0) TR(TE + 1);
  if (PS != PS_WO) rel(pass_slot<PS>(NS - 1));
}

template <int NF, int N0 = 0> __device__ __forceinline__ void load_frags(uint32_t (&a)[144], const uint8_t* sb, uint32_t uo, uint32_t t) {
#pragma unroll
  for (int i = N0; i < NF; i++) load_frag(a, i, sb, uo, t);
}
__device__ __forceinline__ void ln_scalars(float s1, float s2, uint32_t& m, float& var, uint32_t zero) {
  const float mean = s1 * (1.f / DM);
  var = s2 * (1.f / DM) - mean * mean;
  m = pack_bf16(mean, mean) ^ (__float_as_uint(var) & zero);
}
__device__ __forceinline__ float ln_rstd(float var, float after, uint32_t zero) {
  var = __uint_as_float(__float_as_uint(var) ^ (__float_as_uint(after) & zero));
  float sd, r;
  asm("sqrt.approx.ftz.f32 %0, %1;" : "=f"(sd) : "f"(bf_round(bf_round(fmaxf(var, 0.f)) + 1e-5f)));
  asm("rcp.approx.ftz.f32 %0, %1;" : "=f"(r) : "f"(bf_round(sd)));
  return r;
}
template <int NF> __device__ __forceinline__ void gather_ln(uint32_t (&a)[144], const uint8_t* sb, uint32_t uo, uint32_t sto,
                                          uint32_t& m0, uint32_t& m1, float& r0, float& r1, uint32_t zero) {
  uint32_t u[32];
  const uint32_t t = tid_(), so = sto + (t >> 5) * 1024 + (t & 28) * 4;
#pragma unroll
  for (int i = 0; i < 8; i++) ld16(&u[4 * i], sb, so, OFF_ST + i * 128);
  load_frags<N_UP>(a, sb, uo, t);
  while (true) {
    uint32_t m = a[4 * NF - 4];
#pragma unroll
    for (int i = NF - 2; i >= 0; i--) m = min(m, a[4 * i]);
#pragma unroll
    for (int i = 0; i < 8; i++) m = min(m, u[4 * i]);
    if (!__any_sync(0xffffffffu, m == 0)) break;
#pragma unroll
    for (int i = 0; i < 8; i++) ld16(&u[4 * i], sb, so, OFF_ST + i * 128);
    load_frags<NF>(a, sb, uo, t);
  }
  float v[4];
#pragma unroll
  for (int k = 0; k < 4; k++)
    v[k] = ((__uint_as_float(u[k]) + __uint_as_float(u[4 + k])) + (__uint_as_float(u[8 + k]) + __uint_as_float(u[12 + k]))) +
           ((__uint_as_float(u[16 + k]) + __uint_as_float(u[20 + k])) + (__uint_as_float(u[24 + k]) + __uint_as_float(u[28 + k])));
  ln_scalars(v[1], v[0], m0, r0, zero); ln_scalars(v[3], v[2], m1, r1, zero);
}
struct Stats {
  float s[4] = {0, 0, 0, 0}, d0[4] = {0, 0, 0, 0}, d1[4] = {0, 0, 0, 0};
  __device__ __forceinline__ void add16(const uint32_t* f) {
    mma16816(s, f[0], f[1], f[2], f[3], 0x3f803f80u, 0x3f803f80u);
    mma1688(d0, f[0], f[1], f[0]); mma1688(d1, f[0], f[1], f[1]);
    mma1688(d0, f[2], f[3], f[2]); mma1688(d1, f[2], f[3], f[3]);
  }
  __device__ __forceinline__ float sq0(int g) const { return (g & 1) ? d0[1] : d0[0]; }
  __device__ __forceinline__ float sq1(int g) const { return (g & 1) ? d1[3] : d1[2]; }
};
struct RowStats {
  float s[4] = {0, 0, 0, 0}, u[4] = {0, 0, 0, 0};
  template <int N> __device__ __forceinline__ void add(const uint32_t* y) {
#pragma unroll
    for (int i = 0; i < N; i++) {
      const float lo = bf_lo(y[i]), hi = bf_hi(y[i]);
      const int r = (i & 1) * 2;
      s[r] = fmaf(lo, lo, s[r]); u[r] = fmaf(hi, hi, u[r]); s[r + 1] += lo; u[r + 1] += hi;
    }
  }
  __device__ __forceinline__ uint32_t fold() {
    uint32_t x = 0;
#pragma unroll
    for (int i = 0; i < 4; i++) { s[i] += u[i]; u[i] = 0; x |= __float_as_uint(s[i]); }
    return x;
  }
  __device__ __forceinline__ void store(uint8_t* sb, uint32_t sto, uint32_t t) {
    fold();
#pragma unroll
    for (int i = 0; i < 4; i++) s[i] += __shfl_xor_sync(0xffffffffu, s[i], 1);
#pragma unroll
    for (int i = 0; i < 4; i++) s[i] += __shfl_xor_sync(0xffffffffu, s[i], 2);
    if ((t & 3) == 0) st16(sb, sto + (t >> 5) * 1024 + (t & 28) * 4, OFF_ST, __float_as_uint(s[0]) | 1u, __float_as_uint(s[1]), __float_as_uint(s[2]), __float_as_uint(s[3]));
  }
};
template <bool SET> __device__ __forceinline__ void add_piece(float* acc, uint32_t sm) {
#pragma unroll
  for (int i = 0; i < 4; i++) {
    uint32_t v[4];
    lds128(v, sm + i * 2048);
#pragma unroll
    for (int k = 0; k < 4; k++) {
      acc[8 * i + 2 * k] = SET ? bf_lo(v[k]) : acc[8 * i + 2 * k] + bf_lo(v[k]);
      acc[8 * i + 2 * k + 1] = SET ? bf_hi(v[k]) : acc[8 * i + 2 * k + 1] + bf_hi(v[k]);
    }
  }
}

#define TS(i) do {} while (0)
#define TSP(i) do {} while (0)
#define TSH(i) do {} while (0)

__device__ __forceinline__ uint32_t row_off(int rb, int wg, uint32_t t) { return (rb * 128 + wg + ((t >> 5) * 16 + (t & 15)) * 2) * (2 * DM); }

__device__ __forceinline__ const __nv_bfloat16* wo_src(const __nv_bfloat16* wo, int k, int u, int j) {
  const int ko = k < 512 ? (k >> 6) * 72 + (k & 63) : ((k >> 3) & 7) * 72 + 64 + (k & 7);
  return wo + ko * 576 + (u < 8 ? j * 64 + u * 8 : 512 + j * 8);
}

struct Params {
  const __nv_bfloat16* wqkv;
  uint8_t* scr;
  uint8_t role[64];
  const __nv_bfloat16* wo;
  __nv_bfloat16* out;
  uint8_t* times;
  unsigned zero;
};

__cluster_dims__(2, 1, 1)
__global__ void __launch_bounds__(384, 1)
fused_kernel(const __grid_constant__ Params P, const __grid_constant__ CUtensorMap map_x, const __grid_constant__ CUtensorMap map_wg,
             const __grid_constant__ CUtensorMap map_wu, const __grid_constant__ CUtensorMap map_wd) {
  const int wg = __shfl_sync(0xffffffffu, threadIdx.x >> 7, 0);
  const int cta = blockIdx.x, rank = cta & 1, role = P.role[cta >> 1], j = role & 7, rb = (role >> 3) * 2 + rank;
  const uint32_t own = win();
  unsigned* const flags = (unsigned*)(P.scr + OFF_FLAGS);
  if (__shfl_sync(0xffffffffu, threadIdx.x >> 5, 0) == 11) {
    if (threadIdx.x == 352) {
#pragma unroll
      for (int i = 0; i < 14; i++) { mbar_init(bar_full(i), 1); mbar_init(bar_empty(i), i < 12 ? 4 : i == 12 ? 8 : 2); }
      mbar_init(bar_full(14), 1); mbar_init(bar_empty(14), 1);
      asm volatile("fence.mbarrier_init.release.cluster;" ::: "memory");
      if (smem_u32(smem_raw) != own + SB) asm volatile("trap;");
    }
    __syncwarp();
    asm volatile("barrier.cluster.arrive.relaxed.aligned;" ::: "memory");
#pragma unroll
    for (int c = 0; c < 9; c++) {
      w_tma_3d(own + slot_addr(c), &map_x, c * 64, rb * 64, 0, own + bar_full(c));
      w_expect_tx(own + bar_full(c), SLOT);
    }
  } else {
    const bool on = threadIdx.x < 324;
    const int k = rb * 36 + (on ? threadIdx.x / 36 : 0) * 4 + (threadIdx.x & 3), u = (threadIdx.x % 36) >> 2;
    const uint4* s = (const uint4*)(P.wqkv + k * 1728 + j * 72 + u * 8);
    const uint4 vk = ldg_line(s + 72), vv = ldg_line(s + 144);
    const unsigned ep0 = *(volatile unsigned*)&flags[(72 + cta) * 8];
    asm volatile("barrier.cluster.arrive.relaxed.aligned;" ::: "memory");
    uint8_t* d = P.scr + OFF_WPACK + j * 24 * PSLOT;
    if (on) {
      const uint32_t dkv = (k / 48) * PSLOT + u * 768 + (k % 48) * 16;
      st16(d, dkv, 0, vk.x, vk.y, vk.z, vk.w);
      st16(d, dkv, 9 * 768, vv.x, vv.y, vv.z, vv.w);
    }
    asm volatile("fence.proxy.async.global;" ::: "memory");
    bar_arrive(NB_PUB + 3, 384);
    if (threadIdx.x == 351) sts32(SM_EPOCH, ep0);
    if (wg == 2) bar_sync(NB_PUB + 1, 96);
  }
  __syncwarp();
  asm volatile("barrier.cluster.wait.acquire.aligned;" ::: "memory");

  if (wg == 2) {
    asm volatile("setmaxnreg.dec.sync.aligned.u32 24;");
    const int pw = __shfl_sync(0xffffffffu, (threadIdx.x >> 5) & 3, 0), lane = threadIdx.x & 31;
    auto tile_col = [](int t, int h, int j) { return t < 9 ? j * 576 + t * 64 : (t == 9 && h) ? 512 : ((j + ((h ? 0x05760 : 0x04123) >> (4 * (t - 9)))) & 7) * 64; };
    auto prefetch_tile = [&](int t) {
#pragma unroll 1
      for (int b = rb; b < 18; b += 16) {
        const int h = b & 1, k = b >> 1;
        if (t < 9) w_tma_prefetch(h ? &map_wu : &map_wg, tile_col(t, h, j), k * 64);
        else if (t != 13 || !h) w_tma_prefetch(&map_wd, tile_col(t, h, j), j * 576 + k * 64);
      }
    };
    if (pw == 0) {
      {
        flag_wait(&flags[j * 8], (lds32(SM_EPOCH) + 1) * 16);
        TSP(7);
        asm volatile("fence.proxy.async.global;" ::: "memory");
        const uint8_t* wp = P.scr + OFF_WPACK + j * 24 * PSLOT;
        wp += rank * (PSLOT / 2);
        auto packed = [&](int sl, uint32_t par, int f) {
          mbar_wait(bar_empty(0) + sl * 8, par);
          w_bulk_load_mc(own + SB + rank * (PSLOT / 2) + sl * SLOT, wp + f * PSLOT, PSLOT / 2, own + bar_full(0) + sl * 8);
          w_expect_tx(own + bar_full(0) + sl * 8, PSLOT);
        };
        const uint32_t half = own + SB + rank * 8192;
#pragma unroll 1
        for (int L = 0; L < 2; L++) {
#pragma unroll 1
          for (int s = L ? 0 : -3; s < 21; s++) {
            if (s == 9 && L == 0) { flag_wait(&flags[(56 + j) * 8], (lds32(SM_EPOCH) + 1) * 16); asm volatile("fence.proxy.async.global;" ::: "memory"); }
            packed(s < 0 ? s + 12 : s < 9 ? s : s - 9, s < 0 || (s >= 9 && s < 18), s + 3);
          }
#pragma unroll 1
          for (int t = 0; t < 14; t++) {
            if (L * 14 + t + PF_AHEAD < 28) prefetch_tile((t + PF_AHEAD) % 14);
            const CUtensorMap* mp = t >= 9 ? &map_wd : rank ? &map_wu : &map_wg;
            const bool nar = t == 13;
            const int col = tile_col(t, nar ? 0 : rank, j);
            const uint32_t dst = nar ? own + SB : half, bytes = nar ? 8192 : SLOT;
            const int ra = t < 9 ? 0 : j * 576 + 320, rbs = t < 9 ? 0 : j * 576 - 192, rc = t < 9 ? 0 : j * 576;
#pragma unroll
            for (int k = 0; k < 9; k++) {
              mbar_wait(bar_empty(k), t & 1);
              if (!nar || rank == (k & 1)) w_tma_2d_mc(dst + k * SLOT, mp, col, (k < 3 ? ra : k < 8 ? rbs : rc) + k * 64, own + bar_full(k));
              w_expect_tx(own + bar_full(k), bytes);
            }
            if (t == 12 && L == 0) {
              w_l2_prefetch(P.scr + OFF_WPACK + j * 24 * PSLOT + rb * (24 * PSLOT / 16), 24 * PSLOT / 16);
#pragma unroll 1
              for (int s = 0; s < 3; s++) packed(9 + s, 1, s);
            }
          }
        }
        flags[(72 + cta) * 8] = lds32(SM_EPOCH) + 1;
      }
    } else if (pw < 3) {
      const int hw = pw - 1;
      const uint32_t ep = __shfl_sync(0xffffffffu, lds32(SM_EPOCH), 0);
      uint8_t* const sb = P.scr + (rb * 2 + hw) * STRM;
      const uint32_t xs = slot_addr(12) + hw * SLOT, fb = bar_full(12) + hw * 8;
      uint32_t hph = 0;
#pragma unroll 1
      for (int L = 0; L < 2; L++) {
        const uint32_t tag = ep * 2 + L + 1;
        bar_sync(NB_FREE + hw, 160);
        if (rb > 0) hint_wait(sb + OFF_HINT + 512 + j * 128, tag);
        uint32_t bad;
        do {
          if (rb > 0) {
            w_bulk_load(own + ytail(hw * 2), sb + OFF_HALO + (L * 8 + j) * 3072, 1536, own + bar_full(14) + hw * 128);
            w_bulk_load(own + ytail(hw * 2 + 1), sb + OFF_HALO + (L * 8 + j) * 3072 + 1536, 1536, own + bar_full(14) + hw * 128);
            w_expect_tx(own + bar_full(14) + hw * 128, 3072);
            mbar_wait(bar_full(14) + hw * 128, hph);
            hph ^= 1;
          }
          bad = 0;
#pragma unroll 1
          for (int c = 0; c < 3; c++) {
            uint32_t u[4] = {tag, 0, 0, 0}, v[4] = {tag, 0, 0, 0};
            if (rb > 0) { lds128(u, ytail(hw * 2) + c * 512 + lane * 16); lds128(v, ytail(hw * 2 + 1) + c * 512 + lane * 16); }
            bad |= (u[0] ^ tag) | (v[0] ^ tag);
#pragma unroll
            for (int i = 0; i < 3; i++) { sts32(xs + KSTG + (c * 3 + i) * 128 + lane * 4, u[i + 1]); sts32(xs + (c * 3 + i) * 128 + lane * 4, v[i + 1]); }
          }
        } while (__any_sync(0xffffffffu, bad != 0));
        bar_arrive(NB_HALO + hw, 160);
#pragma unroll 1
        for (int p = 0; p < 4; p++) {
          if (L == 0 && p == 3) flag_wait(flags + (40 + rb) * 8, (ep + 1) * 8);
          bar_sync(NB_FREE + hw, 160);
          TSH(L * 12 + p * 3);
          hint_wait(sb + OFF_HINT + (lane & 3) * 128, (ep * 13 + L * 7 + p + 3) * 8);
          TSH(L * 12 + p * 3 + 1);
          w_bulk_load(own + xs, sb + OFF_P + j * PSRC + (p & 1) * 16384, p ? 16384 : 8192, own + fb);
          if (p == 0) w_bulk_load(own + xs + 8192, sb + OFF_P + j * PSRC + 32768, 7168, own + fb);
          w_expect_tx(own + fb, p ? 16384 : 15360);
          TSH(L * 12 + p * 3 + 2);
        }
      }
    } else {
      auto clear = [&](int t) {
        const uint32_t so = rb * 2 * STRM + (threadIdx.x & 31) * 16;
#pragma unroll 1
        for (int i = 0; i < 18; i++) {
          st16(P.scr, so + t * TILE + j * 9216 + i * 512, 0, 0, 0, 0, 0);
          st16(P.scr, so + t * TILE + j * 9216 + i * 512, STRM, 0, 0, 0, 0);
          __nanosleep(0);
        }
        if (t != 1) {
          st16(P.scr, so + (t ? t - 1 : 0) * 4096 + j * 512, OFF_ST, 0, 0, 0, 0);
          st16(P.scr, so + (t ? t - 1 : 0) * 4096 + j * 512, OFF_ST + STRM, 0, 0, 0, 0);
        }
      };
      bar_sync(NB_PUB + 3, 384);
      if (lane == 0) flag_signal(&flags[j * 8]);
      TSP(5);
      bar_sync(NB_PUB + 2, 288);
      if (lane == 0) flag_signal(&flags[(56 + j) * 8]);
      TSP(4);
      __syncwarp();
#pragma unroll 1
      for (int t = 0; t < PF_AHEAD; t++) prefetch_tile(t);
#pragma unroll 1
      for (int L = 0; L < 2; L++) {
        timed_wait(bar_empty(13), L);
#pragma unroll 1
        for (int t = L ^ 1; t < 4 - 2 * L; t++) clear(t);
        __syncwarp();
        if (lane == 0 && L == 0) flag_signal(flags + (40 + rb) * 8);
      }
      timed_wait(bar_empty(12), 0);
      asm volatile("barrier.cluster.arrive.relaxed.aligned;\nbarrier.cluster.wait.aligned;" ::: "memory");
    }
  } else {
    asm volatile("setmaxnreg.inc.sync.aligned.u32 240;");
    const int w = __shfl_sync(0xffffffffu, (threadIdx.x >> 5) & 3, 0);
    Rel rel{(threadIdx.x & 95) == 0, cta_window(w & 1), 0};
    uint8_t* const sb = P.scr + (rb * 2 + wg) * STRM;
    uint8_t* const hint = sb + OFF_HINT + w * 128;
    auto hint_target = [](int e) { return (lds32(SM_EPOCH) * 13 + e + 1) * 8; };
    TS(0);
    uint32_t a[144];
#pragma unroll 1
    for (int L = 0; L < 2; L++) {
      uint32_t m0, m1; float r0, r1;
      rel.tr = win() + ytail(3) + 1536 + (L == TRACE - 1 && w == 1 ? wg * 384 : 768);
      if (L == 0) {
        Stats st;
        const int lane = tid_() & 31, g = lane >> 2;
        const int row = w * 16 + (lane & 15);
        const uint32_t ra = SB + wg * 8192 + row * 128;
        const uint32_t pt = tid_(), pu = (pt % 36) >> 2, pk = rb * 36 + (pt < 108 ? pt / 36 : 0) * 4 + (pt & 3);
        uint4 pv[3];
#pragma unroll
        for (int i = 0; i < 3; i++) pv[i] = ldg_line(wg ? wo_src(P.wo, pk + i * 12, pu, j) : P.wqkv + (pk + i * 12) * 1728 + j * 72 + pu * 8);
#pragma unroll
        for (int c = 0; c < 9; c++) {
          mbar_wait(bar_full(c), 0);
          if (c == 0) TS(60); if (c == 8) TS(62);
#pragma unroll
          for (int kk = 0; kk < 4; kk++) ldsm4(&a[c * 16 + kk * 4], ra + (((kk * 2 + (lane >> 4)) ^ (row & 7)) << 4) + c * SLOT);
          if (c == 8) {
            uint32_t y[18], z[4];
#pragma unroll
            for (int i = 0; i < 4; i++) ldsm4(&y[4 * i], ra + (((i * 2 + (lane >> 4)) ^ (row & 7)) << 4) + j * SLOT);
            ldsm4(z, ra + ((j ^ (row & 7)) << 4) + 8 * SLOT);
            y[16] = z[0]; y[17] = z[1];
            bar_sync(NB_WG + wg, 128);
#pragma unroll
            for (int i = 0; i < 9; i++) rel(i);
            if (pt < 108) {
#pragma unroll
              for (int i = 0; i < 3; i++) {
                const uint32_t k = pk + i * 12;
                st16(P.scr, (j * 24 + wg * 6 + k / 96) * PSLOT + pu * 1536 + (k % 96) * 16, OFF_WPACK + 12 * PSLOT, pv[i].x, pv[i].y, pv[i].z, pv[i].w);
              }
            }
            asm volatile("fence.proxy.async.global;" ::: "memory");
            bar_arrive(NB_PUB + 2, 288);
            store_own(y, sb, OFF_X2, j, tid_());
          }
#pragma unroll
          for (int kk = 0; kk < 4; kk++) st.add16(&a[c * 16 + kk * 4]);
        }
        const int dl = (lane & ~3) | (g >> 1);
        ln_scalars(st.s[0], __shfl_sync(0xffffffffu, st.sq0(g), dl), m0, r0, P.zero);
        ln_scalars(st.s[2], __shfl_sync(0xffffffffu, st.sq1(g), dl), m1, r1, P.zero);
      } else {
#pragma unroll
        for (int i = 4 * N_UP; i < 144; i++) a[i] = 0;
        hint_wait(hint, hint_target(6));
        TS(61);
        gather_ln<3 * D_KV>(a, sb, OFF_X2, 8192, m0, m1, r0, r1, P.zero);
      }
      TS(1 + L * 20);
      uint32_t kf[18], qf[18];
      {
        float acc[72];
        mma_pass<144, PS_KV, 3, 256, D_KV, true>(acc, a, DESC_KV, 1, rel, wg == 0 ? NB_ORD1 : -1, sb, OFF_X2, L ^ 1, m0, m1, ytail(wg * 2));
        r0 = ln_rstd(r0, acc[0], P.zero); r1 = ln_rstd(r1, acc[0], P.zero);
        uint32_t vf[18];
#pragma unroll
        for (int c = 0; c < 9; c++) {
          kf[c] = pack_bf16(acc[4 * c] * r0, acc[4 * c + 1] * r0);
          kf[9 + c] = pack_bf16(acc[4 * c + 2] * r1, acc[4 * c + 3] * r1);
          vf[c] = pack_bf16(acc[36 + 4 * c] * r0, acc[36 + 4 * c + 1] * r0);
          vf[9 + c] = pack_bf16(acc[36 + 4 * c + 2] * r1, acc[36 + 4 * c + 3] * r1);
        }
        TS(2 + L * 20);
        const uint32_t l16 = (tid_() & 31) * 16, xs = slot_addr(12) + wg * SLOT + w * 1152;
#pragma unroll
        for (int i = 0; i < 4; i++) stsm4(xs + w * 1152 + 1152 + i * 512 + l16, vf[4 * i], vf[4 * i + 1], vf[4 * i + 2], vf[4 * i + 3]);
        sts32(xs + w * 1152 + 1152 + 2048 + l16 / 4, vf[16]); sts32(xs + w * 1152 + 1152 + 2176 + l16 / 4, vf[17]);
        if (w < 3) {
          stsm4(xs + KSTG + 1152 + l16, kf[9], kf[10], kf[11], kf[12]);
          stsm4(xs + KSTG + 1152 + 512 + l16, kf[13], kf[14], kf[15], kf[16]);
          sts32(xs + KSTG + 1152 + 1024 + l16 / 4, kf[17]);
        } else if (rb < 15) {
          const uint32_t tag = lds32(SM_EPOCH) * 2 + L + 1;
          const uint32_t ho = l16 + (L * 8 + j) * 3072;
#pragma unroll
          for (int c = 0; c < 3; c++) {
            st16(sb, ho, 2 * STRM + OFF_HALO + c * 512, tag, kf[9 + 3 * c], kf[10 + 3 * c], kf[11 + 3 * c]);
            st16(sb, ho, 2 * STRM + OFF_HALO + 1536 + c * 512, tag, vf[9 + 3 * c], vf[10 + 3 * c], vf[11 + 3 * c]);
          }
          hint_post(sb + 2 * STRM + OFF_HINT + 512 + j * 128);
        }
      }
      lds128(a, ytail(wg * 2) + tid_() * 16);
      bar_arrive(NB_FREE + wg, 160);
      uint32_t kh[12], vp[20], v1[12];
      {
        float acc[36];
        if (wg == 1) bar_sync(NB_ORD1, 256);
        mma_pass<72, PS_Q, 6, 256, 0, false, false>(acc, a, DESC_Q, 0, rel, -1, nullptr, 0, 0, 0, 0, 0, [&]() {
          bar_sync(NB_HALO + wg, 160);
#pragma unroll
          for (int i = 0; i < 3; i++) ldsm4(&kh[4 * i], slot_addr(12) + wg * SLOT + w * 640 + tid_() * 16 + KSTG + i * 512);
          const uint32_t l = tid_() & 31, vb = slot_addr(12) + wg * SLOT + w * 2304;
#pragma unroll
          for (int i = 0; i < 5; i++) ldsm4t(&vp[4 * i], vb + (l & 8) * 144 + (l & 16) * 8 + (l & 7) * 16 + i * 256);
#pragma unroll
          for (int i = 0; i < 3; i++) ldsm4t(&v1[4 * i], vb + 2304 + l * 16 + i * 512);
        });
#pragma unroll
        for (int i = 0; i < 18; i++) qf[i] = pack_bf16(acc[2 * i], acc[2 * i + 1]);
      }
      TS(3 + L * 20);
      uint32_t xr[18];
      {
        const int tid = tid_(), g = (tid >> 2) & 7, q = tid & 3;
        const bool nohalo = (rb == 0 && w == 0);
        const bool le0 = 2 * q <= g, le1 = 2 * q + 1 <= g;
        const uint32_t M = (le0 ? 0xffffu : 0u) | (le1 ? 0xffff0000u : 0u);
        const float sc0 = r0 * (0.23570226039551584f * 1.4426950408889634f), sc1 = r1 * (0.23570226039551584f * 1.4426950408889634f);
        float l[16], t[8];
#pragma unroll
        for (int h = 0; h < 4; h++) {
          const uint32_t qa0 = q >= h ? qf[4 * h] : 0u, qa1 = q >= h ? qf[4 * h + 1] : 0u;
          const uint32_t qc0 = q <= h ? qf[4 * h + 4] : 0u, qc1 = q <= h ? qf[4 * h + 5] : 0u;
          float sm[4] = {0, 0, 0, 0}, s0[4] = {0, 0, 0, 0}, s1[4] = {0, 0, 0, 0};
          mma16816(s0, qa0, qa1, qf[4 * h + 2], qf[4 * h + 3], kf[2 * h], kf[2 * h + 1]);
          mma16816(s1, qa0, qa1, qf[4 * h + 2], qf[4 * h + 3], kf[9 + 2 * h], kf[10 + 2 * h]);
          mma16816(sm, qa0, qa1, qf[4 * h + 2], qf[4 * h + 3], kh[2 * h], kh[2 * h + 1]);
          mma1688(s0, qc0, qc1, kf[2 * h + 2]);
          mma1688(s1, qc0, qc1, kf[11 + 2 * h]);
          mma1688(sm, qc0, qc1, kh[2 * h + 2]);
          if (nohalo) sm[0] = sm[1] = -3e38f;
          l[4 * h] = le0 ? s0[0] : sm[0]; l[4 * h + 1] = le1 ? s0[1] : sm[1];
          l[4 * h + 2] = le0 ? s1[2] : s0[2]; l[4 * h + 3] = le1 ? s1[3] : s0[3];
        }
#pragma unroll
        for (int i = 0; i < 8; i++) t[i] = fmaxf(l[2 * i], l[2 * i + 1]);
        TS(14 + L * 20);
#pragma unroll
        for (int i = 0; i < 8; i++) t[i] = fmaxf(t[i], __shfl_xor_sync(0xffffffffu, t[i], 1));
#pragma unroll
        for (int i = 0; i < 8; i++) t[i] = fmaxf(t[i], __shfl_xor_sync(0xffffffffu, t[i], 2)) * ((i & 1) ? sc1 : sc0);
#pragma unroll
        for (int i = 0; i < 8; i++) {
          const float sc = (i & 1) ? sc1 : sc0;
          l[2 * i] = ex2(fmaf(l[2 * i], sc, -t[i])); l[2 * i + 1] = ex2(fmaf(l[2 * i + 1], sc, -t[i])); t[i] = l[2 * i] + l[2 * i + 1];
        }
#pragma unroll
        for (int i = 0; i < 8; i++) t[i] += __shfl_xor_sync(0xffffffffu, t[i], 1);
#pragma unroll
        for (int i = 0; i < 8; i++) t[i] += __shfl_xor_sync(0xffffffffu, t[i], 2);
        uint32_t pf[16], pz[8];
#pragma unroll
        for (int i = 0; i < 8; i++) {
          float r; asm("rcp.approx.ftz.f32 %0, %1;" : "=f"(r) : "f"(t[i]));
          const uint32_t p = pack_bf16(l[2 * i] * r, l[2 * i + 1] * r);
          pf[2 * i] = p & ~M; pf[2 * i + 1] = p & M; pz[i] = p & P.zero;
        }
#pragma unroll
        for (int c = 0; c < 9; c++) {
          const int h = c == 8 ? 3 : c >> 1;
          float o[4] = {0, 0, 0, 0};
          mma16816(o, pf[4 * h], pz[2 * h], pf[4 * h + 1], pf[4 * h + 2], vp[2 * c], vp[2 * c + 1]);
          mma1688(o, pz[2 * h + 1], pf[4 * h + 3], v1[c]);
          if (c == 2 || c == 4 || c == 6) {
            float e[4] = {0, 0, 0, 0};
            mma16816(e, pf[4 * h - 4], pz[2 * h - 2], pf[4 * h - 3], pf[4 * h - 2], vp[2 * c], vp[2 * c + 1]);
            mma1688(e, pz[2 * h - 1], pf[4 * h - 1], v1[c]);
            const uint32_t u = pack_bf16(e[0], e[1]), v = pack_bf16(e[2], e[3]);
            qf[2 * c] = q < h ? u : pack_bf16(o[0], o[1]); qf[2 * c + 1] = q < h ? v : pack_bf16(o[2], o[3]);
          } else {
            qf[2 * c] = pack_bf16(o[0], o[1]); qf[2 * c + 1] = pack_bf16(o[2], o[3]);
          }
        }
        {
          uint32_t x = 0;
#pragma unroll
          for (int i = 0; i < 18; i += 2) x |= qf[i];
          bar_arrive(NB_ORD1 - wg + (x & P.zero), 256);
        }
        store_own(qf, sb, OFF_O, j, tid);
        hint_post(hint);
        load_own(xr, sb, OFF_X2, j);
      }
      TS(4 + L * 20);
      {
        hint_wait(hint, hint_target(L * 7));
        TS(5 + L * 20);
        load_frags<N_WO>(a, sb, OFF_O, tid_());
        float acc[36];
        if (wg == 0) bar_sync(NB_ORD0, 256);
        load_frags<N_UP, N_WO>(a, sb, OFF_O, tid_());
        TS(19 + L * 20);
        mma_pass<72, PS_WO, 6, 256, D_WO, false>(acc, a, DESC_Q, 0, rel, -1, sb, OFF_O);
        TS(6 + L * 20);
#pragma unroll
        for (int c = 0; c < 9; c++) {
          xr[2 * c] = bf2_add(xr[2 * c], pack_bf16(acc[4 * c], acc[4 * c + 1]));
          xr[2 * c + 1] = bf2_add(xr[2 * c + 1], pack_bf16(acc[4 * c + 2], acc[4 * c + 3]));
        }
        store_own(xr, sb, L * 3 * TILE, j, tid_());
        RowStats rs;
        rs.add<18>(xr);
        rs.store(sb, L * 4096 + j * 128, tid_());
        hint_post(hint);
      }
      TS(16 + L * 20);
      hint_wait(hint, hint_target(L * 7 + 1));
      TS(15 + L * 20);
      gather_ln<4 * D_T0>(a, sb, L * 3 * TILE, L * 4096, m0, m1, r0, r1, P.zero);
      TS(7 + L * 20);
      const uint32_t hb = OFF_H + j * 24576;
      {
        float ka0, kb0, kc0, ka1, kb1, kc1;
        float acc[64];
        uint32_t hf[16];
        auto geglu = [&](auto chains, uint32_t hsm) {
          constexpr int CH = decltype(chains)::value & 15;
          float r[32];
#pragma unroll
          for (int e = 0; e < 32; e++) {
            float x = acc[e];
            if (e >= CH) x = __uint_as_float(__float_as_uint(x) ^ (__float_as_uint(r[e - CH]) & P.zero));
            if (decltype(chains)::value > 15 && e < 20) {
              const uint32_t ad = (e < 8 ? slot_addr(12) + e * 2048 + wg * 8192 : slot_addr(7 + (e >> 2)) + (e & 3) * 2048) + hsm;
              lds128(&a[48 + 4 * e], e >= CH ? ad ^ (__float_as_uint(r[e - CH]) & P.zero) : ad);
            }
            const bool hi = e & 2;
            float t = x * fmaf(x * x, hi ? kb1 : kb0, hi ? ka1 : ka0);
            asm("tanh.approx.f32 %0, %0;" : "+f"(t));
            const float u = x * acc[32 + e] * (hi ? kc1 : kc0);
            r[e] = fmaf(u, t, u);
            if (e & 1) hf[e >> 1] = pack_bf16(r[e - 1], r[e]);
          }
        };
        if (wg == 1) bar_sync(NB_ORD1, 256);
        mma_pass<128, PS_FF, 4, 2048, D_T0, true>(acc, a, DESC_SW128, 1, rel, NB_ORD1 - wg, sb, L * 3 * TILE, 0, m0, m1);
        if (tid_() == 0) mbar_arrive(bar_empty(13));
        TS(8 + L * 20);
        r0 = ln_rstd(r0, acc[0], P.zero); r1 = ln_rstd(r1, acc[0], P.zero);
        ka0 = 0.7978845608028654f * r0; kb0 = 0.035677408136300125f * r0 * r0 * r0; kc0 = 0.5f * r0 * r0;
        ka1 = 0.7978845608028654f * r1; kb1 = 0.035677408136300125f * r1 * r1 * r1; kc1 = 0.5f * r1 * r1;
#pragma unroll 1
        for (int t = 0; t < 8; t++) {
          geglu(IntC<2>(), 0);
          const uint32_t t16 = tid_() * 16;
          if (t < 5) {
            const uint32_t d = (t < 2 ? slot_addr(12) + wg * SLOT + t * 8192 : slot_addr(7) + t * SLOT + wg * 8192) + t16;
#pragma unroll
            for (int i = 0; i < 4; i++)
              sts128(d + i * 2048, hf[4 * i], hf[4 * i + 1], hf[4 * i + 2], hf[4 * i + 3]);
            if (t == 4) asm volatile("fence.proxy.async.shared::cta;" ::: "memory");
          } else {
#pragma unroll
            for (int i = 0; i < 4; i++) st16(sb, hb + (t - 5) * 8192 + t16, i * 2048, hf[4 * i], hf[4 * i + 1], hf[4 * i + 2], hf[4 * i + 3]);
          }
          bar_sync(NB_ORD0 + wg, 256);
          mma_pass<128, PS_FF, 4, 2048, 0, false, true>(acc, a, DESC_SW128, t & 1, rel, NB_ORD1 - wg, sb, hb + t16, t == 7);
        }
        TS(9 + L * 20);
        const uint32_t hsm = wg * 8192 + tid_() * 16;
        geglu(IntC<16 + CH_LAST>(), hsm);
#pragma unroll
        for (int i = 0; i < 16; i++) a[128 + i] = hf[i];
      }
      TS(10 + L * 20);
      {
        const uint32_t xs = slot_addr(12) + wg * SLOT;
        auto verify = [&](int p, uint32_t t16) {
          mbar_wait(bar_full(12) + wg * 8, p & 1);
          TS(71 + L * 32 + p * 5);
          const uint32_t ta = p < 2, tb = (p & 1) ? ta : L ^ 1, nb = p ? 4 : 7, sh = p == 0;
          uint32_t m = 0;
#pragma unroll
          for (int s = 0; s < 4; s++) m |= (lds32(xs + s * 2048 + t16) ^ ta) | (lds32(xs + 8192 + ((s * 2048 + t16) >> sh)) ^ tb);
          if (p == 0) {
#pragma unroll
            for (int s = 4; s < 7; s++) m |= lds32(xs + 8192 + s * 1024 + t16 / 2) ^ tb;
          }
          if (__any_sync(0xffffffffu, m & 1)) {
#pragma unroll 1
            for (int s = 0; s < 4 + nb; s++) {
              const bool nar = sh && s >= 4;
              const uint32_t o = nar ? 4096 + s * 1024 + t16 / 2 : s * 2048 + t16;
              uint32_t v[4] = {0, 0, 0, 0};
              do {
                if (nar) ld8(v, sb, j * PSRC + o, OFF_P + 32768 - 8192);
                else ld16(v, sb, j * PSRC + (p & 1) * 16384 + o, OFF_P);
              } while (__any_sync(0xffffffffu, (v[0] ^ (s < 4 ? ta : tb)) & 1));
              sts64(xs + o, v[0], v[1]);
              if (!nar) sts64(xs + o + 8, v[2], v[3]);
            }
            asm volatile("fence.proxy.async.shared::cta;" ::: "memory");
          }
        };
        uint32_t t16 = (a[142] | a[143]) & P.zero;
#pragma unroll 1
        for (int p = 0; p < 4; p++) {
          float acc[64];
          bar_sync(NB_ORD0 + wg + (p ? 0 : t16), 256);
          TS(64 + L * 32 + p * 5);
          if (p == 0) { rel(9); rel(10); rel(11); }
          mma_pass<128, PS_FF, 4, 2048, 0, false, false>(acc, a, DESC_SW128, p & 1, rel, NB_ORD1 - wg, nullptr, 0, 0, 0, 0, 0, [&]() {
            t16 = tid_() * 16;
            if (p) verify(p - 1, t16);
          });
          TS(65 + L * 32 + p * 5);
          if (p == 1 || p == 2) add_piece<false>(acc, xs + t16);
          const uint32_t oa = ((j + (p < 3 ? 1 : 4)) & 7) * PSRC + (p & 1) * 16384 + t16;
#pragma unroll
          for (int i = 0; i < 4; i++)
            st16(sb, oa, OFF_P + i * 2048, (pack_bf16(acc[8 * i], acc[8 * i + 1]) & ~1u) | (p < 2), pack_bf16(acc[8 * i + 2], acc[8 * i + 3]),
                 pack_bf16(acc[8 * i + 4], acc[8 * i + 5]), pack_bf16(acc[8 * i + 6], acc[8 * i + 7]));
          if (p == 0) {
#pragma unroll
            for (int i = 0; i < 8; i++)
              send8(sb, j * 1024 + t16 / 2, OFF_P + 32768 + i * PSRC, xs + 15360 + t16 / 2, i, j,
                    (pack_bf16(acc[32 + 4 * i], acc[33 + 4 * i]) & ~1u) | (L ^ 1), pack_bf16(acc[34 + 4 * i], acc[35 + 4 * i]));
          } else {
            if (p == 2) add_piece<false>(acc + 32, xs + 8192 + t16);
            const uint32_t ob = ((j + (p < 3 ? 7 : 5)) & 7) * PSRC + (p & 1) * 16384 + t16, tb = p == 2 ? L ^ 1 : p < 2;
#pragma unroll
            for (int i = 4; i < 8; i++)
              st16(sb, ob, OFF_P + i * 2048, (pack_bf16(acc[8 * i], acc[8 * i + 1]) & ~1u) | tb, pack_bf16(acc[8 * i + 2], acc[8 * i + 3]),
                   pack_bf16(acc[8 * i + 4], acc[8 * i + 5]), pack_bf16(acc[8 * i + 6], acc[8 * i + 7]));
          }
          hint_post(hint);
          TS(68 + L * 32 + p * 5);
          if (p == 1) {
            float s0 = 0.f, s1 = 0.f, s2 = 0.f, s3 = 0.f;
#pragma unroll
            for (int s = 0; s < 8; s++) {
              uint32_t u, v;
              lds64(u, v, xs + 8192 + s * 1024 + t16 / 2);
              s0 += bf_lo(u); s1 += bf_hi(u); s2 += bf_lo(v); s3 += bf_hi(v);
            }
            sts64(ytail(wg * 2) + t16, pack_bf16(s0, s1), pack_bf16(s2, s3));
          }
          if (p < 3) bar_arrive(NB_FREE + wg, 160);
          TS(67 + L * 32 + p * 5);
        }
        float acc[32];
        add_piece<true>(acc, xs + t16);
        add_piece<false>(acc, xs + 8192 + t16);
        bar_arrive(NB_FREE + wg, 160);
        load_own(xr, sb, L * 3 * TILE, j);
        bar_sync(NB_ORD0 + wg, 256);
        TS(84 + L * 32);
        uint32_t t, yn[2];
        mma_pass<64, PS_FFA, 4, 2048, 0, false, false>(acc, a, DESC_SW128, 0, rel, wg ? -1 : NB_ORD1, nullptr, 0, 0, 0, 0, 0, [&]() {
          t = tid_();
          lds64(yn[0], yn[1], ytail(wg * 2) + t * 16);
          mbar_wait(bar_full(12) + wg * 8, 1);
#pragma unroll
          for (int i = 0; i < 8; i++) lds128(&a[4 * i], xs + i * 2048 + t * 16);
        });
        TS(11 + L * 20);
        while (true) {
          uint32_t m = 0;
#pragma unroll
          for (int i = 0; i < 8; i++) m |= a[4 * i];
          if (!__any_sync(0xffffffffu, m & 1)) break;
#pragma unroll
          for (int i = 0; i < 8; i++) ld16(&a[4 * i], sb, j * PSRC + t * 16, OFF_P + 16384 + i * 2048);
        }
        TS(12 + L * 20);
#pragma unroll
        for (int i = 0; i < 18; i++)
          xr[i] = bf2_add(xr[i], i < 16 ? pack_bf16(acc[2 * i] + (bf_lo(a[i]) + bf_lo(a[16 + i])), acc[2 * i + 1] + (bf_hi(a[i]) + bf_hi(a[16 + i]))) : yn[i - 16]);
        TS(18 + L * 20);
        if (L == 0) {
          store_own(xr, sb, OFF_X2, j, t);
          RowStats rs;
          rs.add<18>(xr);
          rs.store(sb, 8192 + j * 128, t);
          hint_post(hint);
        } else {
          const uint32_t l = t & 31, wb = xs + w * 512;
          if (l == 0) mbar_arrive(bar_empty(12));
          __syncwarp();
          asm volatile("barrier.cluster.arrive.relaxed.aligned;" ::: "memory");
#pragma unroll
          for (int i = 0; i < 4; i++) stsm4(wb + i * 2048 + (l & 24) * 16 + (((l & 7) ^ (i * 2 + (l >> 4))) << 4), xr[4 * i], xr[4 * i + 1], xr[4 * i + 2], xr[4 * i + 3]);
          stsm4(wb + 8192 + l * 16, xr[16], xr[17], 0, 0);
          __syncwarp();
          uint8_t* op = (uint8_t*)P.out + row_off(rb, wg, w * 32 + (l >> 3)) + j * 128 + (l & 7) * 16;
#pragma unroll
          for (int i = 0; i < 4; i++) {
            uint32_t r[4];
            lds128(r, wb + ((l & 6) << 10) + ((l & 1) * 2 + (i >> 1)) * 128 + (((((i & 1) * 4 + (l >> 3)) ^ l) & 7) << 4));
            *(uint4*)(op + i * 16 * DM) = make_uint4(r[0], r[1], r[2], r[3]);
          }
          uint32_t r[4];
          lds128(r, wb + 8192 + l * 16);
          if (l < 16) *(uint4*)((uint8_t*)P.out + row_off(rb, wg, t) + 1024 + j * 16) = make_uint4(r[0], r[1], r[2], r[3]);
        }
      }
      TS(13 + L * 20);
    }
  }
}

typedef CUresult (*EncodeFn)(CUtensorMap*, CUtensorMapDataType, cuuint32_t, void*, const cuuint64_t*, const cuuint64_t*, const cuuint32_t*,
                             const cuuint32_t*, CUtensorMapInterleave, CUtensorMapSwizzle, CUtensorMapL2promotion, CUtensorMapFloatOOBfill);

void encode(EncodeFn fn, CUtensorMap* m, const void* p, int rank, const cuuint64_t* dims, const cuuint64_t* str, const cuuint32_t* box) {
  const cuuint32_t es[3] = {1, 1, 1};
  fn(m, CU_TENSOR_MAP_DATA_TYPE_BFLOAT16, rank, const_cast<void*>(p), dims, str, box, es, CU_TENSOR_MAP_INTERLEAVE_NONE,
     CU_TENSOR_MAP_SWIZZLE_128B, CU_TENSOR_MAP_L2_PROMOTION_L2_256B, CU_TENSOR_MAP_FLOAT_OOB_FILL_NONE);
}

__global__ void probe_kernel() {}

void make_roles(uint8_t* role) {
  int cnt[8];
  cudaFuncSetAttribute(probe_kernel, cudaFuncAttributeMaxDynamicSharedMemorySize, SMEM_BYTES);
  cudaFuncSetAttribute(probe_kernel, cudaFuncAttributeNonPortableClusterSizeAllowed, 1);
  for (int r = 7; r >= 0; r--) {
    int n = 0;
    cudaLaunchConfig_t cfg = {};
    cudaLaunchAttribute at;
    at.id = cudaLaunchAttributeClusterDimension; at.val.clusterDim.x = 2 * (r < 3 ? 4 : r + 1); at.val.clusterDim.y = at.val.clusterDim.z = 1;
    cfg.gridDim = dim3(at.val.clusterDim.x); cfg.blockDim = dim3(384); cfg.dynamicSmemBytes = SMEM_BYTES; cfg.attrs = &at; cfg.numAttrs = 1;
    if (cudaOccupancyMaxActiveClusters(&n, probe_kernel, &cfg) != cudaSuccess) { cudaGetLastError(); n = r > 3 ? 8 : 8 + cnt[7]; }
    cnt[r] = r > 3 ? n : n - cnt[7];
  }
  int key[64], c = 0, total = 0, seg = 0;
  for (int r = 0; r < 8; r++) total += cnt[r];
  for (; c < 64 - total; c++) key[c] = -1;
  for (int r = 0; r < 8; r++) {
    if (r && cnt[r] != cnt[r - 1]) seg++;
    for (int i = 0; i < cnt[r] && c < 64; i++) key[c++] = seg * 16 + i;
  }
  int order[64], n = 0;
  bool used[64] = {};
  for (int pass = 0; pass < 2; pass++)
    for (int i = 0; i < 64; i++) {
      if (used[i]) continue;
      int m[4], k = 0;
      for (int q = i; q < 64 && k < 4; q++) if (!used[q] && (pass || (key[q] == key[i] && key[i] >= 0))) m[k++] = q;
      if (k == 4) for (int q = 0; q < 4; q++) { used[m[q]] = true; order[n++] = m[q]; }
    }
  for (int i = 0; i < 64; i++) role[order[i]] = (uint8_t)(((i >> 2) & 7) << 3 | (i >> 5) << 2 | (i & 3));
}

}

extern "C" void kernel_launch(void* const* d_in, const int* in_sizes, int n_in, void* d_out, int out_size) {
  (void)in_sizes; (void)n_in; (void)out_size;
  Params P = {};
  P.wqkv = (const __nv_bfloat16*)d_in[1]; P.wo = (const __nv_bfloat16*)d_in[2];
  P.out = (__nv_bfloat16*)d_out; P.zero = 0;
  cudaGetSymbolAddress((void**)&P.scr, g_scr);
  make_roles(P.role);
  void* fnp = nullptr; cudaDriverEntryPointQueryResult qr;
  cudaGetDriverEntryPoint("cuTensorMapEncodeTiled", &fnp, cudaEnableDefault, &qr);
  EncodeFn fn = (EncodeFn)fnp;
  CUtensorMap mx, mg, mu, md;
  { const cuuint64_t dims[3] = {DM, SEQ / 2, 2}, str[2] = {DM * 4, DM * 2}; const cuuint32_t box[3] = {64, 64, 2}; encode(fn, &mx, d_in[0], 3, dims, str, box); }
  { const cuuint64_t dims[2] = {DFF, DM}, str[1] = {DFF * 2}; const cuuint32_t box[2] = {64, 64}; encode(fn, &mg, d_in[4], 2, dims, str, box); encode(fn, &mu, d_in[5], 2, dims, str, box); }
  { const cuuint64_t dims[2] = {DM, DFF}, str[1] = {DM * 2}; const cuuint32_t box[2] = {64, 64}; encode(fn, &md, d_in[6], 2, dims, str, box); }
  cudaFuncSetAttribute(fused_kernel, cudaFuncAttributeMaxDynamicSharedMemorySize, SMEM_BYTES);
  fused_kernel<<<128, 384, SMEM_BYTES, cudaStreamPerThread>>>(P, mx, mg, mu, md);
}
```

```cpp
#include <cuda_runtime.h>
#include <cuda_bf16.h>
#include <cuda.h>
#include <stdint.h>

#define TIMING 0
#define TRACE 0

namespace {

constexpr int SEQ = 2048, DM = 576, DFF = 4608;
constexpr int KV_S1 = 4;
constexpr int KV_LEAD = 5;
constexpr int D_KV = 6, D_WO = 3, D_T0 = 5;
constexpr int N_UP = 26, N_WO = 12;
constexpr int PF_AHEAD = 2;
constexpr int CH_LAST = 3;
constexpr uint32_t SB = 1024;
constexpr uint32_t SLOT = 16384;
constexpr uint32_t PSLOT = 13824;
constexpr uint32_t BARS = SB + 14 * SLOT;
constexpr int SMEM_BYTES = 14 * SLOT + 256 + 2560 + (TRACE ? 256 : 0);
__host__ __device__ constexpr uint32_t slot_addr(int s) { return SB + s * SLOT; }
__host__ __device__ constexpr uint32_t bar_full(int s) { return BARS + 8 * s; }
__host__ __device__ constexpr uint32_t bar_empty(int s) { return BARS + 128 + 8 * s; }
enum { NB_ORD0 = 1, NB_ORD1 = 2, NB_WG = 3  , NB_HALO = 5  , NB_FREE = 7  , NB_PUB = 9   };
constexpr uint32_t SM_EPOCH = BARS + 120;
__host__ __device__ constexpr uint32_t ytail(uint32_t k) { return k < 3 ? slot_addr(9) + PSLOT + k * SLOT : BARS + 256; }
constexpr uint32_t KSTG = 9 * 1152;

constexpr uint32_t TILE = 36 * 2048;
constexpr uint32_t OFF_X1 = 0  , OFF_O = TILE, OFF_X2 = 2 * TILE, OFF_ST = 4 * TILE  ;
constexpr uint32_t PSRC = 2 * 16384 + 7 * 1024;
constexpr uint32_t OFF_P = OFF_ST + 3 * 4096, OFF_HALO = OFF_P + 8 * PSRC  , OFF_HINT = OFF_HALO + 2 * 8 * 3072  ,
                   OFF_H = OFF_HINT + 16 * 128  , STRM = OFF_H + 8 * 24576;
constexpr uint32_t OFF_WPACK = 32 * STRM, OFF_FLAGS = OFF_WPACK + 8 * 24 * PSLOT;
__device__ __align__(1024) uint8_t g_scr[OFF_FLAGS + (8 + 64 + 128) * 32];

__device__ __forceinline__ uint32_t smem_u32(const void* p) { return (uint32_t)__cvta_generic_to_shared(p); }
extern __shared__ __align__(1024) uint8_t smem_raw[];
__device__ __forceinline__ uint32_t win() { return (blockIdx.x & 1) << 24; }
#define SA(A, W) ".reg .u32 sa;\nadd.u32 sa, " A ", " W ";\n"
__device__ __forceinline__ void mbar_init(uint32_t bar, uint32_t cnt) { asm volatile("{\n" SA("%0", "%2") "mbarrier.init.shared::cta.b64 [sa], %1;\n}" ::"r"(bar), "r"(cnt), "r"(win())); }
__device__ __forceinline__ void mbar_arrive(uint32_t bar) { asm volatile("{\n" SA("%0", "%1") "mbarrier.arrive.shared::cta.b64 _, [sa];\n}" ::"r"(bar), "r"(win()) : "memory"); }
__device__ __forceinline__ uint32_t lds32(uint32_t a) { uint32_t v; asm volatile("{\n" SA("%1", "%2") "ld.shared.u32 %0, [sa];\n}" : "=r"(v) : "r"(a), "r"(win()) : "memory"); return v; }
__device__ __forceinline__ void lds64(uint32_t& x, uint32_t& y, uint32_t a) { asm volatile("{\n" SA("%2", "%3") "ld.shared.v2.u32 {%0,%1}, [sa];\n}" : "=r"(x), "=r"(y) : "r"(a), "r"(win()) : "memory"); }
__device__ __forceinline__ void lds128(uint32_t* v, uint32_t a) {
  asm volatile("{\n" SA("%4", "%5") "ld.shared.v4.u32 {%0,%1,%2,%3}, [sa];\n}" : "=r"(v[0]), "=r"(v[1]), "=r"(v[2]), "=r"(v[3]) : "r"(a), "r"(win()) : "memory");
}
__device__ __forceinline__ void stsm4(uint32_t a, uint32_t x, uint32_t y, uint32_t z, uint32_t w) {
  asm volatile("{\n" SA("%0", "%5") "stmatrix.sync.aligned.m8n8.x4.shared.b16 [sa], {%1,%2,%3,%4};\n}" ::"r"(a), "r"(x), "r"(y), "r"(z), "r"(w), "r"(win()) : "memory");
}
__device__ __forceinline__ void ldsm4(uint32_t* v, uint32_t a) {
  asm volatile("{\n" SA("%4", "%5") "ldmatrix.sync.aligned.m8n8.x4.shared.b16 {%0,%1,%2,%3}, [sa];\n}" : "=r"(v[0]), "=r"(v[1]), "=r"(v[2]), "=r"(v[3]) : "r"(a), "r"(win()) : "memory");
}
__device__ __forceinline__ void ldsm4t(uint32_t* v, uint32_t a) {
  asm volatile("{\n" SA("%4", "%5") "ldmatrix.sync.aligned.m8n8.x4.trans.shared.b16 {%0,%1,%2,%3}, [sa];\n}" : "=r"(v[0]), "=r"(v[1]), "=r"(v[2]), "=r"(v[3]) : "r"(a), "r"(win()) : "memory");
}
__device__ __forceinline__ void sts32(uint32_t a, uint32_t x) { asm volatile("{\n" SA("%0", "%2") "st.shared.u32 [sa], %1;\n}" ::"r"(a), "r"(x), "r"(win()) : "memory"); }
__device__ __forceinline__ void sts64(uint32_t a, uint32_t x, uint32_t y) { asm volatile("{\n" SA("%0", "%3") "st.shared.v2.u32 [sa], {%1,%2};\n}" ::"r"(a), "r"(x), "r"(y), "r"(win()) : "memory"); }
__device__ __forceinline__ void sts128(uint32_t a, uint32_t x, uint32_t y, uint32_t z, uint32_t w) {
  asm volatile("{\n" SA("%0", "%5") "st.shared.v4.u32 [sa], {%1,%2,%3,%4};\n}" ::"r"(a), "r"(x), "r"(y), "r"(z), "r"(w), "r"(win()) : "memory");
}
__device__ __forceinline__ void mbar_wait(uint32_t bar, uint32_t parity) {
  asm volatile("{\n.reg .pred p;\n" SA("%0", "%2") "LAB_WAIT:\nmbarrier.try_wait.parity.shared::cta.b64 p, [sa], %1;\n@!p bra LAB_WAIT;\n}" ::"r"(bar), "r"(parity), "r"(win()) : "memory");
}
__device__ __forceinline__ void timed_wait(uint32_t bar, uint32_t par) {
  asm volatile("{\n.reg .pred p;\n.reg .u64 t0, t1;\nmov.u64 t0, %%globaltimer;\nLAB_WD:\n"
               "mbarrier.try_wait.parity.shared::cta.b64 p, [%0], %1, 100000;\n@p bra LAB_OK;\n"
               "mov.u64 t1, %%globaltimer;\nsub.u64 t1, t1, t0;\nsetp.lt.u64 p, t1, 2000000000;\n@p bra LAB_WD;\ntrap;\nLAB_OK:\n}" ::"r"(bar + win()), "r"(par) : "memory");
}
__device__ __forceinline__ void flag_wait(const unsigned* flag, unsigned target) {
  asm volatile("{\n.reg .pred p;\n.reg .u32 v;\nLAB_WAIT:\nld.acquire.gpu.global.u32 v, [%0];\nsub.u32 v, v, %1;\n"
               "setp.lt.s32 p, v, 0;\nvote.sync.any.pred p, p, 0xffffffff;\n@p nanosleep.u32 100;\n@p bra LAB_WAIT;\n}" ::"l"(flag), "r"(target) : "memory");
}
__device__ __forceinline__ void hint_post(uint8_t* p) {
  __syncwarp();
  asm volatile("{\n.reg .pred p;\nelect.sync _|p, 0xffffffff;\n@p red.relaxed.gpu.global.add.u32 [%0], 1;\n}" ::"l"(p) : "memory");
}
__device__ __forceinline__ void hint_wait(const uint8_t* p, uint32_t target) {
  asm volatile("{\n.reg .pred p;\n.reg .u32 v;\nLAB_WAIT:\nld.relaxed.gpu.global.u32 v, [%0];\nsub.u32 v, v, %1;\n"
               "setp.lt.s32 p, v, 0;\nvote.sync.any.pred p, p, 0xffffffff;\n@p bra LAB_WAIT;\n}" ::"l"(p), "r"(target) : "memory");
}
__device__ __forceinline__ void flag_signal(unsigned* flag) { asm volatile("red.release.gpu.global.add.u32 [%0], 1;" ::"l"(flag) : "memory"); }
struct Rel {
  bool on; uint32_t base;
  uint32_t tr;
  __device__ __forceinline__ void operator()(int s) const {
    if (on) asm volatile("{\n" SA("%0", "%1") "mbarrier.arrive.shared::cluster.b64 _, [sa];\n}" ::"r"(bar_empty(s)), "r"(base) : "memory");
  }
};
__device__ __forceinline__ uint32_t cta_window(uint32_t rank) { uint32_t a; asm("mapa.shared::cluster.u32 %0, %1, %2;" : "=r"(a) : "r"(0), "r"(rank)); return a; }
#define ELECT ".reg .pred e;\nelect.sync _|e, 0xffffffff;\n"
__device__ __forceinline__ void w_expect_tx(uint32_t bar, uint32_t bytes) {
  asm volatile("{\n" ELECT "@e mbarrier.arrive.expect_tx.shared::cta.b64 _, [%0], %1;\n}" ::"r"(bar), "r"(bytes) : "memory");
}
__device__ __forceinline__ void w_tma_2d_mc(uint32_t dst, const CUtensorMap* m, int c0, int c1, uint32_t bar) {
  asm volatile("{\n" ELECT "@e cp.async.bulk.tensor.2d.shared::cluster.global.mbarrier::complete_tx::bytes.multicast::cluster [%0], [%1, {%3, %4}], [%2], %5;\n}"
               ::"r"(dst), "l"(m), "r"(bar), "r"(c0), "r"(c1), "h"((uint16_t)3) : "memory");
}
__device__ __forceinline__ void w_bulk_load_mc(uint32_t dst, const void* src, uint32_t bytes, uint32_t bar) {
  asm volatile("{\n" ELECT "@e cp.async.bulk.shared::cluster.global.mbarrier::complete_tx::bytes.multicast::cluster [%0], [%1], %2, [%3], %4;\n}"
               ::"r"(dst), "l"(src), "r"(bytes), "r"(bar), "h"((uint16_t)3) : "memory");
}
__device__ __forceinline__ void w_bulk_load(uint32_t dst, const void* src, uint32_t bytes, uint32_t bar) {
  asm volatile("{\n" ELECT "@e cp.async.bulk.shared::cluster.global.mbarrier::complete_tx::bytes [%0], [%1], %2, [%3];\n}" ::"r"(dst), "l"(src), "r"(bytes), "r"(bar) : "memory");
}
__device__ __forceinline__ void w_l2_prefetch(const void* src, uint32_t bytes) { asm volatile("{\n" ELECT "@e cp.async.bulk.prefetch.L2.global [%0], %1;\n}" ::"l"(src), "r"(bytes) : "memory"); }
__device__ __forceinline__ void w_tma_prefetch(const CUtensorMap* m, int c0, int c1) {
  asm volatile("{\n" ELECT "@e cp.async.bulk.prefetch.tensor.2d.L2.global [%0, {%1, %2}];\n}" ::"l"(m), "r"(c0), "r"(c1) : "memory");
}
__device__ __forceinline__ void w_tma_3d(uint32_t dst, const CUtensorMap* m, int c0, int c1, int c2, uint32_t bar) {
  asm volatile("{\n" ELECT "@e cp.async.bulk.tensor.3d.shared::cluster.global.mbarrier::complete_tx::bytes [%0], [%1, {%3, %4, %5}], [%2];\n}"
               ::"r"(dst), "l"(m), "r"(bar), "r"(c0), "r"(c1), "r"(c2) : "memory");
}
__device__ __forceinline__ void wg_fence() { asm volatile("wgmma.fence.sync.aligned;" ::: "memory"); }
__device__ __forceinline__ void wg_commit() { asm volatile("wgmma.commit_group.sync.aligned;" ::: "memory"); }
template <int N> __device__ __forceinline__ void wg_wait() { asm volatile("wgmma.wait_group.sync.aligned %0;" ::"n"(N) : "memory"); }
__device__ __forceinline__ void bar_sync(int id, int n) { asm volatile("bar.sync %0, %1;" ::"r"(id), "r"(n) : "memory"); }
__device__ __forceinline__ void bar_arrive(int id, int n) { asm volatile("bar.arrive %0, %1;" ::"r"(id), "r"(n) : "memory"); }
__device__ __forceinline__ uint32_t pack_bf16(float lo, float hi) { uint32_t r; asm("cvt.rn.bf16x2.f32 %0, %1, %2;" : "=r"(r) : "f"(hi), "f"(lo)); return r; }
__device__ __forceinline__ float bf_lo(uint32_t w) { return __uint_as_float(w << 16); }
__device__ __forceinline__ float bf_hi(uint32_t w) { return __uint_as_float(w & 0xffff0000u); }
__device__ __forceinline__ float bf_round(float x) { return bf_lo(pack_bf16(x, 0.f)); }
__device__ __forceinline__ uint32_t bf2_sub(uint32_t a, uint32_t b) { uint32_t r; asm("sub.rn.bf16x2 %0, %1, %2;" : "=r"(r) : "r"(a), "r"(b)); return r; }
__device__ __forceinline__ uint32_t bf2_add(uint32_t a, uint32_t b) { uint32_t r; asm("add.rn.bf16x2 %0, %1, %2;" : "=r"(r) : "r"(a), "r"(b)); return r; }
#define GADDR(B, O, I) "cvt.u64.u32 ad, " O ";\nadd.u64 ad, ad, " B ";\nadd.u64 ad, ad, " I ";\n"
__device__ __forceinline__ void ld16(uint32_t* v, const uint8_t* ub, uint32_t off, uint32_t imm) {
  asm volatile("{\n.reg .b128 z;\n.reg .b64 x, y, ad;\n" GADDR("%4", "%5", "%6") "ld.relaxed.gpu.global.b128 z, [ad];\n"
               "mov.b128 {x, y}, z;\nmov.b64 {%0,%1}, x;\nmov.b64 {%2,%3}, y;\n}"
               : "=r"(v[0]), "=r"(v[1]), "=r"(v[2]), "=r"(v[3]) : "l"(ub), "r"(off), "l"((uint64_t)imm) : "memory");
}
__device__ __forceinline__ void ld8(uint32_t* v, const uint8_t* ub, uint32_t off, uint32_t imm) {
  asm volatile("{\n.reg .b64 x, ad;\n" GADDR("%2", "%3", "%4") "ld.relaxed.gpu.global.b64 x, [ad];\nmov.b64 {%0,%1}, x;\n}"
               : "=r"(v[0]), "=r"(v[1]) : "l"(ub), "r"(off), "l"((uint64_t)imm) : "memory");
}
__device__ __forceinline__ void st16(uint8_t* ub, uint32_t off, uint32_t imm, uint32_t a, uint32_t b, uint32_t c, uint32_t d) {
  asm volatile("{\n.reg .b128 z;\n.reg .b64 x, y, ad;\n" GADDR("%0", "%1", "%2") "mov.b64 x, {%3,%4};\nmov.b64 y, {%5,%6};\nmov.b128 z, {x, y};\n"
               "st.relaxed.gpu.global.b128 [ad], z;\n}" ::"l"(ub), "r"(off), "l"((uint64_t)imm), "r"(a), "r"(b), "r"(c), "r"(d) : "memory");
}
__device__ __forceinline__ void st8(uint8_t* ub, uint32_t off, uint32_t imm, uint32_t a, uint32_t b) {
  asm volatile("{\n.reg .b64 x, ad;\n" GADDR("%0", "%1", "%2") "mov.b64 x, {%3,%4};\nst.relaxed.gpu.global.b64 [ad], x;\n}"
               ::"l"(ub), "r"(off), "l"((uint64_t)imm), "r"(a), "r"(b) : "memory");
}
__device__ __forceinline__ void send8(uint8_t* ub, uint32_t off, uint32_t imm, uint32_t sm, int i, int j, uint32_t a, uint32_t b) {
  asm volatile("{\n.reg .pred p, q, e;\n.reg .b64 x, ad;\n" SA("%3", "%8") GADDR("%0", "%1", "%2")
               "setp.lt.s32 p, %4, %5;\nsetp.gt.s32 q, %4, %5;\nsetp.eq.s32 e, %4, %5;\nmov.b64 x, {%6,%7};\n"
               "@p st.relaxed.gpu.global.b64 [ad+-1024], x;\n@q st.relaxed.gpu.global.b64 [ad], x;\n@e st.shared.v2.u32 [sa], {%6,%7};\n}"
               ::"l"(ub), "r"(off), "l"((uint64_t)imm), "r"(sm), "r"(i), "r"(j), "r"(a), "r"(b), "r"(win()) : "memory");
}
__device__ __forceinline__ uint4 ldg_line(const void* p) {
  uint4 v; asm volatile("ld.global.nc.L2::128B.v4.u32 {%0,%1,%2,%3}, [%4];" : "=r"(v.x), "=r"(v.y), "=r"(v.z), "=r"(v.w) : "l"(p)); return v;
}
__device__ __forceinline__ uint32_t tid_() { uint32_t t; asm volatile("mov.u32 %0, %%tid.x;" : "=r"(t)); return t & 127; }
__device__ __forceinline__ uint32_t token() { uint32_t c; asm volatile("mov.u32 %0, %%clock;" : "=r"(c) :: "memory"); return c | 1; }
__device__ __forceinline__ uint32_t nz(uint32_t w) { return w ? w : 0x8000u; }
__device__ __forceinline__ void mma16816(float (&c)[4], uint32_t a0, uint32_t a1, uint32_t a2, uint32_t a3, uint32_t b0, uint32_t b1) {
  asm("mma.sync.aligned.m16n8k16.row.col.f32.bf16.bf16.f32 {%0,%1,%2,%3}, {%4,%5,%6,%7}, {%8,%9}, {%0,%1,%2,%3};"
               : "+f"(c[0]), "+f"(c[1]), "+f"(c[2]), "+f"(c[3]) : "r"(a0), "r"(a1), "r"(a2), "r"(a3), "r"(b0), "r"(b1));
}
__device__ __forceinline__ void mma1688(float (&c)[4], uint32_t a0, uint32_t a1, uint32_t b0) {
  asm("mma.sync.aligned.m16n8k8.row.col.f32.bf16.bf16.f32 {%0,%1,%2,%3}, {%4,%5}, {%6}, {%0,%1,%2,%3};"
               : "+f"(c[0]), "+f"(c[1]), "+f"(c[2]), "+f"(c[3]) : "r"(a0), "r"(a1), "r"(b0));
}
__device__ __forceinline__ float ex2(float x) { float r; asm("ex2.approx.ftz.f32 %0, %1;" : "=f"(r) : "f"(x)); return r; }

__device__ __forceinline__ void wgmma_rs_n64(float (&d)[32], uint32_t a0, uint32_t a1, uint32_t a2, uint32_t a3, uint64_t desc, int scale_d) {
  asm volatile("{\n.reg .pred p;\nsetp.ne.b32 p, %37, 0;\n"
    "wgmma.mma_async.sync.aligned.m64n64k16.f32.bf16.bf16 "
    "{%0, %1, %2, %3, %4, %5, %6, %7, %8, %9, %10, %11, %12, %13, %14, %15, %16, %17, %18, %19, %20, %21, %22, %23, %24, %25, %26, %27, %28, %29, %30, %31}, "
    "{%32, %33, %34, %35}, %36, p, 1, 1, 1;\n}\n"
    : "+f"(d[0]), "+f"(d[1]), "+f"(d[2]), "+f"(d[3]), "+f"(d[4]), "+f"(d[5]), "+f"(d[6]), "+f"(d[7]), "+f"(d[8]), "+f"(d[9]), "+f"(d[10]), "+f"(d[11]), "+f"(d[12]), "+f"(d[13]), "+f"(d[14]), "+f"(d[15]), "+f"(d[16]), "+f"(d[17]), "+f"(d[18]), "+f"(d[19]), "+f"(d[20]), "+f"(d[21]), "+f"(d[22]), "+f"(d[23]), "+f"(d[24]), "+f"(d[25]), "+f"(d[26]), "+f"(d[27]), "+f"(d[28]), "+f"(d[29]), "+f"(d[30]), "+f"(d[31])
    : "r"(a0), "r"(a1), "r"(a2), "r"(a3), "l"(desc), "r"(scale_d));
}

__device__ __forceinline__ void wgmma_rs_n72(float (&d)[36], uint32_t a0, uint32_t a1, uint32_t a2, uint32_t a3, uint64_t desc, int scale_d) {
  asm volatile("{\n.reg .pred p;\nsetp.ne.b32 p, %41, 0;\n"
    "wgmma.mma_async.sync.aligned.m64n72k16.f32.bf16.bf16 "
    "{%0, %1, %2, %3, %4, %5, %6, %7, %8, %9, %10, %11, %12, %13, %14, %15, %16, %17, %18, %19, %20, %21, %22, %23, %24, %25, %26, %27, %28, %29, %30, %31, %32, %33, %34, %35}, "
    "{%36, %37, %38, %39}, %40, p, 1, 1, 1;\n}\n"
    : "+f"(d[0]), "+f"(d[1]), "+f"(d[2]), "+f"(d[3]), "+f"(d[4]), "+f"(d[5]), "+f"(d[6]), "+f"(d[7]), "+f"(d[8]), "+f"(d[9]), "+f"(d[10]), "+f"(d[11]), "+f"(d[12]), "+f"(d[13]), "+f"(d[14]), "+f"(d[15]), "+f"(d[16]), "+f"(d[17]), "+f"(d[18]), "+f"(d[19]), "+f"(d[20]), "+f"(d[21]), "+f"(d[22]), "+f"(d[23]), "+f"(d[24]), "+f"(d[25]), "+f"(d[26]), "+f"(d[27]), "+f"(d[28]), "+f"(d[29]), "+f"(d[30]), "+f"(d[31]), "+f"(d[32]), "+f"(d[33]), "+f"(d[34]), "+f"(d[35])
    : "r"(a0), "r"(a1), "r"(a2), "r"(a3), "l"(desc), "r"(scale_d));
}

__device__ __forceinline__ void wgmma_rs_n128(float (&d)[64], uint32_t a0, uint32_t a1, uint32_t a2, uint32_t a3, uint64_t desc, int scale_d) {
  asm volatile("{\n.reg .pred p;\nsetp.ne.b32 p, %69, 0;\n"
    "wgmma.mma_async.sync.aligned.m64n128k16.f32.bf16.bf16 "
    "{%0, %1, %2, %3, %4, %5, %6, %7, %8, %9, %10, %11, %12, %13, %14, %15, %16, %17, %18, %19, %20, %21, %22, %23, %24, %25, %26, %27, %28, %29, %30, %31, %32, %33, %34, %35, %36, %37, %38, %39, %40, %41, %42, %43, %44, %45, %46, %47, %48, %49, %50, %51, %52, %53, %54, %55, %56, %57, %58, %59, %60, %61, %62, %63}, "
    "{%64, %65, %66, %67}, %68, p, 1, 1, 1;\n}\n"
    : "+f"(d[0]), "+f"(d[1]), "+f"(d[2]), "+f"(d[3]), "+f"(d[4]), "+f"(d[5]), "+f"(d[6]), "+f"(d[7]), "+f"(d[8]), "+f"(d[9]), "+f"(d[10]), "+f"(d[11]), "+f"(d[12]), "+f"(d[13]), "+f"(d[14]), "+f"(d[15]), "+f"(d[16]), "+f"(d[17]), "+f"(d[18]), "+f"(d[19]), "+f"(d[20]), "+f"(d[21]), "+f"(d[22]), "+f"(d[23]), "+f"(d[24]), "+f"(d[25]), "+f"(d[26]), "+f"(d[27]), "+f"(d[28]), "+f"(d[29]), "+f"(d[30]), "+f"(d[31]), "+f"(d[32]), "+f"(d[33]), "+f"(d[34]), "+f"(d[35]), "+f"(d[36]), "+f"(d[37]), "+f"(d[38]), "+f"(d[39]), "+f"(d[40]), "+f"(d[41]), "+f"(d[42]), "+f"(d[43]), "+f"(d[44]), "+f"(d[45]), "+f"(d[46]), "+f"(d[47]), "+f"(d[48]), "+f"(d[49]), "+f"(d[50]), "+f"(d[51]), "+f"(d[52]), "+f"(d[53]), "+f"(d[54]), "+f"(d[55]), "+f"(d[56]), "+f"(d[57]), "+f"(d[58]), "+f"(d[59]), "+f"(d[60]), "+f"(d[61]), "+f"(d[62]), "+f"(d[63])
    : "r"(a0), "r"(a1), "r"(a2), "r"(a3), "l"(desc), "r"(scale_d));
}

__device__ __forceinline__ void wgmma_rs_n144(float (&d)[72], uint32_t a0, uint32_t a1, uint32_t a2, uint32_t a3, uint64_t desc, int scale_d) {
  asm volatile("{\n.reg .pred p;\nsetp.ne.b32 p, %77, 0;\n"
    "wgmma.mma_async.sync.aligned.m64n144k16.f32.bf16.bf16 "
    "{%0, %1, %2, %3, %4, %5, %6, %7, %8, %9, %10, %11, %12, %13, %14, %15, %16, %17, %18, %19, %20, %21, %22, %23, %24, %25, %26, %27, %28, %29, %30, %31, %32, %33, %34, %35, %36, %37, %38, %39, %40, %41, %42, %43, %44, %45, %46, %47, %48, %49, %50, %51, %52, %53, %54, %55, %56, %57, %58, %59, %60, %61, %62, %63, %64, %65, %66, %67, %68, %69, %70, %71}, "
    "{%72, %73, %74, %75}, %76, p, 1, 1, 1;\n}\n"
    : "+f"(d[0]), "+f"(d[1]), "+f"(d[2]), "+f"(d[3]), "+f"(d[4]), "+f"(d[5]), "+f"(d[6]), "+f"(d[7]), "+f"(d[8]), "+f"(d[9]), "+f"(d[10]), "+f"(d[11]), "+f"(d[12]), "+f"(d[13]), "+f"(d[14]), "+f"(d[15]), "+f"(d[16]), "+f"(d[17]), "+f"(d[18]), "+f"(d[19]), "+f"(d[20]), "+f"(d[21]), "+f"(d[22]), "+f"(d[23]), "+f"(d[24]), "+f"(d[25]), "+f"(d[26]), "+f"(d[27]), "+f"(d[28]), "+f"(d[29]), "+f"(d[30]), "+f"(d[31]), "+f"(d[32]), "+f"(d[33]), "+f"(d[34]), "+f"(d[35]), "+f"(d[36]), "+f"(d[37]), "+f"(d[38]), "+f"(d[39]), "+f"(d[40]), "+f"(d[41]), "+f"(d[42]), "+f"(d[43]), "+f"(d[44]), "+f"(d[45]), "+f"(d[46]), "+f"(d[47]), "+f"(d[48]), "+f"(d[49]), "+f"(d[50]), "+f"(d[51]), "+f"(d[52]), "+f"(d[53]), "+f"(d[54]), "+f"(d[55]), "+f"(d[56]), "+f"(d[57]), "+f"(d[58]), "+f"(d[59]), "+f"(d[60]), "+f"(d[61]), "+f"(d[62]), "+f"(d[63]), "+f"(d[64]), "+f"(d[65]), "+f"(d[66]), "+f"(d[67]), "+f"(d[68]), "+f"(d[69]), "+f"(d[70]), "+f"(d[71])
    : "r"(a0), "r"(a1), "r"(a2), "r"(a3), "l"(desc), "r"(scale_d));
}

template <int N> struct WG;
template <> struct WG<64>  { static __device__ __forceinline__ void f(float (&d)[32], const uint32_t* a, uint64_t ds, int s) { wgmma_rs_n64(d, a[0], a[1], a[2], a[3], ds, s); } };
template <> struct WG<72>  { static __device__ __forceinline__ void f(float (&d)[36], const uint32_t* a, uint64_t ds, int s) { wgmma_rs_n72(d, a[0], a[1], a[2], a[3], ds, s); } };
template <> struct WG<128> { static __device__ __forceinline__ void f(float (&d)[64], const uint32_t* a, uint64_t ds, int s) { wgmma_rs_n128(d, a[0], a[1], a[2], a[3], ds, s); } };
template <> struct WG<144> { static __device__ __forceinline__ void f(float (&d)[72], const uint32_t* a, uint64_t ds, int s) { wgmma_rs_n144(d, a[0], a[1], a[2], a[3], ds, s); } };

constexpr uint64_t DESC_SW128 = ((uint64_t)(8192 >> 4) << 16) | ((uint64_t)(1024 >> 4) << 32) | (1ull << 62);
constexpr uint64_t DESC_KV = ((uint64_t)(128 >> 4) << 16) | ((uint64_t)(768 >> 4) << 32);
constexpr uint64_t DESC_Q = ((uint64_t)(128 >> 4) << 16) | ((uint64_t)(1536 >> 4) << 32);

template <int V> struct IntC { static constexpr int value = V; };
enum { PS_KV, PS_Q, PS_WO, PS_FF, PS_FFA   };
template <int PS> __host__ __device__ constexpr int pass_slot(int i) {
  return PS == PS_KV ? (i < 3 ? 9 + i : i - 3) : PS == PS_WO ? 6 + i : i;
}

__device__ __forceinline__ void load_frag(uint32_t (&a)[144], int i, const uint8_t* sb, uint32_t uo, uint32_t t) {
  if (i < 32) ld16(&a[4 * i], sb, uo + t * 16, i * 2048);
  else { ld8(&a[4 * i], sb, uo + t * 8, i * 2048); ld8(&a[4 * i + 2], sb, uo + t * 8, i * 2048 + 1024); }
}
__device__ __forceinline__ void store_own(const uint32_t (&y)[18], uint8_t* sb, uint32_t uo, int j, uint32_t t) {
#pragma unroll
  for (int i = 0; i < 4; i++) st16(sb, uo + j * 8192 + t * 16, i * 2048, nz(y[4 * i]), y[4 * i + 1], y[4 * i + 2], y[4 * i + 3]);
  st8(sb, uo + j * 1024 + t * 8, 65536, nz(y[16]), y[17]);
}
__device__ __forceinline__ void load_own(uint32_t* y, const uint8_t* sb, uint32_t uo, int j) {
  const uint32_t t = tid_();
#pragma unroll
  for (int i = 0; i < 4; i++) ld16(&y[4 * i], sb, uo + j * 8192 + t * 16, i * 2048);
  ld8(&y[16], sb, uo + j * 1024 + t * 8, 65536);
}

#define TR(i) do {} while (0)
struct NoTail { __device__ __forceinline__ void operator()() const {} };
template <int N, int PS, int KPS, int KSTEP, int CHK, bool SUB, bool HREL = false, class Tail = NoTail>
__device__ __forceinline__ void mma_pass(float (&acc)[N / 2], uint32_t (&a)[144], uint64_t desc, uint32_t par, const Rel& rel, int bar_id,
                                         const uint8_t* sb = nullptr, uint32_t uo = 0, uint32_t flag = 0, uint32_t m0 = 0, uint32_t m1 = 0, uint32_t park = 0, Tail tail = Tail()) {
  constexpr int NS = 36 / KPS;
  auto check = [&](int lo, int hi, uint32_t m0_) {
    auto missing = [&]() {
      uint32_t u[3] = {m0_, m0_, m0_};
#pragma unroll
      for (int i = hi - 1; i >= lo; i--) {
        u[i % 3] = min(u[i % 3], a[4 * i]);
        if (i >= 32) u[i % 3] = min(u[i % 3], a[4 * i + 2]);
      }
      return __any_sync(0xffffffffu, (min(u[0], min(u[1], u[2])) | flag) == 0);
    };
    if (__builtin_expect(missing(), 0)) {
      do {
        const uint32_t t = tid_();
#pragma unroll
        for (int i = lo; i < hi; i++) load_frag(a, i, sb, uo, t);
      } while (missing());
    }
  };
#pragma unroll
  for (int s = 0; s < NS; s++) {
    const int sl = pass_slot<PS>(s);
    if (CHK && s == 0 && !SUB) check(0, CHK * KPS, ~0u);
    if (CHK && s == CHK) check(CHK * KPS, 36, token());
    if (SUB) {
#pragma unroll
      for (int i = s * KPS * 4; i < (s + 1) * KPS * 4; i += 2) { a[i] = bf2_sub(a[i], m0); a[i + 1] = bf2_sub(a[i + 1], m1); }
    }
    if (PS == PS_KV && bar_id < 0 && (s == 0 || s == KV_S1) && (s == (flag ? KV_S1 : 0))) bar_sync(NB_ORD1, 256);
    if (PS == PS_KV && s == 0) sts128(park + tid_() * 16, a[0], a[1], a[2], a[3]);
    constexpr int TB = PS == PS_KV ? 0 : PS == PS_Q ? 26 : PS == PS_WO ? 40 : SUB ? 54 : PS == PS_FFA ? 74 : -1;
    if (TB >= 0) TR(TB + 2 * s);
    mbar_wait(bar_full(sl), sl < 9 ? par : par ^ 1);
    if (TB >= 0) TR(TB + 2 * s + 1);
    wg_fence();
#pragma unroll
    for (int kk = 0; kk < KPS; kk++)
      WG<N>::f(acc, &a[(s * KPS + kk) * 4], desc + ((slot_addr(sl) + kk * KSTEP) >> 4), (s | kk) || PS == PS_FFA);
    wg_commit();
    if (CHK && s < 2 && N_UP < 36 && !flag) {
      const uint32_t t = tid_();
#pragma unroll
      for (int i = s ? (N_UP + 36) / 2 : N_UP; i < (s ? 36 : (N_UP + 36) / 2); i++) load_frag(a, i, sb, uo, t);
    }
    if (PS == PS_KV ? (s == KV_LEAD || s == KV_S1 + KV_LEAD) && s == (flag ? KV_S1 : 0) + KV_LEAD : s == NS - 1)
      if (bar_id >= 0) bar_arrive(bar_id, 256);
    if (s > 0) {
      wg_wait<1>();
      if (!(PS == PS_WO && s > 3)) rel(pass_slot<PS>(s - 1));
    }
    if (HREL && s == 3 && flag) {
#pragma unroll
      for (int i = 0; i < 12; i++) ld16(&a[4 * i], sb, uo, i * 2048);
    }
  }
  constexpr int TE = PS == PS_KV ? 24 : PS == PS_Q ? 38 : PS == PS_WO ? 52 : SUB ? 72 : PS == PS_FFA ? 92 : -1;
  tail();
  if (TE >= 0) TR(TE);
  wg_wait<0>();
  if (TE >= 0) TR(TE + 1);
  if (PS != PS_WO) rel(pass_slot<PS>(NS - 1));
}

template <int NF, int N0 = 0> __device__ __forceinline__ void load_frags(uint32_t (&a)[144], const uint8_t* sb, uint32_t uo, uint32_t t) {
#pragma unroll
  for (int i = N0; i < NF; i++) load_frag(a, i, sb, uo, t);
}
__device__ __forceinline__ void ln_scalars(float s1, float s2, uint32_t& m, float& var, uint32_t zero) {
  const float mean = s1 * (1.f / DM);
  var = s2 * (1.f / DM) - mean * mean;
  m = pack_bf16(mean, mean) ^ (__float_as_uint(var) & zero);
}
__device__ __forceinline__ float ln_rstd(float var, float after, uint32_t zero) {
  var = __uint_as_float(__float_as_uint(var) ^ (__float_as_uint(after) & zero));
  float sd, r;
  asm("sqrt.approx.ftz.f32 %0, %1;" : "=f"(sd) : "f"(bf_round(bf_round(fmaxf(var, 0.f)) + 1e-5f)));
  asm("rcp.approx.ftz.f32 %0, %1;" : "=f"(r) : "f"(bf_round(sd)));
  return r;
}
template <int NF> __device__ __forceinline__ void gather_ln(uint32_t (&a)[144], const uint8_t* sb, uint32_t uo, uint32_t sto,
                                          uint32_t& m0, uint32_t& m1, float& r0, float& r1, uint32_t zero) {
  uint32_t u[32];
  const uint32_t t = tid_(), so = sto + (t >> 5) * 1024 + (t & 28) * 4;
#pragma unroll
  for (int i = 0; i < 8; i++) ld16(&u[4 * i], sb, so, OFF_ST + i * 128);
  load_frags<N_UP>(a, sb, uo, t);
  while (true) {
    uint32_t m = a[4 * NF - 4];
#pragma unroll
    for (int i = NF - 2; i >= 0; i--) m = min(m, a[4 * i]);
#pragma unroll
    for (int i = 0; i < 8; i++) m = min(m, u[4 * i]);
    if (!__any_sync(0xffffffffu, m == 0)) break;
#pragma unroll
    for (int i = 0; i < 8; i++) ld16(&u[4 * i], sb, so, OFF_ST + i * 128);
    load_frags<NF>(a, sb, uo, t);
  }
  float v[4];
#pragma unroll
  for (int k = 0; k < 4; k++)
    v[k] = ((__uint_as_float(u[k]) + __uint_as_float(u[4 + k])) + (__uint_as_float(u[8 + k]) + __uint_as_float(u[12 + k]))) +
           ((__uint_as_float(u[16 + k]) + __uint_as_float(u[20 + k])) + (__uint_as_float(u[24 + k]) + __uint_as_float(u[28 + k])));
  ln_scalars(v[1], v[0], m0, r0, zero); ln_scalars(v[3], v[2], m1, r1, zero);
}
struct Stats {
  float s[4] = {0, 0, 0, 0}, d0[4] = {0, 0, 0, 0}, d1[4] = {0, 0, 0, 0};
  __device__ __forceinline__ void add16(const uint32_t* f) {
    mma16816(s, f[0], f[1], f[2], f[3], 0x3f803f80u, 0x3f803f80u);
    mma1688(d0, f[0], f[1], f[0]); mma1688(d1, f[0], f[1], f[1]);
    mma1688(d0, f[2], f[3], f[2]); mma1688(d1, f[2], f[3], f[3]);
  }
  __device__ __forceinline__ float sq0(int g) const { return (g & 1) ? d0[1] : d0[0]; }
  __device__ __forceinline__ float sq1(int g) const { return (g & 1) ? d1[3] : d1[2]; }
};
struct RowStats {
  float s[4] = {0, 0, 0, 0}, u[4] = {0, 0, 0, 0};
  template <int N> __device__ __forceinline__ void add(const uint32_t* y) {
#pragma unroll
    for (int i = 0; i < N; i++) {
      const float lo = bf_lo(y[i]), hi = bf_hi(y[i]);
      const int r = (i & 1) * 2;
      s[r] = fmaf(lo, lo, s[r]); u[r] = fmaf(hi, hi, u[r]); s[r + 1] += lo; u[r + 1] += hi;
    }
  }
  __device__ __forceinline__ uint32_t fold() {
    uint32_t x = 0;
#pragma unroll
    for (int i = 0; i < 4; i++) { s[i] += u[i]; u[i] = 0; x |= __float_as_uint(s[i]); }
    return x;
  }
  __device__ __forceinline__ void store(uint8_t* sb, uint32_t sto, uint32_t t) {
    fold();
#pragma unroll
    for (int i = 0; i < 4; i++) s[i] += __shfl_xor_sync(0xffffffffu, s[i], 1);
#pragma unroll
    for (int i = 0; i < 4; i++) s[i] += __shfl_xor_sync(0xffffffffu, s[i], 2);
    if ((t & 3) == 0) st16(sb, sto + (t >> 5) * 1024 + (t & 28) * 4, OFF_ST, __float_as_uint(s[0]) | 1u, __float_as_uint(s[1]), __float_as_uint(s[2]), __float_as_uint(s[3]));
  }
};
template <bool SET> __device__ __forceinline__ void add_piece(float* acc, uint32_t sm) {
#pragma unroll
  for (int i = 0; i < 4; i++) {
    uint32_t v[4];
    lds128(v, sm + i * 2048);
#pragma unroll
    for (int k = 0; k < 4; k++) {
      acc[8 * i + 2 * k] = SET ? bf_lo(v[k]) : acc[8 * i + 2 * k] + bf_lo(v[k]);
      acc[8 * i + 2 * k + 1] = SET ? bf_hi(v[k]) : acc[8 * i + 2 * k + 1] + bf_hi(v[k]);
    }
  }
}

#define TS(i) do {} while (0)
#define TSP(i) do {} while (0)
#define TSH(i) do {} while (0)

__device__ __forceinline__ uint32_t row_off(int rb, int wg, uint32_t t) { return (rb * 128 + wg + ((t >> 5) * 16 + (t & 15)) * 2) * (2 * DM); }

__device__ __forceinline__ const __nv_bfloat16* wo_src(const __nv_bfloat16* wo, int k, int u, int j) {
  const int ko = k < 512 ? (k >> 6) * 72 + (k & 63) : ((k >> 3) & 7) * 72 + 64 + (k & 7);
  return wo + ko * 576 + (u < 8 ? j * 64 + u * 8 : 512 + j * 8);
}

struct Params {
  const __nv_bfloat16* wqkv;
  uint8_t* scr;
  uint8_t role[64];
  const __nv_bfloat16* wo;
  __nv_bfloat16* out;
  uint8_t* times;
  unsigned zero;
};

__cluster_dims__(2, 1, 1)
__global__ void __launch_bounds__(384, 1)
fused_kernel(const __grid_constant__ Params P, const __grid_constant__ CUtensorMap map_x, const __grid_constant__ CUtensorMap map_wg,
             const __grid_constant__ CUtensorMap map_wu, const __grid_constant__ CUtensorMap map_wd) {
  const int wg = __shfl_sync(0xffffffffu, threadIdx.x >> 7, 0);
  const int cta = blockIdx.x, rank = cta & 1, role = P.role[cta >> 1], j = role & 7, rb = (role >> 3) * 2 + rank;
  const uint32_t own = win();
  unsigned* const flags = (unsigned*)(P.scr + OFF_FLAGS);
  if (__shfl_sync(0xffffffffu, threadIdx.x >> 5, 0) == 11) {
    if (threadIdx.x == 352) {
#pragma unroll
      for (int i = 0; i < 14; i++) { mbar_init(bar_full(i), 1); mbar_init(bar_empty(i), i < 12 ? 4 : i == 12 ? 8 : 2); }
      mbar_init(bar_full(14), 1); mbar_init(bar_empty(14), 1);
      asm volatile("fence.mbarrier_init.release.cluster;" ::: "memory");
      if (smem_u32(smem_raw) != own + SB) asm volatile("trap;");
    }
    __syncwarp();
    asm volatile("barrier.cluster.arrive.relaxed.aligned;" ::: "memory");
#pragma unroll
    for (int c = 0; c < 9; c++) {
      w_tma_3d(own + slot_addr(c), &map_x, c * 64, rb * 64, 0, own + bar_full(c));
      w_expect_tx(own + bar_full(c), SLOT);
    }
  } else {
    const bool on = threadIdx.x < 324;
    const int k = rb * 36 + (on ? threadIdx.x / 36 : 0) * 4 + (threadIdx.x & 3), u = (threadIdx.x % 36) >> 2;
    const uint4* s = (const uint4*)(P.wqkv + k * 1728 + j * 72 + u * 8);
    const uint4 vk = ldg_line(s + 72), vv = ldg_line(s + 144);
    const unsigned ep0 = *(volatile unsigned*)&flags[(72 + cta) * 8];
    asm volatile("barrier.cluster.arrive.relaxed.aligned;" ::: "memory");
    uint8_t* d = P.scr + OFF_WPACK + j * 24 * PSLOT;
    if (on) {
      const uint32_t dkv = (k / 48) * PSLOT + u * 768 + (k % 48) * 16;
      st16(d, dkv, 0, vk.x, vk.y, vk.z, vk.w);
      st16(d, dkv, 9 * 768, vv.x, vv.y, vv.z, vv.w);
    }
    asm volatile("fence.proxy.async.global;" ::: "memory");
    bar_arrive(NB_PUB + 3, 384);
    if (threadIdx.x == 351) sts32(SM_EPOCH, ep0);
    if (wg == 2) bar_sync(NB_PUB + 1, 96);
  }
  __syncwarp();
  asm volatile("barrier.cluster.wait.acquire.aligned;" ::: "memory");

  if (wg == 2) {
    asm volatile("setmaxnreg.dec.sync.aligned.u32 24;");
    const int pw = __shfl_sync(0xffffffffu, (threadIdx.x >> 5) & 3, 0), lane = threadIdx.x & 31;
    auto tile_col = [](int t, int h, int j) { return t < 9 ? j * 576 + t * 64 : (t == 9 && h) ? 512 : ((j + ((h ? 0x05760 : 0x04123) >> (4 * (t - 9)))) & 7) * 64; };
    auto prefetch_tile = [&](int t) {
#pragma unroll 1
      for (int b = rb; b < 18; b += 16) {
        const int h = b & 1, k = b >> 1;
        if (t < 9) w_tma_prefetch(h ? &map_wu : &map_wg, tile_col(t, h, j), k * 64);
        else if (t != 13 || !h) w_tma_prefetch(&map_wd, tile_col(t, h, j), j * 576 + k * 64);
      }
    };
    if (pw == 0) {
      {
        flag_wait(&flags[j * 8], (lds32(SM_EPOCH) + 1) * 16);
        TSP(7);
        asm volatile("fence.proxy.async.global;" ::: "memory");
        const uint8_t* wp = P.scr + OFF_WPACK + j * 24 * PSLOT;
        wp += rank * (PSLOT / 2);
        auto packed = [&](int sl, uint32_t par, int f) {
          mbar_wait(bar_empty(0) + sl * 8, par);
          w_bulk_load_mc(own + SB + rank * (PSLOT / 2) + sl * SLOT, wp + f * PSLOT, PSLOT / 2, own + bar_full(0) + sl * 8);
          w_expect_tx(own + bar_full(0) + sl * 8, PSLOT);
        };
        const uint32_t half = own + SB + rank * 8192;
#pragma unroll 1
        for (int L = 0; L < 2; L++) {
#pragma unroll 1
          for (int s = L ? 0 : -3; s < 21; s++) {
            if (s == 9 && L == 0) { flag_wait(&flags[(56 + j) * 8], (lds32(SM_EPOCH) + 1) * 16); asm volatile("fence.proxy.async.global;" ::: "memory"); }
            packed(s < 0 ? s + 12 : s < 9 ? s : s - 9, s < 0 || (s >= 9 && s < 18), s + 3);
          }
#pragma unroll 1
          for (int t = 0; t < 14; t++) {
            if (L * 14 + t + PF_AHEAD < 28) prefetch_tile((t + PF_AHEAD) % 14);
            const CUtensorMap* mp = t >= 9 ? &map_wd : rank ? &map_wu : &map_wg;
            const bool nar = t == 13;
            const int col = tile_col(t, nar ? 0 : rank, j);
            const uint32_t dst = nar ? own + SB : half, bytes = nar ? 8192 : SLOT;
            const int ra = t < 9 ? 0 : j * 576 + 320, rbs = t < 9 ? 0 : j * 576 - 192, rc = t < 9 ? 0 : j * 576;
#pragma unroll
            for (int k = 0; k < 9; k++) {
              mbar_wait(bar_empty(k), t & 1);
              if (!nar || rank == (k & 1)) w_tma_2d_mc(dst + k * SLOT, mp, col, (k < 3 ? ra : k < 8 ? rbs : rc) + k * 64, own + bar_full(k));
              w_expect_tx(own + bar_full(k), bytes);
            }
            if (t == 12 && L == 0) {
              w_l2_prefetch(P.scr + OFF_WPACK + j * 24 * PSLOT + rb * (24 * PSLOT / 16), 24 * PSLOT / 16);
#pragma unroll 1
              for (int s = 0; s < 3; s++) packed(9 + s, 1, s);
            }
          }
        }
        flags[(72 + cta) * 8] = lds32(SM_EPOCH) + 1;
      }
    } else if (pw < 3) {
      const int hw = pw - 1;
      const uint32_t ep = __shfl_sync(0xffffffffu, lds32(SM_EPOCH), 0);
      uint8_t* const sb = P.scr + (rb * 2 + hw) * STRM;
      const uint32_t xs = slot_addr(12) + hw * SLOT, fb = bar_full(12) + hw * 8;
      uint32_t hph = 0;
#pragma unroll 1
      for (int L = 0; L < 2; L++) {
        const uint32_t tag = ep * 2 + L + 1;
        bar_sync(NB_FREE + hw, 160);
        if (rb > 0) hint_wait(sb + OFF_HINT + 512 + j * 128, tag);
        uint32_t bad;
        do {
          if (rb > 0) {
            w_bulk_load(own + ytail(hw * 2), sb + OFF_HALO + (L * 8 + j) * 3072, 1536, own + bar_full(14) + hw * 128);
            w_bulk_load(own + ytail(hw * 2 + 1), sb + OFF_HALO + (L * 8 + j) * 3072 + 1536, 1536, own + bar_full(14) + hw * 128);
            w_expect_tx(own + bar_full(14) + hw * 128, 3072);
            mbar_wait(bar_full(14) + hw * 128, hph);
            hph ^= 1;
          }
          bad = 0;
#pragma unroll 1
          for (int c = 0; c < 3; c++) {
            uint32_t u[4] = {tag, 0, 0, 0}, v[4] = {tag, 0, 0, 0};
            if (rb > 0) { lds128(u, ytail(hw * 2) + c * 512 + lane * 16); lds128(v, ytail(hw * 2 + 1) + c * 512 + lane * 16); }
            bad |= (u[0] ^ tag) | (v[0] ^ tag);
#pragma unroll
            for (int i = 0; i < 3; i++) { sts32(xs + KSTG + (c * 3 + i) * 128 + lane * 4, u[i + 1]); sts32(xs + (c * 3 + i) * 128 + lane * 4, v[i + 1]); }
          }
        } while (__any_sync(0xffffffffu, bad != 0));
        bar_arrive(NB_HALO + hw, 160);
#pragma unroll 1
        for (int p = 0; p < 4; p++) {
          if (L == 0 && p == 3) flag_wait(flags + (40 + rb) * 8, (ep + 1) * 8);
          bar_sync(NB_FREE + hw, 160);
          TSH(L * 12 + p * 3);
          hint_wait(sb + OFF_HINT + (lane & 3) * 128, (ep * 13 + L * 7 + p + 3) * 8);
          TSH(L * 12 + p * 3 + 1);
          w_bulk_load(own + xs, sb + OFF_P + j * PSRC + (p & 1) * 16384, p ? 16384 : 8192, own + fb);
          if (p == 0) w_bulk_load(own + xs + 8192, sb + OFF_P + j * PSRC + 32768, 7168, own + fb);
          w_expect_tx(own + fb, p ? 16384 : 15360);
          TSH(L * 12 + p * 3 + 2);
        }
      }
    } else {
      auto clear = [&](int t) {
        const uint32_t so = rb * 2 * STRM + (threadIdx.x & 31) * 16;
#pragma unroll 1
        for (int i = 0; i < 18; i++) {
          st16(P.scr, so + t * TILE + j * 9216 + i * 512, 0, 0, 0, 0, 0);
          st16(P.scr, so + t * TILE + j * 9216 + i * 512, STRM, 0, 0, 0, 0);
          __nanosleep(0);
        }
        if (t != 1) {
          st16(P.scr, so + (t ? t - 1 : 0) * 4096 + j * 512, OFF_ST, 0, 0, 0, 0);
          st16(P.scr, so + (t ? t - 1 : 0) * 4096 + j * 512, OFF_ST + STRM, 0, 0, 0, 0);
        }
      };
      bar_sync(NB_PUB + 3, 384);
      if (lane == 0) flag_signal(&flags[j * 8]);
      TSP(5);
      bar_sync(NB_PUB + 2, 288);
      if (lane == 0) flag_signal(&flags[(56 + j) * 8]);
      TSP(4);
      __syncwarp();
#pragma unroll 1
      for (int t = 0; t < PF_AHEAD; t++) prefetch_tile(t);
#pragma unroll 1
      for (int L = 0; L < 2; L++) {
        timed_wait(bar_empty(13), L);
#pragma unroll 1
        for (int t = L ^ 1; t < 4 - 2 * L; t++) clear(t);
        __syncwarp();
        if (lane == 0 && L == 0) flag_signal(flags + (40 + rb) * 8);
      }
      timed_wait(bar_empty(12), 0);
      asm volatile("barrier.cluster.arrive.relaxed.aligned;\nbarrier.cluster.wait.aligned;" ::: "memory");
    }
  } else {
    asm volatile("setmaxnreg.inc.sync.aligned.u32 240;");
    const int w = __shfl_sync(0xffffffffu, (threadIdx.x >> 5) & 3, 0);
    Rel rel{(threadIdx.x & 95) == 0, cta_window(w & 1), 0};
    uint8_t* const sb = P.scr + (rb * 2 + wg) * STRM;
    uint8_t* const hint = sb + OFF_HINT + w * 128;
    auto hint_target = [](int e) { return (lds32(SM_EPOCH) * 13 + e + 1) * 8; };
    TS(0);
    uint32_t a[144];
#pragma unroll 1
    for (int L = 0; L < 2; L++) {
      uint32_t m0, m1; float r0, r1;
      rel.tr = win() + ytail(3) + 1536 + (L == TRACE - 1 && w == 1 ? wg * 384 : 768);
      if (L == 0) {
        Stats st;
        const int lane = tid_() & 31, g = lane >> 2;
        const int row = w * 16 + (lane & 15);
        const uint32_t ra = SB + wg * 8192 + row * 128;
        const uint32_t pt = tid_(), pu = (pt % 36) >> 2, pk = rb * 36 + (pt < 108 ? pt / 36 : 0) * 4 + (pt & 3);
        uint4 pv[3];
#pragma unroll
        for (int i = 0; i < 3; i++) pv[i] = ldg_line(wg ? wo_src(P.wo, pk + i * 12, pu, j) : P.wqkv + (pk + i * 12) * 1728 + j * 72 + pu * 8);
#pragma unroll
        for (int c = 0; c < 9; c++) {
          mbar_wait(bar_full(c), 0);
          if (c == 0) TS(60); if (c == 8) TS(62);
#pragma unroll
          for (int kk = 0; kk < 4; kk++) ldsm4(&a[c * 16 + kk * 4], ra + (((kk * 2 + (lane >> 4)) ^ (row & 7)) << 4) + c * SLOT);
          if (c == 8) {
            uint32_t y[18], z[4];
#pragma unroll
            for (int i = 0; i < 4; i++) ldsm4(&y[4 * i], ra + (((i * 2 + (lane >> 4)) ^ (row & 7)) << 4) + j * SLOT);
            ldsm4(z, ra + ((j ^ (row & 7)) << 4) + 8 * SLOT);
            y[16] = z[0]; y[17] = z[1];
            bar_sync(NB_WG + wg + ((z[0] | y[12] | a[140]) & P.zero), 128);
#pragma unroll
            for (int i = 0; i < 9; i++) rel(i);
            if (pt < 108) {
#pragma unroll
              for (int i = 0; i < 3; i++) {
                const uint32_t k = pk + i * 12;
                st16(P.scr, (j * 24 + wg * 6 + k / 96) * PSLOT + pu * 1536 + (k % 96) * 16, OFF_WPACK + 12 * PSLOT, pv[i].x, pv[i].y, pv[i].z, pv[i].w);
              }
            }
            asm volatile("fence.proxy.async.global;" ::: "memory");
            bar_arrive(NB_PUB + 2, 288);
            store_own(y, sb, OFF_X2, j, tid_());
          }
#pragma unroll
          for (int kk = 0; kk < 4; kk++) st.add16(&a[c * 16 + kk * 4]);
        }
        const int dl = (lane & ~3) | (g >> 1);
        ln_scalars(st.s[0], __shfl_sync(0xffffffffu, st.sq0(g), dl), m0, r0, P.zero);
        ln_scalars(st.s[2], __shfl_sync(0xffffffffu, st.sq1(g), dl), m1, r1, P.zero);
      } else {
#pragma unroll
        for (int i = 4 * N_UP; i < 144; i++) a[i] = 0;
        hint_wait(hint, hint_target(6));
        TS(61);
        gather_ln<3 * D_KV>(a, sb, OFF_X2, 8192, m0, m1, r0, r1, P.zero);
      }
      TS(1 + L * 20);
      uint32_t kf[18], qf[18];
      {
        float acc[72];
        mma_pass<144, PS_KV, 3, 256, D_KV, true>(acc, a, DESC_KV, 1, rel, wg == 0 ? NB_ORD1 : -1, sb, OFF_X2, L ^ 1, m0, m1, ytail(wg * 2));
        r0 = ln_rstd(r0, acc[0], P.zero); r1 = ln_rstd(r1, acc[0], P.zero);
        uint32_t vf[18];
#pragma unroll
        for (int c = 0; c < 9; c++) {
          kf[c] = pack_bf16(acc[4 * c] * r0, acc[4 * c + 1] * r0);
          kf[9 + c] = pack_bf16(acc[4 * c + 2] * r1, acc[4 * c + 3] * r1);
          vf[c] = pack_bf16(acc[36 + 4 * c] * r0, acc[36 + 4 * c + 1] * r0);
          vf[9 + c] = pack_bf16(acc[36 + 4 * c + 2] * r1, acc[36 + 4 * c + 3] * r1);
        }
        TS(2 + L * 20);
        const uint32_t l16 = (tid_() & 31) * 16, xs = slot_addr(12) + wg * SLOT + w * 1152;
#pragma unroll
        for (int i = 0; i < 4; i++) stsm4(xs + w * 1152 + 1152 + i * 512 + l16, vf[4 * i], vf[4 * i + 1], vf[4 * i + 2], vf[4 * i + 3]);
        sts32(xs + w * 1152 + 1152 + 2048 + l16 / 4, vf[16]); sts32(xs + w * 1152 + 1152 + 2176 + l16 / 4, vf[17]);
        if (w < 3) {
          stsm4(xs + KSTG + 1152 + l16, kf[9], kf[10], kf[11], kf[12]);
          stsm4(xs + KSTG + 1152 + 512 + l16, kf[13], kf[14], kf[15], kf[16]);
          sts32(xs + KSTG + 1152 + 1024 + l16 / 4, kf[17]);
        } else if (rb < 15) {
          const uint32_t tag = lds32(SM_EPOCH) * 2 + L + 1;
          const uint32_t ho = l16 + (L * 8 + j) * 3072;
#pragma unroll
          for (int c = 0; c < 3; c++) {
            st16(sb, ho, 2 * STRM + OFF_HALO + c * 512, tag, kf[9 + 3 * c], kf[10 + 3 * c], kf[11 + 3 * c]);
            st16(sb, ho, 2 * STRM + OFF_HALO + 1536 + c * 512, tag, vf[9 + 3 * c], vf[10 + 3 * c], vf[11 + 3 * c]);
          }
          hint_post(sb + 2 * STRM + OFF_HINT + 512 + j * 128);
        }
      }
      lds128(a, ytail(wg * 2) + tid_() * 16);
      bar_arrive(NB_FREE + wg + (a[0] & P.zero), 160);
      uint32_t kh[12], vp[20], v1[12];
      {
        float acc[36];
        if (wg == 1) bar_sync(NB_ORD1, 256);
        mma_pass<72, PS_Q, 6, 256, 0, false, false>(acc, a, DESC_Q, 0, rel, -1, nullptr, 0, 0, 0, 0, 0, [&]() {
          bar_sync(NB_HALO + wg, 160);
#pragma unroll
          for (int i = 0; i < 3; i++) ldsm4(&kh[4 * i], slot_addr(12) + wg * SLOT + w * 640 + tid_() * 16 + KSTG + i * 512);
          const uint32_t l = tid_() & 31, vb = slot_addr(12) + wg * SLOT + w * 2304;
#pragma unroll
          for (int i = 0; i < 5; i++) ldsm4t(&vp[4 * i], vb + (l & 8) * 144 + (l & 16) * 8 + (l & 7) * 16 + i * 256);
#pragma unroll
          for (int i = 0; i < 3; i++) ldsm4t(&v1[4 * i], vb + 2304 + l * 16 + i * 512);
        });
#pragma unroll
        for (int i = 0; i < 18; i++) qf[i] = pack_bf16(acc[2 * i], acc[2 * i + 1]);
      }
      TS(3 + L * 20);
      uint32_t xr[18];
      {
        const int tid = tid_(), g = (tid >> 2) & 7, q = tid & 3;
        const bool nohalo = (rb == 0 && w == 0);
        const bool le0 = 2 * q <= g, le1 = 2 * q + 1 <= g;
        const uint32_t M = (le0 ? 0xffffu : 0u) | (le1 ? 0xffff0000u : 0u);
        const float sc0 = r0 * (0.23570226039551584f * 1.4426950408889634f), sc1 = r1 * (0.23570226039551584f * 1.4426950408889634f);
        float l[16], t[8];
#pragma unroll
        for (int h = 0; h < 4; h++) {
          const uint32_t qa0 = q >= h ? qf[4 * h] : 0u, qa1 = q >= h ? qf[4 * h + 1] : 0u;
          const uint32_t qc0 = q <= h ? qf[4 * h + 4] : 0u, qc1 = q <= h ? qf[4 * h + 5] : 0u;
          float sm[4] = {0, 0, 0, 0}, s0[4] = {0, 0, 0, 0}, s1[4] = {0, 0, 0, 0};
          mma16816(s0, qa0, qa1, qf[4 * h + 2], qf[4 * h + 3], kf[2 * h], kf[2 * h + 1]);
          mma16816(s1, qa0, qa1, qf[4 * h + 2], qf[4 * h + 3], kf[9 + 2 * h], kf[10 + 2 * h]);
          mma16816(sm, qa0, qa1, qf[4 * h + 2], qf[4 * h + 3], kh[2 * h], kh[2 * h + 1]);
          mma1688(s0, qc0, qc1, kf[2 * h + 2]);
          mma1688(s1, qc0, qc1, kf[11 + 2 * h]);
          mma1688(sm, qc0, qc1, kh[2 * h + 2]);
          if (nohalo) sm[0] = sm[1] = -3e38f;
          l[4 * h] = le0 ? s0[0] : sm[0]; l[4 * h + 1] = le1 ? s0[1] : sm[1];
          l[4 * h + 2] = le0 ? s1[2] : s0[2]; l[4 * h + 3] = le1 ? s1[3] : s0[3];
        }
#pragma unroll
        for (int i = 0; i < 8; i++) t[i] = fmaxf(l[2 * i], l[2 * i + 1]);
        TS(14 + L * 20);
#pragma unroll
        for (int i = 0; i < 8; i++) t[i] = fmaxf(t[i], __shfl_xor_sync(0xffffffffu, t[i], 1));
#pragma unroll
        for (int i = 0; i < 8; i++) t[i] = fmaxf(t[i], __shfl_xor_sync(0xffffffffu, t[i], 2)) * ((i & 1) ? sc1 : sc0);
#pragma unroll
        for (int i = 0; i < 8; i++) {
          const float sc = (i & 1) ? sc1 : sc0;
          l[2 * i] = ex2(fmaf(l[2 * i], sc, -t[i])); l[2 * i + 1] = ex2(fmaf(l[2 * i + 1], sc, -t[i])); t[i] = l[2 * i] + l[2 * i + 1];
        }
#pragma unroll
        for (int i = 0; i < 8; i++) t[i] += __shfl_xor_sync(0xffffffffu, t[i], 1);
#pragma unroll
        for (int i = 0; i < 8; i++) t[i] += __shfl_xor_sync(0xffffffffu, t[i], 2);
        uint32_t pf[16], pz[8];
#pragma unroll
        for (int i = 0; i < 8; i++) {
          float r; asm("rcp.approx.ftz.f32 %0, %1;" : "=f"(r) : "f"(t[i]));
          const uint32_t p = pack_bf16(l[2 * i] * r, l[2 * i + 1] * r);
          pf[2 * i] = p & ~M; pf[2 * i + 1] = p & M; pz[i] = p & P.zero;
        }
#pragma unroll
        for (int c = 0; c < 9; c++) {
          const int h = c == 8 ? 3 : c >> 1;
          float o[4] = {0, 0, 0, 0};
          mma16816(o, pf[4 * h], pz[2 * h], pf[4 * h + 1], pf[4 * h + 2], vp[2 * c], vp[2 * c + 1]);
          mma1688(o, pz[2 * h + 1], pf[4 * h + 3], v1[c]);
          if (c == 2 || c == 4 || c == 6) {
            float e[4] = {0, 0, 0, 0};
            mma16816(e, pf[4 * h - 4], pz[2 * h - 2], pf[4 * h - 3], pf[4 * h - 2], vp[2 * c], vp[2 * c + 1]);
            mma1688(e, pz[2 * h - 1], pf[4 * h - 1], v1[c]);
            const uint32_t u = pack_bf16(e[0], e[1]), v = pack_bf16(e[2], e[3]);
            qf[2 * c] = q < h ? u : pack_bf16(o[0], o[1]); qf[2 * c + 1] = q < h ? v : pack_bf16(o[2], o[3]);
          } else {
            qf[2 * c] = pack_bf16(o[0], o[1]); qf[2 * c + 1] = pack_bf16(o[2], o[3]);
          }
        }
        {
          uint32_t x = 0;
#pragma unroll
          for (int i = 0; i < 18; i += 2) x |= qf[i];
          bar_arrive(NB_ORD1 - wg + (x & P.zero), 256);
        }
        store_own(qf, sb, OFF_O, j, tid);
        hint_post(hint);
        load_own(xr, sb, OFF_X2, j);
      }
      TS(4 + L * 20);
      {
        hint_wait(hint, hint_target(L * 7));
        TS(5 + L * 20);
        load_frags<N_WO>(a, sb, OFF_O, tid_());
        float acc[36];
        if (wg == 0) bar_sync(NB_ORD0, 256);
        load_frags<N_UP, N_WO>(a, sb, OFF_O, tid_());
        TS(19 + L * 20);
        mma_pass<72, PS_WO, 6, 256, D_WO, false>(acc, a, DESC_Q, 0, rel, -1, sb, OFF_O);
        TS(6 + L * 20);
#pragma unroll
        for (int c = 0; c < 9; c++) {
          xr[2 * c] = bf2_add(xr[2 * c], pack_bf16(acc[4 * c], acc[4 * c + 1]));
          xr[2 * c + 1] = bf2_add(xr[2 * c + 1], pack_bf16(acc[4 * c + 2], acc[4 * c + 3]));
        }
        store_own(xr, sb, L * 3 * TILE, j, tid_());
        RowStats rs;
        rs.add<18>(xr);
        rs.store(sb, L * 4096 + j * 128, tid_());
        hint_post(hint);
      }
      TS(16 + L * 20);
      hint_wait(hint, hint_target(L * 7 + 1));
      TS(15 + L * 20);
      gather_ln<4 * D_T0>(a, sb, L * 3 * TILE, L * 4096, m0, m1, r0, r1, P.zero);
      TS(7 + L * 20);
      const uint32_t hb = OFF_H + j * 24576;
      {
        float ka0, kb0, kc0, ka1, kb1, kc1;
        float acc[64];
        uint32_t hf[16];
        auto geglu = [&](auto chains, uint32_t hsm) {
          constexpr int CH = decltype(chains)::value & 15;
          float r[32];
#pragma unroll
          for (int e = 0; e < 32; e++) {
            float x = acc[e];
            if (e >= CH) x = __uint_as_float(__float_as_uint(x) ^ (__float_as_uint(r[e - CH]) & P.zero));
            if (decltype(chains)::value > 15 && e < 20) {
              const uint32_t ad = (e < 8 ? slot_addr(12) + e * 2048 + wg * 8192 : slot_addr(7 + (e >> 2)) + (e & 3) * 2048) + hsm;
              lds128(&a[48 + 4 * e], e >= CH ? ad ^ (__float_as_uint(r[e - CH]) & P.zero) : ad);
            }
            const bool hi = e & 2;
            float t = x * fmaf(x * x, hi ? kb1 : kb0, hi ? ka1 : ka0);
            asm("tanh.approx.f32 %0, %0;" : "+f"(t));
            const float u = x * acc[32 + e] * (hi ? kc1 : kc0);
            r[e] = fmaf(u, t, u);
            if (e & 1) hf[e >> 1] = pack_bf16(r[e - 1], r[e]);
          }
        };
        if (wg == 1) bar_sync(NB_ORD1, 256);
        mma_pass<128, PS_FF, 4, 2048, D_T0, true>(acc, a, DESC_SW128, 1, rel, NB_ORD1 - wg, sb, L * 3 * TILE, 0, m0, m1);
        if (tid_() == 0) mbar_arrive(bar_empty(13));
        TS(8 + L * 20);
        r0 = ln_rstd(r0, acc[0], P.zero); r1 = ln_rstd(r1, acc[0], P.zero);
        ka0 = 0.7978845608028654f * r0; kb0 = 0.035677408136300125f * r0 * r0 * r0; kc0 = 0.5f * r0 * r0;
        ka1 = 0.7978845608028654f * r1; kb1 = 0.035677408136300125f * r1 * r1 * r1; kc1 = 0.5f * r1 * r1;
#pragma unroll 1
        for (int t = 0; t < 8; t++) {
          geglu(IntC<2>(), 0);
          const uint32_t t16 = tid_() * 16;
          if (t < 5) {
            const uint32_t d = (t < 2 ? slot_addr(12) + wg * SLOT + t * 8192 : slot_addr(7) + t * SLOT + wg * 8192) + t16;
#pragma unroll
            for (int i = 0; i < 4; i++)
              sts128(d + i * 2048, hf[4 * i], hf[4 * i + 1], hf[4 * i + 2], hf[4 * i + 3]);
            if (t == 4) asm volatile("fence.proxy.async.shared::cta;" ::: "memory");
          } else {
#pragma unroll
            for (int i = 0; i < 4; i++) st16(sb, hb + (t - 5) * 8192 + t16, i * 2048, hf[4 * i], hf[4 * i + 1], hf[4 * i + 2], hf[4 * i + 3]);
          }
          bar_sync(NB_ORD0 + wg, 256);
          mma_pass<128, PS_FF, 4, 2048, 0, false, true>(acc, a, DESC_SW128, t & 1, rel, NB_ORD1 - wg, sb, hb + t16, t == 7);
        }
        TS(9 + L * 20);
        const uint32_t hsm = wg * 8192 + tid_() * 16;
        geglu(IntC<16 + CH_LAST>(), hsm);
#pragma unroll
        for (int i = 0; i < 16; i++) a[128 + i] = hf[i];
      }
      TS(10 + L * 20);
      {
        const uint32_t xs = slot_addr(12) + wg * SLOT;
        auto verify = [&](int p, uint32_t t16) {
          mbar_wait(bar_full(12) + wg * 8, p & 1);
          TS(71 + L * 32 + p * 5);
          const uint32_t ta = p < 2, tb = (p & 1) ? ta : L ^ 1, nb = p ? 4 : 7, sh = p == 0;
          uint32_t m = 0;
#pragma unroll
          for (int s = 0; s < 4; s++) m |= (lds32(xs + s * 2048 + t16) ^ ta) | (lds32(xs + 8192 + ((s * 2048 + t16) >> sh)) ^ tb);
          if (p == 0) {
#pragma unroll
            for (int s = 4; s < 7; s++) m |= lds32(xs + 8192 + s * 1024 + t16 / 2) ^ tb;
          }
          if (__any_sync(0xffffffffu, m & 1)) {
#pragma unroll 1
            for (int s = 0; s < 4 + nb; s++) {
              const bool nar = sh && s >= 4;
              const uint32_t o = nar ? 4096 + s * 1024 + t16 / 2 : s * 2048 + t16;
              uint32_t v[4] = {0, 0, 0, 0};
              do {
                if (nar) ld8(v, sb, j * PSRC + o, OFF_P + 32768 - 8192);
                else ld16(v, sb, j * PSRC + (p & 1) * 16384 + o, OFF_P);
              } while (__any_sync(0xffffffffu, (v[0] ^ (s < 4 ? ta : tb)) & 1));
              sts64(xs + o, v[0], v[1]);
              if (!nar) sts64(xs + o + 8, v[2], v[3]);
            }
            asm volatile("fence.proxy.async.shared::cta;" ::: "memory");
          }
        };
        uint32_t t16 = (a[142] | a[143]) & P.zero;
#pragma unroll 1
        for (int p = 0; p < 4; p++) {
          float acc[64];
          bar_sync(NB_ORD0 + wg + (p ? 0 : t16), 256);
          TS(64 + L * 32 + p * 5);
          if (p == 0) { rel(9); rel(10); rel(11); }
          mma_pass<128, PS_FF, 4, 2048, 0, false, false>(acc, a, DESC_SW128, p & 1, rel, NB_ORD1 - wg, nullptr, 0, 0, 0, 0, 0, [&]() {
            t16 = tid_() * 16;
            if (p) verify(p - 1, t16);
          });
          TS(65 + L * 32 + p * 5);
          if (p == 1 || p == 2) add_piece<false>(acc, xs + t16);
          const uint32_t oa = ((j + (p < 3 ? 1 : 4)) & 7) * PSRC + (p & 1) * 16384 + t16;
#pragma unroll
          for (int i = 0; i < 4; i++)
            st16(sb, oa, OFF_P + i * 2048, (pack_bf16(acc[8 * i], acc[8 * i + 1]) & ~1u) | (p < 2), pack_bf16(acc[8 * i + 2], acc[8 * i + 3]),
                 pack_bf16(acc[8 * i + 4], acc[8 * i + 5]), pack_bf16(acc[8 * i + 6], acc[8 * i + 7]));
          if (p == 0) {
#pragma unroll
            for (int i = 0; i < 8; i++)
              send8(sb, j * 1024 + t16 / 2, OFF_P + 32768 + i * PSRC, xs + 15360 + t16 / 2, i, j,
                    (pack_bf16(acc[32 + 4 * i], acc[33 + 4 * i]) & ~1u) | (L ^ 1), pack_bf16(acc[34 + 4 * i], acc[35 + 4 * i]));
          } else {
            if (p == 2) add_piece<false>(acc + 32, xs + 8192 + t16);
            const uint32_t ob = ((j + (p < 3 ? 7 : 5)) & 7) * PSRC + (p & 1) * 16384 + t16, tb = p == 2 ? L ^ 1 : p < 2;
#pragma unroll
            for (int i = 4; i < 8; i++)
              st16(sb, ob, OFF_P + i * 2048, (pack_bf16(acc[8 * i], acc[8 * i + 1]) & ~1u) | tb, pack_bf16(acc[8 * i + 2], acc[8 * i + 3]),
                   pack_bf16(acc[8 * i + 4], acc[8 * i + 5]), pack_bf16(acc[8 * i + 6], acc[8 * i + 7]));
          }
          hint_post(hint);
          TS(68 + L * 32 + p * 5);
          if (p == 1) {
            float s0 = 0.f, s1 = 0.f, s2 = 0.f, s3 = 0.f;
#pragma unroll
            for (int s = 0; s < 8; s++) {
              uint32_t u, v;
              lds64(u, v, xs + 8192 + s * 1024 + t16 / 2);
              s0 += bf_lo(u); s1 += bf_hi(u); s2 += bf_lo(v); s3 += bf_hi(v);
            }
            sts64(ytail(wg * 2) + t16, pack_bf16(s0, s1), pack_bf16(s2, s3));
          }
          if (p < 3) bar_arrive(NB_FREE + wg, 160);
          TS(67 + L * 32 + p * 5);
        }
        float acc[32];
        add_piece<true>(acc, xs + t16);
        add_piece<false>(acc, xs + 8192 + t16);
        bar_arrive(NB_FREE + wg + ((__float_as_uint(acc[0]) | __float_as_uint(acc[8]) | __float_as_uint(acc[16]) | __float_as_uint(acc[24])) & P.zero), 160);
        load_own(xr, sb, L * 3 * TILE, j);
        bar_sync(NB_ORD0 + wg, 256);
        TS(84 + L * 32);
        uint32_t t, yn[2];
        mma_pass<64, PS_FFA, 4, 2048, 0, false, false>(acc, a, DESC_SW128, 0, rel, wg ? -1 : NB_ORD1, nullptr, 0, 0, 0, 0, 0, [&]() {
          t = tid_();
          lds64(yn[0], yn[1], ytail(wg * 2) + t * 16);
          mbar_wait(bar_full(12) + wg * 8, 1);
#pragma unroll
          for (int i = 0; i < 8; i++) lds128(&a[4 * i], xs + i * 2048 + t * 16);
        });
        TS(11 + L * 20);
        while (true) {
          uint32_t m = 0;
#pragma unroll
          for (int i = 0; i < 8; i++) m |= a[4 * i];
          if (!__any_sync(0xffffffffu, m & 1)) break;
#pragma unroll
          for (int i = 0; i < 8; i++) ld16(&a[4 * i], sb, j * PSRC + t * 16, OFF_P + 16384 + i * 2048);
        }
        TS(12 + L * 20);
#pragma unroll
        for (int i = 0; i < 18; i++)
          xr[i] = bf2_add(xr[i], i < 16 ? pack_bf16(acc[2 * i] + (bf_lo(a[i]) + bf_lo(a[16 + i])), acc[2 * i + 1] + (bf_hi(a[i]) + bf_hi(a[16 + i]))) : yn[i - 16]);
        TS(18 + L * 20);
        if (L == 0) {
          store_own(xr, sb, OFF_X2, j, t);
          RowStats rs;
          rs.add<18>(xr);
          rs.store(sb, 8192 + j * 128, t);
          hint_post(hint);
        } else {
          const uint32_t l = t & 31, wb = xs + w * 512;
          if (l == 0) mbar_arrive(bar_empty(12));
          __syncwarp();
          asm volatile("barrier.cluster.arrive.relaxed.aligned;" ::: "memory");
#pragma unroll
          for (int i = 0; i < 4; i++) stsm4(wb + i * 2048 + (l & 24) * 16 + (((l & 7) ^ (i * 2 + (l >> 4))) << 4), xr[4 * i], xr[4 * i + 1], xr[4 * i + 2], xr[4 * i + 3]);
          stsm4(wb + 8192 + l * 16, xr[16], xr[17], 0, 0);
          __syncwarp();
          uint8_t* op = (uint8_t*)P.out + row_off(rb, wg, w * 32 + (l >> 3)) + j * 128 + (l & 7) * 16;
#pragma unroll
          for (int i = 0; i < 4; i++) {
            uint32_t r[4];
            lds128(r, wb + ((l & 6) << 10) + ((l & 1) * 2 + (i >> 1)) * 128 + (((((i & 1) * 4 + (l >> 3)) ^ l) & 7) << 4));
            *(uint4*)(op + i * 16 * DM) = make_uint4(r[0], r[1], r[2], r[3]);
          }
          uint32_t r[4];
          lds128(r, wb + 8192 + l * 16);
          if (l < 16) *(uint4*)((uint8_t*)P.out + row_off(rb, wg, t) + 1024 + j * 16) = make_uint4(r[0], r[1], r[2], r[3]);
        }
      }
      TS(13 + L * 20);
    }
  }
}

typedef CUresult (*EncodeFn)(CUtensorMap*, CUtensorMapDataType, cuuint32_t, void*, const cuuint64_t*, const cuuint64_t*, const cuuint32_t*,
                             const cuuint32_t*, CUtensorMapInterleave, CUtensorMapSwizzle, CUtensorMapL2promotion, CUtensorMapFloatOOBfill);

void encode(EncodeFn fn, CUtensorMap* m, const void* p, int rank, const cuuint64_t* dims, const cuuint64_t* str, const cuuint32_t* box) {
  const cuuint32_t es[3] = {1, 1, 1};
  fn(m, CU_TENSOR_MAP_DATA_TYPE_BFLOAT16, rank, const_cast<void*>(p), dims, str, box, es, CU_TENSOR_MAP_INTERLEAVE_NONE,
     CU_TENSOR_MAP_SWIZZLE_128B, CU_TENSOR_MAP_L2_PROMOTION_L2_256B, CU_TENSOR_MAP_FLOAT_OOB_FILL_NONE);
}

__global__ void probe_kernel() {}

void make_roles(uint8_t* role) {
  int cnt[8];
  cudaFuncSetAttribute(probe_kernel, cudaFuncAttributeMaxDynamicSharedMemorySize, SMEM_BYTES);
  cudaFuncSetAttribute(probe_kernel, cudaFuncAttributeNonPortableClusterSizeAllowed, 1);
  for (int r = 7; r >= 0; r--) {
    int n = 0;
    cudaLaunchConfig_t cfg = {};
    cudaLaunchAttribute at;
    at.id = cudaLaunchAttributeClusterDimension; at.val.clusterDim.x = 2 * (r < 3 ? 4 : r + 1); at.val.clusterDim.y = at.val.clusterDim.z = 1;
    cfg.gridDim = dim3(at.val.clusterDim.x); cfg.blockDim = dim3(384); cfg.dynamicSmemBytes = SMEM_BYTES; cfg.attrs = &at; cfg.numAttrs = 1;
    if (cudaOccupancyMaxActiveClusters(&n, probe_kernel, &cfg) != cudaSuccess) { cudaGetLastError(); n = r > 3 ? 8 : 8 + cnt[7]; }
    cnt[r] = r > 3 ? n : n - cnt[7];
  }
  int key[64], c = 0, total = 0, seg = 0;
  for (int r = 0; r < 8; r++) total += cnt[r];
  for (; c < 64 - total; c++) key[c] = -1;
  for (int r = 0; r < 8; r++) {
    if (r && cnt[r] != cnt[r - 1]) seg++;
    for (int i = 0; i < cnt[r] && c < 64; i++) key[c++] = seg * 16 + i;
  }
  int order[64], n = 0;
  bool used[64] = {};
  for (int pass = 0; pass < 2; pass++)
    for (int i = 0; i < 64; i++) {
      if (used[i]) continue;
      int m[4], k = 0;
      for (int q = i; q < 64 && k < 4; q++) if (!used[q] && (pass || (key[q] == key[i] && key[i] >= 0))) m[k++] = q;
      if (k == 4) for (int q = 0; q < 4; q++) { used[m[q]] = true; order[n++] = m[q]; }
    }
  for (int i = 0; i < 64; i++) role[order[i]] = (uint8_t)(((i >> 2) & 7) << 3 | (i >> 5) << 2 | (i & 3));
}

}

extern "C" void kernel_launch(void* const* d_in, const int* in_sizes, int n_in, void* d_out, int out_size) {
  (void)in_sizes; (void)n_in; (void)out_size;
  Params P = {};
  P.wqkv = (const __nv_bfloat16*)d_in[1]; P.wo = (const __nv_bfloat16*)d_in[2];
  P.out = (__nv_bfloat16*)d_out; P.zero = 0;
  cudaGetSymbolAddress((void**)&P.scr, g_scr);
  make_roles(P.role);
  void* fnp = nullptr; cudaDriverEntryPointQueryResult qr;
  cudaGetDriverEntryPoint("cuTensorMapEncodeTiled", &fnp, cudaEnableDefault, &qr);
  EncodeFn fn = (EncodeFn)fnp;
  CUtensorMap mx, mg, mu, md;
  { const cuuint64_t dims[3] = {DM, SEQ / 2, 2}, str[2] = {DM * 4, DM * 2}; const cuuint32_t box[3] = {64, 64, 2}; encode(fn, &mx, d_in[0], 3, dims, str, box); }
  { const cuuint64_t dims[2] = {DFF, DM}, str[1] = {DFF * 2}; const cuuint32_t box[2] = {64, 64}; encode(fn, &mg, d_in[4], 2, dims, str, box); encode(fn, &mu, d_in[5], 2, dims, str, box); }
  { const cuuint64_t dims[2] = {DM, DFF}, str[1] = {DM * 2}; const cuuint32_t box[2] = {64, 64}; encode(fn, &md, d_in[6], 2, dims, str, box); }
  cudaFuncSetAttribute(fused_kernel, cudaFuncAttributeMaxDynamicSharedMemorySize, SMEM_BYTES);
  fused_kernel<<<128, 384, SMEM_BYTES, cudaStreamPerThread>>>(P, mx, mg, mu, md);
}
```

```cpp
#include <cuda_runtime.h>
#include <cuda_bf16.h>
#include <cuda.h>
#include <stdint.h>

#define TIMING 0
#define TRACE 0

namespace {

constexpr int SEQ = 2048, DM = 576, DFF = 4608;
constexpr int KV_S1 = 4;
constexpr int KV_LEAD = 5;
constexpr int D_KV = 6, D_WO = 3, D_T0 = 5;
constexpr int N_UP = 26, N_WO = 12;
constexpr int PF_AHEAD = 2;
constexpr int CH_LAST = 3;
constexpr uint32_t SB = 1024;
constexpr uint32_t SLOT = 16384;
constexpr uint32_t PSLOT = 13824;
constexpr uint32_t BARS = SB + 14 * SLOT;
constexpr int SMEM_BYTES = 14 * SLOT + 256 + 2560 + 256;
__host__ __device__ constexpr uint32_t slot_addr(int s) { return SB + s * SLOT; }
__host__ __device__ constexpr uint32_t bar_full(int s) { return BARS + 8 * s; }
__host__ __device__ constexpr uint32_t bar_empty(int s) { return BARS + 128 + 8 * s; }
enum { NB_ORD0 = 1, NB_ORD1 = 2, NB_WG = 3  , NB_HALO = 5  , NB_FREE = 7  , NB_PUB = 9   };
constexpr uint32_t SM_EPOCH = BARS + 120, BAR_X = BARS + 256 + 2560 + 192;
__host__ __device__ constexpr uint32_t ytail(uint32_t k) { return k < 3 ? slot_addr(9) + PSLOT + k * SLOT : BARS + 256; }
constexpr uint32_t KSTG = 9 * 1152;

constexpr uint32_t TILE = 36 * 2048;
constexpr uint32_t OFF_X1 = 0  , OFF_O = TILE, OFF_X2 = 2 * TILE, OFF_ST = 4 * TILE  ;
constexpr uint32_t PSRC = 2 * 16384 + 7 * 1024;
constexpr uint32_t OFF_P = OFF_ST + 3 * 4096, OFF_HALO = OFF_P + 8 * PSRC  , OFF_HINT = OFF_HALO + 2 * 8 * 3072  ,
                   OFF_H = OFF_HINT + 16 * 128  , STRM = OFF_H + 8 * 24576;
constexpr uint32_t OFF_WPACK = 32 * STRM, OFF_FLAGS = OFF_WPACK + 8 * 24 * PSLOT;
__device__ __align__(1024) uint8_t g_scr[OFF_FLAGS + (8 + 64 + 128) * 32];

__device__ __forceinline__ uint32_t smem_u32(const void* p) { return (uint32_t)__cvta_generic_to_shared(p); }
extern __shared__ __align__(1024) uint8_t smem_raw[];
__device__ __forceinline__ uint32_t win() { return (blockIdx.x & 1) << 24; }
#define SA(A, W) ".reg .u32 sa;\nadd.u32 sa, " A ", " W ";\n"
__device__ __forceinline__ void mbar_init(uint32_t bar, uint32_t cnt) { asm volatile("{\n" SA("%0", "%2") "mbarrier.init.shared::cta.b64 [sa], %1;\n}" ::"r"(bar), "r"(cnt), "r"(win())); }
__device__ __forceinline__ void mbar_arrive(uint32_t bar) { asm volatile("{\n" SA("%0", "%1") "mbarrier.arrive.shared::cta.b64 _, [sa];\n}" ::"r"(bar), "r"(win()) : "memory"); }
__device__ __forceinline__ uint32_t lds32(uint32_t a) { uint32_t v; asm volatile("{\n" SA("%1", "%2") "ld.shared.u32 %0, [sa];\n}" : "=r"(v) : "r"(a), "r"(win()) : "memory"); return v; }
__device__ __forceinline__ void lds64(uint32_t& x, uint32_t& y, uint32_t a) { asm volatile("{\n" SA("%2", "%3") "ld.shared.v2.u32 {%0,%1}, [sa];\n}" : "=r"(x), "=r"(y) : "r"(a), "r"(win()) : "memory"); }
__device__ __forceinline__ void lds128(uint32_t* v, uint32_t a) {
  asm volatile("{\n" SA("%4", "%5") "ld.shared.v4.u32 {%0,%1,%2,%3}, [sa];\n}" : "=r"(v[0]), "=r"(v[1]), "=r"(v[2]), "=r"(v[3]) : "r"(a), "r"(win()) : "memory");
}
__device__ __forceinline__ void stsm4(uint32_t a, uint32_t x, uint32_t y, uint32_t z, uint32_t w) {
  asm volatile("{\n" SA("%0", "%5") "stmatrix.sync.aligned.m8n8.x4.shared.b16 [sa], {%1,%2,%3,%4};\n}" ::"r"(a), "r"(x), "r"(y), "r"(z), "r"(w), "r"(win()) : "memory");
}
__device__ __forceinline__ void ldsm4(uint32_t* v, uint32_t a) {
  asm volatile("{\n" SA("%4", "%5") "ldmatrix.sync.aligned.m8n8.x4.shared.b16 {%0,%1,%2,%3}, [sa];\n}" : "=r"(v[0]), "=r"(v[1]), "=r"(v[2]), "=r"(v[3]) : "r"(a), "r"(win()) : "memory");
}
__device__ __forceinline__ void ldsm4t(uint32_t* v, uint32_t a) {
  asm volatile("{\n" SA("%4", "%5") "ldmatrix.sync.aligned.m8n8.x4.trans.shared.b16 {%0,%1,%2,%3}, [sa];\n}" : "=r"(v[0]), "=r"(v[1]), "=r"(v[2]), "=r"(v[3]) : "r"(a), "r"(win()) : "memory");
}
__device__ __forceinline__ void sts32(uint32_t a, uint32_t x) { asm volatile("{\n" SA("%0", "%2") "st.shared.u32 [sa], %1;\n}" ::"r"(a), "r"(x), "r"(win()) : "memory"); }
__device__ __forceinline__ void sts64(uint32_t a, uint32_t x, uint32_t y) { asm volatile("{\n" SA("%0", "%3") "st.shared.v2.u32 [sa], {%1,%2};\n}" ::"r"(a), "r"(x), "r"(y), "r"(win()) : "memory"); }
__device__ __forceinline__ void sts128(uint32_t a, uint32_t x, uint32_t y, uint32_t z, uint32_t w) {
  asm volatile("{\n" SA("%0", "%5") "st.shared.v4.u32 [sa], {%1,%2,%3,%4};\n}" ::"r"(a), "r"(x), "r"(y), "r"(z), "r"(w), "r"(win()) : "memory");
}
__device__ __forceinline__ void mbar_wait(uint32_t bar, uint32_t parity) {
  asm volatile("{\n.reg .pred p;\n" SA("%0", "%2") "LAB_WAIT:\nmbarrier.try_wait.parity.shared::cta.b64 p, [sa], %1;\n@!p bra LAB_WAIT;\n}" ::"r"(bar), "r"(parity), "r"(win()) : "memory");
}
__device__ __forceinline__ void timed_wait(uint32_t bar, uint32_t par) {
  asm volatile("{\n.reg .pred p;\n.reg .u64 t0, t1;\nmov.u64 t0, %%globaltimer;\nLAB_WD:\n"
               "mbarrier.try_wait.parity.shared::cta.b64 p, [%0], %1, 100000;\n@p bra LAB_OK;\n"
               "mov.u64 t1, %%globaltimer;\nsub.u64 t1, t1, t0;\nsetp.lt.u64 p, t1, 2000000000;\n@p bra LAB_WD;\ntrap;\nLAB_OK:\n}" ::"r"(bar + win()), "r"(par) : "memory");
}
__device__ __forceinline__ void flag_wait(const unsigned* flag, unsigned target) {
  asm volatile("{\n.reg .pred p;\n.reg .u32 v;\nLAB_WAIT:\nld.acquire.gpu.global.u32 v, [%0];\nsub.u32 v, v, %1;\n"
               "setp.lt.s32 p, v, 0;\nvote.sync.any.pred p, p, 0xffffffff;\n@p nanosleep.u32 100;\n@p bra LAB_WAIT;\n}" ::"l"(flag), "r"(target) : "memory");
}
__device__ __forceinline__ void hint_post(uint8_t* p) {
  __syncwarp();
  asm volatile("{\n.reg .pred p;\nelect.sync _|p, 0xffffffff;\n@p red.relaxed.gpu.global.add.u32 [%0], 1;\n}" ::"l"(p) : "memory");
}
__device__ __forceinline__ void hint_wait(const uint8_t* p, uint32_t target) {
  asm volatile("{\n.reg .pred p;\n.reg .u32 v;\nLAB_WAIT:\nld.relaxed.gpu.global.u32 v, [%0];\nsub.u32 v, v, %1;\n"
               "setp.lt.s32 p, v, 0;\nvote.sync.any.pred p, p, 0xffffffff;\n@p bra LAB_WAIT;\n}" ::"l"(p), "r"(target) : "memory");
}
__device__ __forceinline__ void flag_signal(unsigned* flag) { asm volatile("red.release.gpu.global.add.u32 [%0], 1;" ::"l"(flag) : "memory"); }
struct Rel {
  bool on; uint32_t base;
  uint32_t tr;
  __device__ __forceinline__ void operator()(int s) const {
    if (on) asm volatile("{\n" SA("%0", "%1") "mbarrier.arrive.shared::cluster.b64 _, [sa];\n}" ::"r"(bar_empty(s)), "r"(base) : "memory");
  }
};
__device__ __forceinline__ uint32_t cta_window(uint32_t rank) { uint32_t a; asm("mapa.shared::cluster.u32 %0, %1, %2;" : "=r"(a) : "r"(0), "r"(rank)); return a; }
#define ELECT ".reg .pred e;\nelect.sync _|e, 0xffffffff;\n"
__device__ __forceinline__ void w_expect_tx(uint32_t bar, uint32_t bytes) {
  asm volatile("{\n" ELECT "@e mbarrier.arrive.expect_tx.shared::cta.b64 _, [%0], %1;\n}" ::"r"(bar), "r"(bytes) : "memory");
}
__device__ __forceinline__ void w_tma_2d_mc(uint32_t dst, const CUtensorMap* m, int c0, int c1, uint32_t bar) {
  asm volatile("{\n" ELECT "@e cp.async.bulk.tensor.2d.shared::cluster.global.mbarrier::complete_tx::bytes.multicast::cluster [%0], [%1, {%3, %4}], [%2], %5;\n}"
               ::"r"(dst), "l"(m), "r"(bar), "r"(c0), "r"(c1), "h"((uint16_t)3) : "memory");
}
__device__ __forceinline__ void w_bulk_load_mc(uint32_t dst, const void* src, uint32_t bytes, uint32_t bar) {
  asm volatile("{\n" ELECT "@e cp.async.bulk.shared::cluster.global.mbarrier::complete_tx::bytes.multicast::cluster [%0], [%1], %2, [%3], %4;\n}"
               ::"r"(dst), "l"(src), "r"(bytes), "r"(bar), "h"((uint16_t)3) : "memory");
}
__device__ __forceinline__ void w_bulk_load(uint32_t dst, const void* src, uint32_t bytes, uint32_t bar) {
  asm volatile("{\n" ELECT "@e cp.async.bulk.shared::cluster.global.mbarrier::complete_tx::bytes [%0], [%1], %2, [%3];\n}" ::"r"(dst), "l"(src), "r"(bytes), "r"(bar) : "memory");
}
__device__ __forceinline__ void w_l2_prefetch(const void* src, uint32_t bytes) { asm volatile("{\n" ELECT "@e cp.async.bulk.prefetch.L2.global [%0], %1;\n}" ::"l"(src), "r"(bytes) : "memory"); }
__device__ __forceinline__ void w_tma_prefetch(const CUtensorMap* m, int c0, int c1) {
  asm volatile("{\n" ELECT "@e cp.async.bulk.prefetch.tensor.2d.L2.global [%0, {%1, %2}];\n}" ::"l"(m), "r"(c0), "r"(c1) : "memory");
}
__device__ __forceinline__ void w_tma_3d(uint32_t dst, const CUtensorMap* m, int c0, int c1, int c2, uint32_t bar) {
  asm volatile("{\n" ELECT "@e cp.async.bulk.tensor.3d.shared::cluster.global.mbarrier::complete_tx::bytes [%0], [%1, {%3, %4, %5}], [%2];\n}"
               ::"r"(dst), "l"(m), "r"(bar), "r"(c0), "r"(c1), "r"(c2) : "memory");
}
__device__ __forceinline__ void wg_fence() { asm volatile("wgmma.fence.sync.aligned;" ::: "memory"); }
__device__ __forceinline__ void wg_commit() { asm volatile("wgmma.commit_group.sync.aligned;" ::: "memory"); }
template <int N> __device__ __forceinline__ void wg_wait() { asm volatile("wgmma.wait_group.sync.aligned %0;" ::"n"(N) : "memory"); }
__device__ __forceinline__ void bar_sync(int id, int n) { asm volatile("bar.sync %0, %1;" ::"r"(id), "r"(n) : "memory"); }
__device__ __forceinline__ void bar_arrive(int id, int n) { asm volatile("bar.arrive %0, %1;" ::"r"(id), "r"(n) : "memory"); }
__device__ __forceinline__ uint32_t pack_bf16(float lo, float hi) { uint32_t r; asm("cvt.rn.bf16x2.f32 %0, %1, %2;" : "=r"(r) : "f"(hi), "f"(lo)); return r; }
__device__ __forceinline__ float bf_lo(uint32_t w) { return __uint_as_float(w << 16); }
__device__ __forceinline__ float bf_hi(uint32_t w) { return __uint_as_float(w & 0xffff0000u); }
__device__ __forceinline__ float bf_round(float x) { return bf_lo(pack_bf16(x, 0.f)); }
__device__ __forceinline__ uint32_t bf2_sub(uint32_t a, uint32_t b) { uint32_t r; asm("sub.rn.bf16x2 %0, %1, %2;" : "=r"(r) : "r"(a), "r"(b)); return r; }
__device__ __forceinline__ uint32_t bf2_add(uint32_t a, uint32_t b) { uint32_t r; asm("add.rn.bf16x2 %0, %1, %2;" : "=r"(r) : "r"(a), "r"(b)); return r; }
#define GADDR(B, O, I) "cvt.u64.u32 ad, " O ";\nadd.u64 ad, ad, " B ";\nadd.u64 ad, ad, " I ";\n"
__device__ __forceinline__ void ld16(uint32_t* v, const uint8_t* ub, uint32_t off, uint32_t imm) {
  asm volatile("{\n.reg .b128 z;\n.reg .b64 x, y, ad;\n" GADDR("%4", "%5", "%6") "ld.relaxed.gpu.global.b128 z, [ad];\n"
               "mov.b128 {x, y}, z;\nmov.b64 {%0,%1}, x;\nmov.b64 {%2,%3}, y;\n}"
               : "=r"(v[0]), "=r"(v[1]), "=r"(v[2]), "=r"(v[3]) : "l"(ub), "r"(off), "l"((uint64_t)imm) : "memory");
}
__device__ __forceinline__ void ld8(uint32_t* v, const uint8_t* ub, uint32_t off, uint32_t imm) {
  asm volatile("{\n.reg .b64 x, ad;\n" GADDR("%2", "%3", "%4") "ld.relaxed.gpu.global.b64 x, [ad];\nmov.b64 {%0,%1}, x;\n}"
               : "=r"(v[0]), "=r"(v[1]) : "l"(ub), "r"(off), "l"((uint64_t)imm) : "memory");
}
__device__ __forceinline__ void st16(uint8_t* ub, uint32_t off, uint32_t imm, uint32_t a, uint32_t b, uint32_t c, uint32_t d) {
  asm volatile("{\n.reg .b128 z;\n.reg .b64 x, y, ad;\n" GADDR("%0", "%1", "%2") "mov.b64 x, {%3,%4};\nmov.b64 y, {%5,%6};\nmov.b128 z, {x, y};\n"
               "st.relaxed.gpu.global.b128 [ad], z;\n}" ::"l"(ub), "r"(off), "l"((uint64_t)imm), "r"(a), "r"(b), "r"(c), "r"(d) : "memory");
}
__device__ __forceinline__ void st8(uint8_t* ub, uint32_t off, uint32_t imm, uint32_t a, uint32_t b) {
  asm volatile("{\n.reg .b64 x, ad;\n" GADDR("%0", "%1", "%2") "mov.b64 x, {%3,%4};\nst.relaxed.gpu.global.b64 [ad], x;\n}"
               ::"l"(ub), "r"(off), "l"((uint64_t)imm), "r"(a), "r"(b) : "memory");
}
__device__ __forceinline__ void send8(uint8_t* ub, uint32_t off, uint32_t imm, uint32_t sm, int i, int j, uint32_t a, uint32_t b) {
  asm volatile("{\n.reg .pred p, q, e;\n.reg .b64 x, ad;\n" SA("%3", "%8") GADDR("%0", "%1", "%2")
               "setp.lt.s32 p, %4, %5;\nsetp.gt.s32 q, %4, %5;\nsetp.eq.s32 e, %4, %5;\nmov.b64 x, {%6,%7};\n"
               "@p st.relaxed.gpu.global.b64 [ad+-1024], x;\n@q st.relaxed.gpu.global.b64 [ad], x;\n@e st.shared.v2.u32 [sa], {%6,%7};\n}"
               ::"l"(ub), "r"(off), "l"((uint64_t)imm), "r"(sm), "r"(i), "r"(j), "r"(a), "r"(b), "r"(win()) : "memory");
}
__device__ __forceinline__ uint4 ldg_line(const void* p) {
  uint4 v; asm volatile("ld.global.nc.L2::128B.v4.u32 {%0,%1,%2,%3}, [%4];" : "=r"(v.x), "=r"(v.y), "=r"(v.z), "=r"(v.w) : "l"(p)); return v;
}
__device__ __forceinline__ uint32_t tid_() { uint32_t t; asm volatile("mov.u32 %0, %%tid.x;" : "=r"(t)); return t & 127; }
__device__ __forceinline__ uint32_t token() { uint32_t c; asm volatile("mov.u32 %0, %%clock;" : "=r"(c) :: "memory"); return c | 1; }
__device__ __forceinline__ uint32_t nz(uint32_t w) { return w ? w : 0x8000u; }
__device__ __forceinline__ void mma16816(float (&c)[4], uint32_t a0, uint32_t a1, uint32_t a2, uint32_t a3, uint32_t b0, uint32_t b1) {
  asm("mma.sync.aligned.m16n8k16.row.col.f32.bf16.bf16.f32 {%0,%1,%2,%3}, {%4,%5,%6,%7}, {%8,%9}, {%0,%1,%2,%3};"
               : "+f"(c[0]), "+f"(c[1]), "+f"(c[2]), "+f"(c[3]) : "r"(a0), "r"(a1), "r"(a2), "r"(a3), "r"(b0), "r"(b1));
}
__device__ __forceinline__ void mma1688(float (&c)[4], uint32_t a0, uint32_t a1, uint32_t b0) {
  asm("mma.sync.aligned.m16n8k8.row.col.f32.bf16.bf16.f32 {%0,%1,%2,%3}, {%4,%5}, {%6}, {%0,%1,%2,%3};"
               : "+f"(c[0]), "+f"(c[1]), "+f"(c[2]), "+f"(c[3]) : "r"(a0), "r"(a1), "r"(b0));
}
__device__ __forceinline__ float ex2(float x) { float r; asm("ex2.approx.ftz.f32 %0, %1;" : "=f"(r) : "f"(x)); return r; }

__device__ __forceinline__ void wgmma_rs_n64(float (&d)[32], uint32_t a0, uint32_t a1, uint32_t a2, uint32_t a3, uint64_t desc, int scale_d) {
  asm volatile("{\n.reg .pred p;\nsetp.ne.b32 p, %37, 0;\n"
    "wgmma.mma_async.sync.aligned.m64n64k16.f32.bf16.bf16 "
    "{%0, %1, %2, %3, %4, %5, %6, %7, %8, %9, %10, %11, %12, %13, %14, %15, %16, %17, %18, %19, %20, %21, %22, %23, %24, %25, %26, %27, %28, %29, %30, %31}, "
    "{%32, %33, %34, %35}, %36, p, 1, 1, 1;\n}\n"
    : "+f"(d[0]), "+f"(d[1]), "+f"(d[2]), "+f"(d[3]), "+f"(d[4]), "+f"(d[5]), "+f"(d[6]), "+f"(d[7]), "+f"(d[8]), "+f"(d[9]), "+f"(d[10]), "+f"(d[11]), "+f"(d[12]), "+f"(d[13]), "+f"(d[14]), "+f"(d[15]), "+f"(d[16]), "+f"(d[17]), "+f"(d[18]), "+f"(d[19]), "+f"(d[20]), "+f"(d[21]), "+f"(d[22]), "+f"(d[23]), "+f"(d[24]), "+f"(d[25]), "+f"(d[26]), "+f"(d[27]), "+f"(d[28]), "+f"(d[29]), "+f"(d[30]), "+f"(d[31])
    : "r"(a0), "r"(a1), "r"(a2), "r"(a3), "l"(desc), "r"(scale_d));
}

__device__ __forceinline__ void wgmma_rs_n72(float (&d)[36], uint32_t a0, uint32_t a1, uint32_t a2, uint32_t a3, uint64_t desc, int scale_d) {
  asm volatile("{\n.reg .pred p;\nsetp.ne.b32 p, %41, 0;\n"
    "wgmma.mma_async.sync.aligned.m64n72k16.f32.bf16.bf16 "
    "{%0, %1, %2, %3, %4, %5, %6, %7, %8, %9, %10, %11, %12, %13, %14, %15, %16, %17, %18, %19, %20, %21, %22, %23, %24, %25, %26, %27, %28, %29, %30, %31, %32, %33, %34, %35}, "
    "{%36, %37, %38, %39}, %40, p, 1, 1, 1;\n}\n"
    : "+f"(d[0]), "+f"(d[1]), "+f"(d[2]), "+f"(d[3]), "+f"(d[4]), "+f"(d[5]), "+f"(d[6]), "+f"(d[7]), "+f"(d[8]), "+f"(d[9]), "+f"(d[10]), "+f"(d[11]), "+f"(d[12]), "+f"(d[13]), "+f"(d[14]), "+f"(d[15]), "+f"(d[16]), "+f"(d[17]), "+f"(d[18]), "+f"(d[19]), "+f"(d[20]), "+f"(d[21]), "+f"(d[22]), "+f"(d[23]), "+f"(d[24]), "+f"(d[25]), "+f"(d[26]), "+f"(d[27]), "+f"(d[28]), "+f"(d[29]), "+f"(d[30]), "+f"(d[31]), "+f"(d[32]), "+f"(d[33]), "+f"(d[34]), "+f"(d[35])
    : "r"(a0), "r"(a1), "r"(a2), "r"(a3), "l"(desc), "r"(scale_d));
}

__device__ __forceinline__ void wgmma_rs_n128(float (&d)[64], uint32_t a0, uint32_t a1, uint32_t a2, uint32_t a3, uint64_t desc, int scale_d) {
  asm volatile("{\n.reg .pred p;\nsetp.ne.b32 p, %69, 0;\n"
    "wgmma.mma_async.sync.aligned.m64n128k16.f32.bf16.bf16 "
    "{%0, %1, %2, %3, %4, %5, %6, %7, %8, %9, %10, %11, %12, %13, %14, %15, %16, %17, %18, %19, %20, %21, %22, %23, %24, %25, %26, %27, %28, %29, %30, %31, %32, %33, %34, %35, %36, %37, %38, %39, %40, %41, %42, %43, %44, %45, %46, %47, %48, %49, %50, %51, %52, %53, %54, %55, %56, %57, %58, %59, %60, %61, %62, %63}, "
    "{%64, %65, %66, %67}, %68, p, 1, 1, 1;\n}\n"
    : "+f"(d[0]), "+f"(d[1]), "+f"(d[2]), "+f"(d[3]), "+f"(d[4]), "+f"(d[5]), "+f"(d[6]), "+f"(d[7]), "+f"(d[8]), "+f"(d[9]), "+f"(d[10]), "+f"(d[11]), "+f"(d[12]), "+f"(d[13]), "+f"(d[14]), "+f"(d[15]), "+f"(d[16]), "+f"(d[17]), "+f"(d[18]), "+f"(d[19]), "+f"(d[20]), "+f"(d[21]), "+f"(d[22]), "+f"(d[23]), "+f"(d[24]), "+f"(d[25]), "+f"(d[26]), "+f"(d[27]), "+f"(d[28]), "+f"(d[29]), "+f"(d[30]), "+f"(d[31]), "+f"(d[32]), "+f"(d[33]), "+f"(d[34]), "+f"(d[35]), "+f"(d[36]), "+f"(d[37]), "+f"(d[38]), "+f"(d[39]), "+f"(d[40]), "+f"(d[41]), "+f"(d[42]), "+f"(d[43]), "+f"(d[44]), "+f"(d[45]), "+f"(d[46]), "+f"(d[47]), "+f"(d[48]), "+f"(d[49]), "+f"(d[50]), "+f"(d[51]), "+f"(d[52]), "+f"(d[53]), "+f"(d[54]), "+f"(d[55]), "+f"(d[56]), "+f"(d[57]), "+f"(d[58]), "+f"(d[59]), "+f"(d[60]), "+f"(d[61]), "+f"(d[62]), "+f"(d[63])
    : "r"(a0), "r"(a1), "r"(a2), "r"(a3), "l"(desc), "r"(scale_d));
}

__device__ __forceinline__ void wgmma_rs_n144(float (&d)[72], uint32_t a0, uint32_t a1, uint32_t a2, uint32_t a3, uint64_t desc, int scale_d) {
  asm volatile("{\n.reg .pred p;\nsetp.ne.b32 p, %77, 0;\n"
    "wgmma.mma_async.sync.aligned.m64n144k16.f32.bf16.bf16 "
    "{%0, %1, %2, %3, %4, %5, %6, %7, %8, %9, %10, %11, %12, %13, %14, %15, %16, %17, %18, %19, %20, %21, %22, %23, %24, %25, %26, %27, %28, %29, %30, %31, %32, %33, %34, %35, %36, %37, %38, %39, %40, %41, %42, %43, %44, %45, %46, %47, %48, %49, %50, %51, %52, %53, %54, %55, %56, %57, %58, %59, %60, %61, %62, %63, %64, %65, %66, %67, %68, %69, %70, %71}, "
    "{%72, %73, %74, %75}, %76, p, 1, 1, 1;\n}\n"
    : "+f"(d[0]), "+f"(d[1]), "+f"(d[2]), "+f"(d[3]), "+f"(d[4]), "+f"(d[5]), "+f"(d[6]), "+f"(d[7]), "+f"(d[8]), "+f"(d[9]), "+f"(d[10]), "+f"(d[11]), "+f"(d[12]), "+f"(d[13]), "+f"(d[14]), "+f"(d[15]), "+f"(d[16]), "+f"(d[17]), "+f"(d[18]), "+f"(d[19]), "+f"(d[20]), "+f"(d[21]), "+f"(d[22]), "+f"(d[23]), "+f"(d[24]), "+f"(d[25]), "+f"(d[26]), "+f"(d[27]), "+f"(d[28]), "+f"(d[29]), "+f"(d[30]), "+f"(d[31]), "+f"(d[32]), "+f"(d[33]), "+f"(d[34]), "+f"(d[35]), "+f"(d[36]), "+f"(d[37]), "+f"(d[38]), "+f"(d[39]), "+f"(d[40]), "+f"(d[41]), "+f"(d[42]), "+f"(d[43]), "+f"(d[44]), "+f"(d[45]), "+f"(d[46]), "+f"(d[47]), "+f"(d[48]), "+f"(d[49]), "+f"(d[50]), "+f"(d[51]), "+f"(d[52]), "+f"(d[53]), "+f"(d[54]), "+f"(d[55]), "+f"(d[56]), "+f"(d[57]), "+f"(d[58]), "+f"(d[59]), "+f"(d[60]), "+f"(d[61]), "+f"(d[62]), "+f"(d[63]), "+f"(d[64]), "+f"(d[65]), "+f"(d[66]), "+f"(d[67]), "+f"(d[68]), "+f"(d[69]), "+f"(d[70]), "+f"(d[71])
    : "r"(a0), "r"(a1), "r"(a2), "r"(a3), "l"(desc), "r"(scale_d));
}

template <int N> struct WG;
template <> struct WG<64>  { static __device__ __forceinline__ void f(float (&d)[32], const uint32_t* a, uint64_t ds, int s) { wgmma_rs_n64(d, a[0], a[1], a[2], a[3], ds, s); } };
template <> struct WG<72>  { static __device__ __forceinline__ void f(float (&d)[36], const uint32_t* a, uint64_t ds, int s) { wgmma_rs_n72(d, a[0], a[1], a[2], a[3], ds, s); } };
template <> struct WG<128> { static __device__ __forceinline__ void f(float (&d)[64], const uint32_t* a, uint64_t ds, int s) { wgmma_rs_n128(d, a[0], a[1], a[2], a[3], ds, s); } };
template <> struct WG<144> { static __device__ __forceinline__ void f(float (&d)[72], const uint32_t* a, uint64_t ds, int s) { wgmma_rs_n144(d, a[0], a[1], a[2], a[3], ds, s); } };

constexpr uint64_t DESC_SW128 = ((uint64_t)(8192 >> 4) << 16) | ((uint64_t)(1024 >> 4) << 32) | (1ull << 62);
constexpr uint64_t DESC_KV = ((uint64_t)(128 >> 4) << 16) | ((uint64_t)(768 >> 4) << 32);
constexpr uint64_t DESC_Q = ((uint64_t)(128 >> 4) << 16) | ((uint64_t)(1536 >> 4) << 32);

template <int V> struct IntC { static constexpr int value = V; };
enum { PS_KV, PS_Q, PS_WO, PS_FF, PS_FFA   };
template <int PS> __host__ __device__ constexpr int pass_slot(int i) {
  return PS == PS_KV ? (i < 3 ? 9 + i : i - 3) : PS == PS_WO ? 6 + i : i;
}

__device__ __forceinline__ void load_frag(uint32_t (&a)[144], int i, const uint8_t* sb, uint32_t uo, uint32_t t) {
  if (i < 32) ld16(&a[4 * i], sb, uo + t * 16, i * 2048);
  else { ld8(&a[4 * i], sb, uo + t * 8, i * 2048); ld8(&a[4 * i + 2], sb, uo + t * 8, i * 2048 + 1024); }
}
__device__ __forceinline__ void store_own(const uint32_t (&y)[18], uint8_t* sb, uint32_t uo, int j, uint32_t t) {
#pragma unroll
  for (int i = 0; i < 4; i++) st16(sb, uo + j * 8192 + t * 16, i * 2048, nz(y[4 * i]), y[4 * i + 1], y[4 * i + 2], y[4 * i + 3]);
  st8(sb, uo + j * 1024 + t * 8, 65536, nz(y[16]), y[17]);
}
__device__ __forceinline__ void load_own(uint32_t* y, const uint8_t* sb, uint32_t uo, int j) {
  const uint32_t t = tid_();
#pragma unroll
  for (int i = 0; i < 4; i++) ld16(&y[4 * i], sb, uo + j * 8192 + t * 16, i * 2048);
  ld8(&y[16], sb, uo + j * 1024 + t * 8, 65536);
}

#define TR(i) do {} while (0)
struct NoTail { __device__ __forceinline__ void operator()() const {} };
template <int N, int PS, int KPS, int KSTEP, int CHK, bool SUB, bool HREL = false, class Tail = NoTail>
__device__ __forceinline__ void mma_pass(float (&acc)[N / 2], uint32_t (&a)[144], uint64_t desc, uint32_t par, const Rel& rel, int bar_id,
                                         const uint8_t* sb = nullptr, uint32_t uo = 0, uint32_t flag = 0, uint32_t m0 = 0, uint32_t m1 = 0, uint32_t park = 0, Tail tail = Tail()) {
  constexpr int NS = 36 / KPS;
  auto check = [&](int lo, int hi, uint32_t m0_) {
    auto missing = [&]() {
      uint32_t u[3] = {m0_, m0_, m0_};
#pragma unroll
      for (int i = hi - 1; i >= lo; i--) {
        u[i % 3] = min(u[i % 3], a[4 * i]);
        if (i >= 32) u[i % 3] = min(u[i % 3], a[4 * i + 2]);
      }
      return __any_sync(0xffffffffu, (min(u[0], min(u[1], u[2])) | flag) == 0);
    };
    if (__builtin_expect(missing(), 0)) {
      do {
        const uint32_t t = tid_();
#pragma unroll
        for (int i = lo; i < hi; i++) load_frag(a, i, sb, uo, t);
      } while (missing());
    }
  };
#pragma unroll
  for (int s = 0; s < NS; s++) {
    const int sl = pass_slot<PS>(s);
    if (CHK && s == 0 && !SUB) check(0, CHK * KPS, ~0u);
    if (CHK && s == CHK) check(CHK * KPS, 36, token());
    if (SUB) {
#pragma unroll
      for (int i = s * KPS * 4; i < (s + 1) * KPS * 4; i += 2) { a[i] = bf2_sub(a[i], m0); a[i + 1] = bf2_sub(a[i + 1], m1); }
    }
    if (PS == PS_KV && bar_id < 0 && (s == 0 || s == KV_S1) && (s == (flag ? KV_S1 : 0))) bar_sync(NB_ORD1, 256);
    if (PS == PS_KV && s == 0) sts128(park + tid_() * 16, a[0], a[1], a[2], a[3]);
    constexpr int TB = PS == PS_KV ? 0 : PS == PS_Q ? 26 : PS == PS_WO ? 40 : SUB ? 54 : PS == PS_FFA ? 74 : -1;
    if (TB >= 0) TR(TB + 2 * s);
    mbar_wait(bar_full(sl), sl < 9 ? par : par ^ 1);
    if (TB >= 0) TR(TB + 2 * s + 1);
    wg_fence();
#pragma unroll
    for (int kk = 0; kk < KPS; kk++)
      WG<N>::f(acc, &a[(s * KPS + kk) * 4], desc + ((slot_addr(sl) + kk * KSTEP) >> 4), (s | kk) || PS == PS_FFA);
    wg_commit();
    if (CHK && s < 2 && N_UP < 36 && !flag) {
      const uint32_t t = tid_();
#pragma unroll
      for (int i = s ? (N_UP + 36) / 2 : N_UP; i < (s ? 36 : (N_UP + 36) / 2); i++) load_frag(a, i, sb, uo, t);
    }
    if (PS == PS_KV ? (s == KV_LEAD || s == KV_S1 + KV_LEAD) && s == (flag ? KV_S1 : 0) + KV_LEAD : s == NS - 1)
      if (bar_id >= 0) bar_arrive(bar_id, 256);
    if (s > 0) {
      wg_wait<1>();
      if (!(PS == PS_WO && s > 3)) rel(pass_slot<PS>(s - 1));
    }
    if (HREL && s == 3 && flag) {
#pragma unroll
      for (int i = 0; i < 12; i++) ld16(&a[4 * i], sb, uo, i * 2048);
    }
  }
  constexpr int TE = PS == PS_KV ? 24 : PS == PS_Q ? 38 : PS == PS_WO ? 52 : SUB ? 72 : PS == PS_FFA ? 92 : -1;
  tail();
  if (TE >= 0) TR(TE);
  wg_wait<0>();
  if (TE >= 0) TR(TE + 1);
  if (PS != PS_WO) rel(pass_slot<PS>(NS - 1));
}

template <int NF, int N0 = 0> __device__ __forceinline__ void load_frags(uint32_t (&a)[144], const uint8_t* sb, uint32_t uo, uint32_t t) {
#pragma unroll
  for (int i = N0; i < NF; i++) load_frag(a, i, sb, uo, t);
}
__device__ __forceinline__ void ln_scalars(float s1, float s2, uint32_t& m, float& var, uint32_t zero) {
  const float mean = s1 * (1.f / DM);
  var = s2 * (1.f / DM) - mean * mean;
  m = pack_bf16(mean, mean) ^ (__float_as_uint(var) & zero);
}
__device__ __forceinline__ float ln_rstd(float var, float after, uint32_t zero) {
  var = __uint_as_float(__float_as_uint(var) ^ (__float_as_uint(after) & zero));
  float sd, r;
  asm("sqrt.approx.ftz.f32 %0, %1;" : "=f"(sd) : "f"(bf_round(bf_round(fmaxf(var, 0.f)) + 1e-5f)));
  asm("rcp.approx.ftz.f32 %0, %1;" : "=f"(r) : "f"(bf_round(sd)));
  return r;
}
template <int NF> __device__ __forceinline__ void gather_ln(uint32_t (&a)[144], const uint8_t* sb, uint32_t uo, uint32_t sto,
                                          uint32_t& m0, uint32_t& m1, float& r0, float& r1, uint32_t zero) {
  uint32_t u[32];
  const uint32_t t = tid_(), so = sto + (t >> 5) * 1024 + (t & 28) * 4;
#pragma unroll
  for (int i = 0; i < 8; i++) ld16(&u[4 * i], sb, so, OFF_ST + i * 128);
  load_frags<N_UP>(a, sb, uo, t);
  while (true) {
    uint32_t m = a[4 * NF - 4];
#pragma unroll
    for (int i = NF - 2; i >= 0; i--) m = min(m, a[4 * i]);
#pragma unroll
    for (int i = 0; i < 8; i++) m = min(m, u[4 * i]);
    if (!__any_sync(0xffffffffu, m == 0)) break;
#pragma unroll
    for (int i = 0; i < 8; i++) ld16(&u[4 * i], sb, so, OFF_ST + i * 128);
    load_frags<NF>(a, sb, uo, t);
  }
  float v[4];
#pragma unroll
  for (int k = 0; k < 4; k++)
    v[k] = ((__uint_as_float(u[k]) + __uint_as_float(u[4 + k])) + (__uint_as_float(u[8 + k]) + __uint_as_float(u[12 + k]))) +
           ((__uint_as_float(u[16 + k]) + __uint_as_float(u[20 + k])) + (__uint_as_float(u[24 + k]) + __uint_as_float(u[28 + k])));
  ln_scalars(v[1], v[0], m0, r0, zero); ln_scalars(v[3], v[2], m1, r1, zero);
}
struct Stats {
  float s[4] = {0, 0, 0, 0}, d0[4] = {0, 0, 0, 0}, d1[4] = {0, 0, 0, 0};
  __device__ __forceinline__ void add16(const uint32_t* f) {
    mma16816(s, f[0], f[1], f[2], f[3], 0x3f803f80u, 0x3f803f80u);
    mma1688(d0, f[0], f[1], f[0]); mma1688(d1, f[0], f[1], f[1]);
    mma1688(d0, f[2], f[3], f[2]); mma1688(d1, f[2], f[3], f[3]);
  }
  __device__ __forceinline__ float sq0(int g) const { return (g & 1) ? d0[1] : d0[0]; }
  __device__ __forceinline__ float sq1(int g) const { return (g & 1) ? d1[3] : d1[2]; }
};
struct RowStats {
  float s[4] = {0, 0, 0, 0}, u[4] = {0, 0, 0, 0};
  template <int N> __device__ __forceinline__ void add(const uint32_t* y) {
#pragma unroll
    for (int i = 0; i < N; i++) {
      const float lo = bf_lo(y[i]), hi = bf_hi(y[i]);
      const int r = (i & 1) * 2;
      s[r] = fmaf(lo, lo, s[r]); u[r] = fmaf(hi, hi, u[r]); s[r + 1] += lo; u[r + 1] += hi;
    }
  }
  __device__ __forceinline__ uint32_t fold() {
    uint32_t x = 0;
#pragma unroll
    for (int i = 0; i < 4; i++) { s[i] += u[i]; u[i] = 0; x |= __float_as_uint(s[i]); }
    return x;
  }
  __device__ __forceinline__ void store(uint8_t* sb, uint32_t sto, uint32_t t) {
    fold();
#pragma unroll
    for (int i = 0; i < 4; i++) s[i] += __shfl_xor_sync(0xffffffffu, s[i], 1);
#pragma unroll
    for (int i = 0; i < 4; i++) s[i] += __shfl_xor_sync(0xffffffffu, s[i], 2);
    if ((t & 3) == 0) st16(sb, sto + (t >> 5) * 1024 + (t & 28) * 4, OFF_ST, __float_as_uint(s[0]) | 1u, __float_as_uint(s[1]), __float_as_uint(s[2]), __float_as_uint(s[3]));
  }
};
template <bool SET> __device__ __forceinline__ void add_piece(float* acc, uint32_t sm) {
#pragma unroll
  for (int i = 0; i < 4; i++) {
    uint32_t v[4];
    lds128(v, sm + i * 2048);
#pragma unroll
    for (int k = 0; k < 4; k++) {
      acc[8 * i + 2 * k] = SET ? bf_lo(v[k]) : acc[8 * i + 2 * k] + bf_lo(v[k]);
      acc[8 * i + 2 * k + 1] = SET ? bf_hi(v[k]) : acc[8 * i + 2 * k + 1] + bf_hi(v[k]);
    }
  }
}

#define TS(i) do {} while (0)
#define TSP(i) do {} while (0)
#define TSH(i) do {} while (0)

__device__ __forceinline__ uint32_t row_off(int rb, int wg, uint32_t t) { return (rb * 128 + wg + ((t >> 5) * 16 + (t & 15)) * 2) * (2 * DM); }

__device__ __forceinline__ const __nv_bfloat16* wo_src(const __nv_bfloat16* wo, int k, int u, int j) {
  const int ko = k < 512 ? (k >> 6) * 72 + (k & 63) : ((k >> 3) & 7) * 72 + 64 + (k & 7);
  return wo + ko * 576 + (u < 8 ? j * 64 + u * 8 : 512 + j * 8);
}

struct Params {
  const __nv_bfloat16* wqkv;
  uint8_t* scr;
  uint8_t role[64];
  const __nv_bfloat16* wo;
  __nv_bfloat16* out;
  uint8_t* times;
  unsigned zero;
};

__cluster_dims__(2, 1, 1)
__global__ void __launch_bounds__(384, 1)
fused_kernel(const __grid_constant__ Params P, const __grid_constant__ CUtensorMap map_x, const __grid_constant__ CUtensorMap map_x1,
             const __grid_constant__ CUtensorMap map_wg,
             const __grid_constant__ CUtensorMap map_wu, const __grid_constant__ CUtensorMap map_wd) {
  const int wg = __shfl_sync(0xffffffffu, threadIdx.x >> 7, 0);
  const int cta = blockIdx.x, rank = cta & 1, role = P.role[cta >> 1], j = role & 7, rb = (role >> 3) * 2 + rank;
  const uint32_t own = win();
  unsigned* const flags = (unsigned*)(P.scr + OFF_FLAGS);
  if (__shfl_sync(0xffffffffu, threadIdx.x >> 5, 0) == 11) {
    if (threadIdx.x == 352) {
#pragma unroll
      for (int i = 0; i < 14; i++) { mbar_init(bar_full(i), 1); mbar_init(bar_empty(i), i < 12 ? 4 : i == 12 ? 8 : 2); }
      mbar_init(bar_full(14), 1); mbar_init(bar_empty(14), 1);
      mbar_init(BAR_X, 1); mbar_init(BAR_X + 8, 1);
      asm volatile("fence.mbarrier_init.release.cluster;" ::: "memory");
      if (smem_u32(smem_raw) != own + SB) asm volatile("trap;");
    }
    __syncwarp();
    asm volatile("barrier.cluster.arrive.relaxed.aligned;" ::: "memory");
#pragma unroll
    for (int c = 0; c < 9; c++) {
      w_tma_3d(own + slot_addr(c), &map_x, c * 64, rb * 64, 0, own + bar_full(c));
      w_expect_tx(own + bar_full(c), SLOT);
    }
  } else {
    const bool on = threadIdx.x < 324;
    const int k = rb * 36 + (on ? threadIdx.x / 36 : 0) * 4 + (threadIdx.x & 3), u = (threadIdx.x % 36) >> 2;
    const uint4* s = (const uint4*)(P.wqkv + k * 1728 + j * 72 + u * 8);
    const uint4 vk = ldg_line(s + 72), vv = ldg_line(s + 144);
    const unsigned ep0 = *(volatile unsigned*)&flags[(72 + cta) * 8];
    asm volatile("barrier.cluster.arrive.relaxed.aligned;" ::: "memory");
    uint8_t* d = P.scr + OFF_WPACK + j * 24 * PSLOT;
    if (on) {
      const uint32_t dkv = (k / 48) * PSLOT + u * 768 + (k % 48) * 16;
      st16(d, dkv, 0, vk.x, vk.y, vk.z, vk.w);
      st16(d, dkv, 9 * 768, vv.x, vv.y, vv.z, vv.w);
    }
    asm volatile("fence.proxy.async.global;" ::: "memory");
    bar_arrive(NB_PUB + 3, 384);
    if (threadIdx.x == 351) sts32(SM_EPOCH, ep0);
    if (wg == 2) bar_sync(NB_PUB + 1, 96);
  }
  __syncwarp();
  asm volatile("barrier.cluster.wait.acquire.aligned;" ::: "memory");

  if (wg == 2) {
    asm volatile("setmaxnreg.dec.sync.aligned.u32 24;");
    const int pw = __shfl_sync(0xffffffffu, (threadIdx.x >> 5) & 3, 0), lane = threadIdx.x & 31;
    auto tile_col = [](int t, int h, int j) { return t < 9 ? j * 576 + t * 64 : (t == 9 && h) ? 512 : ((j + ((h ? 0x05760 : 0x04123) >> (4 * (t - 9)))) & 7) * 64; };
    auto prefetch_tile = [&](int t) {
#pragma unroll 1
      for (int b = rb; b < 18; b += 16) {
        const int h = b & 1, k = b >> 1;
        if (t < 9) w_tma_prefetch(h ? &map_wu : &map_wg, tile_col(t, h, j), k * 64);
        else if (t != 13 || !h) w_tma_prefetch(&map_wd, tile_col(t, h, j), j * 576 + k * 64);
      }
    };
    if (pw == 0) {
      {
        flag_wait(&flags[j * 8], (lds32(SM_EPOCH) + 1) * 16);
        TSP(7);
        asm volatile("fence.proxy.async.global;" ::: "memory");
        const uint8_t* wp = P.scr + OFF_WPACK + j * 24 * PSLOT;
        wp += rank * (PSLOT / 2);
        auto packed = [&](int sl, uint32_t par, int f) {
          mbar_wait(bar_empty(0) + sl * 8, par);
          w_bulk_load_mc(own + SB + rank * (PSLOT / 2) + sl * SLOT, wp + f * PSLOT, PSLOT / 2, own + bar_full(0) + sl * 8);
          w_expect_tx(own + bar_full(0) + sl * 8, PSLOT);
        };
        const uint32_t half = own + SB + rank * 8192;
#pragma unroll 1
        for (int L = 0; L < 2; L++) {
#pragma unroll 1
          for (int s = L ? 0 : -3; s < 21; s++) {
            if (s == 9 && L == 0) { flag_wait(&flags[(56 + j) * 8], (lds32(SM_EPOCH) + 1) * 16); asm volatile("fence.proxy.async.global;" ::: "memory"); }
            packed(s < 0 ? s + 12 : s < 9 ? s : s - 9, s < 0 || (s >= 9 && s < 18), s + 3);
          }
#pragma unroll 1
          for (int t = 0; t < 14; t++) {
            if (L * 14 + t + PF_AHEAD < 28) prefetch_tile((t + PF_AHEAD) % 14);
            const CUtensorMap* mp = t >= 9 ? &map_wd : rank ? &map_wu : &map_wg;
            const bool nar = t == 13;
            const int col = tile_col(t, nar ? 0 : rank, j);
            const uint32_t dst = nar ? own + SB : half, bytes = nar ? 8192 : SLOT;
            const int ra = t < 9 ? 0 : j * 576 + 320, rbs = t < 9 ? 0 : j * 576 - 192, rc = t < 9 ? 0 : j * 576;
#pragma unroll
            for (int k = 0; k < 9; k++) {
              mbar_wait(bar_empty(k), t & 1);
              if (!nar || rank == (k & 1)) w_tma_2d_mc(dst + k * SLOT, mp, col, (k < 3 ? ra : k < 8 ? rbs : rc) + k * 64, own + bar_full(k));
              w_expect_tx(own + bar_full(k), bytes);
            }
            if (t == 12 && L == 0) {
              w_l2_prefetch(P.scr + OFF_WPACK + j * 24 * PSLOT + rb * (24 * PSLOT / 16), 24 * PSLOT / 16);
#pragma unroll 1
              for (int s = 0; s < 3; s++) packed(9 + s, 1, s);
            }
          }
        }
        flags[(72 + cta) * 8] = lds32(SM_EPOCH) + 1;
      }
    } else if (pw < 3) {
      const int hw = pw - 1;
      const uint32_t ep = __shfl_sync(0xffffffffu, lds32(SM_EPOCH), 0);
      uint8_t* const sb = P.scr + (rb * 2 + hw) * STRM;
      const uint32_t xs = slot_addr(12) + hw * SLOT, fb = bar_full(12) + hw * 8;
      uint32_t hph = 0;
#pragma unroll 1
      for (int L = 0; L < 2; L++) {
        const uint32_t tag = ep * 2 + L + 1;
        bar_sync(NB_FREE + hw, 160);
        if (rb > 0) hint_wait(sb + OFF_HINT + 512 + j * 128, tag);
        uint32_t bad;
        do {
          if (rb > 0) {
            w_bulk_load(own + ytail(hw * 2), sb + OFF_HALO + (L * 8 + j) * 3072, 1536, own + bar_full(14) + hw * 128);
            w_bulk_load(own + ytail(hw * 2 + 1), sb + OFF_HALO + (L * 8 + j) * 3072 + 1536, 1536, own + bar_full(14) + hw * 128);
            w_expect_tx(own + bar_full(14) + hw * 128, 3072);
            mbar_wait(bar_full(14) + hw * 128, hph);
            hph ^= 1;
          }
          bad = 0;
#pragma unroll 1
          for (int c = 0; c < 3; c++) {
            uint32_t u[4] = {tag, 0, 0, 0}, v[4] = {tag, 0, 0, 0};
            if (rb > 0) { lds128(u, ytail(hw * 2) + c * 512 + lane * 16); lds128(v, ytail(hw * 2 + 1) + c * 512 + lane * 16); }
            bad |= (u[0] ^ tag) | (v[0] ^ tag);
#pragma unroll
            for (int i = 0; i < 3; i++) { sts32(xs + KSTG + (c * 3 + i) * 128 + lane * 4, u[i + 1]); sts32(xs + (c * 3 + i) * 128 + lane * 4, v[i + 1]); }
          }
        } while (__any_sync(0xffffffffu, bad != 0));
        bar_arrive(NB_HALO + hw, 160);
        if (L == 0) {
          bar_sync(NB_FREE + hw, 160);
          asm volatile("fence.proxy.async.shared::cta;" ::: "memory");
          w_tma_3d(own + xs, &map_x1, j * 64, rb * 64, hw, own + BAR_X + hw * 8);
          w_tma_3d(own + xs + 8192, &map_x1, 512, rb * 64, hw, own + BAR_X + hw * 8);
          w_expect_tx(own + BAR_X + hw * 8, SLOT);
        }
#pragma unroll 1
        for (int p = 0; p < 4; p++) {
          if (L == 0 && p == 3) flag_wait(flags + (40 + rb) * 8, (ep + 1) * 8);
          bar_sync(NB_FREE + hw, 160);
          TSH(L * 12 + p * 3);
          hint_wait(sb + OFF_HINT + (lane & 3) * 128, (ep * 13 + L * 7 + p + 3) * 8);
          TSH(L * 12 + p * 3 + 1);
          w_bulk_load(own + xs, sb + OFF_P + j * PSRC + (p & 1) * 16384, p ? 16384 : 8192, own + fb);
          if (p == 0) w_bulk_load(own + xs + 8192, sb + OFF_P + j * PSRC + 32768, 7168, own + fb);
          w_expect_tx(own + fb, p ? 16384 : 15360);
          TSH(L * 12 + p * 3 + 2);
        }
      }
    } else {
      auto clear = [&](int t) {
        const uint32_t so = rb * 2 * STRM + (threadIdx.x & 31) * 16;
#pragma unroll 1
        for (int i = 0; i < 18; i++) {
          st16(P.scr, so + t * TILE + j * 9216 + i * 512, 0, 0, 0, 0, 0);
          st16(P.scr, so + t * TILE + j * 9216 + i * 512, STRM, 0, 0, 0, 0);
          __nanosleep(0);
        }
        if (t != 1) {
          st16(P.scr, so + (t ? t - 1 : 0) * 4096 + j * 512, OFF_ST, 0, 0, 0, 0);
          st16(P.scr, so + (t ? t - 1 : 0) * 4096 + j * 512, OFF_ST + STRM, 0, 0, 0, 0);
        }
      };
      bar_sync(NB_PUB + 3, 384);
      if (lane == 0) flag_signal(&flags[j * 8]);
      TSP(5);
      bar_sync(NB_PUB + 2, 288);
      if (lane == 0) flag_signal(&flags[(56 + j) * 8]);
      TSP(4);
      __syncwarp();
#pragma unroll 1
      for (int t = 0; t < PF_AHEAD; t++) prefetch_tile(t);
      __syncwarp();
#pragma unroll 1
      for (int L = 0; L < 2; L++) {
        timed_wait(bar_empty(13), L);
#pragma unroll 1
        for (int t = L ^ 1; t < 4 - 2 * L; t++) clear(t);
        __syncwarp();
        if (lane == 0 && L == 0) flag_signal(flags + (40 + rb) * 8);
      }
      timed_wait(bar_empty(12), 0);
      asm volatile("barrier.cluster.arrive.relaxed.aligned;\nbarrier.cluster.wait.aligned;" ::: "memory");
    }
  } else {
    asm volatile("setmaxnreg.inc.sync.aligned.u32 240;");
    const int w = __shfl_sync(0xffffffffu, (threadIdx.x >> 5) & 3, 0);
    Rel rel{(threadIdx.x & 95) == 0, cta_window(w & 1), 0};
    uint8_t* const sb = P.scr + (rb * 2 + wg) * STRM;
    uint8_t* const hint = sb + OFF_HINT + w * 128;
    auto hint_target = [](int e) { return (lds32(SM_EPOCH) * 13 + e + 1) * 8; };
    TS(0);
    uint32_t a[144];
#pragma unroll 1
    for (int L = 0; L < 2; L++) {
      uint32_t m0, m1; float r0, r1;
      rel.tr = win() + ytail(3) + 1536 + (L == TRACE - 1 && w == 1 ? wg * 384 : 768);
      if (L == 0) {
        Stats st;
        const int lane = tid_() & 31, g = lane >> 2;
        const int row = w * 16 + (lane & 15);
        const uint32_t ra = SB + wg * 8192 + row * 128;
        const uint32_t pt = tid_(), pu = (pt % 36) >> 2, pk = rb * 36 + (pt < 108 ? pt / 36 : 0) * 4 + (pt & 3);
        uint4 pv[3];
#pragma unroll
        for (int i = 0; i < 3; i++) pv[i] = ldg_line(wg ? wo_src(P.wo, pk + i * 12, pu, j) : P.wqkv + (pk + i * 12) * 1728 + j * 72 + pu * 8);
#pragma unroll
        for (int c = 0; c < 9; c++) {
          mbar_wait(bar_full(c), 0);
          if (c == 0) TS(60); if (c == 8) TS(62);
#pragma unroll
          for (int kk = 0; kk < 4; kk++) ldsm4(&a[c * 16 + kk * 4], ra + (((kk * 2 + (lane >> 4)) ^ (row & 7)) << 4) + c * SLOT);
          if (c == 8) {
            bar_sync(NB_WG + wg + (a[140] & P.zero), 128);
#pragma unroll
            for (int i = 0; i < 9; i++) rel(i);
          }
#pragma unroll
          for (int kk = 0; kk < 4; kk++) st.add16(&a[c * 16 + kk * 4]);
        }
        const int dl = (lane & ~3) | (g >> 1);
        ln_scalars(st.s[0], __shfl_sync(0xffffffffu, st.sq0(g), dl), m0, r0, P.zero);
        ln_scalars(st.s[2], __shfl_sync(0xffffffffu, st.sq1(g), dl), m1, r1, P.zero);
        if (pt < 108) {
#pragma unroll
          for (int i = 0; i < 3; i++) {
            const uint32_t k = pk + i * 12 + ((m0 | m1) & P.zero);
            st16(P.scr, (j * 24 + wg * 6 + k / 96) * PSLOT + pu * 1536 + (k % 96) * 16, OFF_WPACK + 12 * PSLOT, pv[i].x, pv[i].y, pv[i].z, pv[i].w);
          }
        }
        asm volatile("fence.proxy.async.global;" ::: "memory");
        bar_arrive(NB_PUB + 2, 288);
      } else {
#pragma unroll
        for (int i = 4 * N_UP; i < 144; i++) a[i] = 0;
        hint_wait(hint, hint_target(6));
        TS(61);
        gather_ln<3 * D_KV>(a, sb, OFF_X2, 8192, m0, m1, r0, r1, P.zero);
      }
      TS(1 + L * 20);
      uint32_t kf[18], qf[18];
      {
        float acc[72];
        mma_pass<144, PS_KV, 3, 256, D_KV, true>(acc, a, DESC_KV, 1, rel, wg == 0 ? NB_ORD1 : -1, sb, OFF_X2, L ^ 1, m0, m1, ytail(wg * 2));
        r0 = ln_rstd(r0, acc[0], P.zero); r1 = ln_rstd(r1, acc[0], P.zero);
        uint32_t vf[18];
#pragma unroll
        for (int c = 0; c < 9; c++) {
          kf[c] = pack_bf16(acc[4 * c] * r0, acc[4 * c + 1] * r0);
          kf[9 + c] = pack_bf16(acc[4 * c + 2] * r1, acc[4 * c + 3] * r1);
          vf[c] = pack_bf16(acc[36 + 4 * c] * r0, acc[36 + 4 * c + 1] * r0);
          vf[9 + c] = pack_bf16(acc[36 + 4 * c + 2] * r1, acc[36 + 4 * c + 3] * r1);
        }
        TS(2 + L * 20);
        const uint32_t l16 = (tid_() & 31) * 16, xs = slot_addr(12) + wg * SLOT + w * 1152;
#pragma unroll
        for (int i = 0; i < 4; i++) stsm4(xs + w * 1152 + 1152 + i * 512 + l16, vf[4 * i], vf[4 * i + 1], vf[4 * i + 2], vf[4 * i + 3]);
        sts32(xs + w * 1152 + 1152 + 2048 + l16 / 4, vf[16]); sts32(xs + w * 1152 + 1152 + 2176 + l16 / 4, vf[17]);
        if (w < 3) {
          stsm4(xs + KSTG + 1152 + l16, kf[9], kf[10], kf[11], kf[12]);
          stsm4(xs + KSTG + 1152 + 512 + l16, kf[13], kf[14], kf[15], kf[16]);
          sts32(xs + KSTG + 1152 + 1024 + l16 / 4, kf[17]);
        } else if (rb < 15) {
          const uint32_t tag = lds32(SM_EPOCH) * 2 + L + 1;
          const uint32_t ho = l16 + (L * 8 + j) * 3072;
#pragma unroll
          for (int c = 0; c < 3; c++) {
            st16(sb, ho, 2 * STRM + OFF_HALO + c * 512, tag, kf[9 + 3 * c], kf[10 + 3 * c], kf[11 + 3 * c]);
            st16(sb, ho, 2 * STRM + OFF_HALO + 1536 + c * 512, tag, vf[9 + 3 * c], vf[10 + 3 * c], vf[11 + 3 * c]);
          }
          hint_post(sb + 2 * STRM + OFF_HINT + 512 + j * 128);
        }
      }
      lds128(a, ytail(wg * 2) + tid_() * 16);
      bar_arrive(NB_FREE + wg + (a[0] & P.zero), 160);
      uint32_t kh[12], vp[20], v1[12];
      {
        float acc[36];
        if (wg == 1) bar_sync(NB_ORD1, 256);
        mma_pass<72, PS_Q, 6, 256, 0, false, false>(acc, a, DESC_Q, 0, rel, -1, nullptr, 0, 0, 0, 0, 0, [&]() {
          bar_sync(NB_HALO + wg, 160);
#pragma unroll
          for (int i = 0; i < 3; i++) ldsm4(&kh[4 * i], slot_addr(12) + wg * SLOT + w * 640 + tid_() * 16 + KSTG + i * 512);
          const uint32_t l = tid_() & 31, vb = slot_addr(12) + wg * SLOT + w * 2304;
#pragma unroll
          for (int i = 0; i < 5; i++) ldsm4t(&vp[4 * i], vb + (l & 8) * 144 + (l & 16) * 8 + (l & 7) * 16 + i * 256);
#pragma unroll
          for (int i = 0; i < 3; i++) ldsm4t(&v1[4 * i], vb + 2304 + l * 16 + i * 512);
        });
#pragma unroll
        for (int i = 0; i < 18; i++) qf[i] = pack_bf16(acc[2 * i], acc[2 * i + 1]);
      }
      TS(3 + L * 20);
      uint32_t xr[18];
      {
        const int tid = tid_(), g = (tid >> 2) & 7, q = tid & 3;
        const bool nohalo = (rb == 0 && w == 0);
        const bool le0 = 2 * q <= g, le1 = 2 * q + 1 <= g;
        const uint32_t M = (le0 ? 0xffffu : 0u) | (le1 ? 0xffff0000u : 0u);
        const float sc0 = r0 * (0.23570226039551584f * 1.4426950408889634f), sc1 = r1 * (0.23570226039551584f * 1.4426950408889634f);
        float l[16], t[8];
#pragma unroll
        for (int h = 0; h < 4; h++) {
          const uint32_t qa0 = q >= h ? qf[4 * h] : 0u, qa1 = q >= h ? qf[4 * h + 1] : 0u;
          const uint32_t qc0 = q <= h ? qf[4 * h + 4] : 0u, qc1 = q <= h ? qf[4 * h + 5] : 0u;
          float sm[4] = {0, 0, 0, 0}, s0[4] = {0, 0, 0, 0}, s1[4] = {0, 0, 0, 0};
          mma16816(s0, qa0, qa1, qf[4 * h + 2], qf[4 * h + 3], kf[2 * h], kf[2 * h + 1]);
          mma16816(s1, qa0, qa1, qf[4 * h + 2], qf[4 * h + 3], kf[9 + 2 * h], kf[10 + 2 * h]);
          mma16816(sm, qa0, qa1, qf[4 * h + 2], qf[4 * h + 3], kh[2 * h], kh[2 * h + 1]);
          mma1688(s0, qc0, qc1, kf[2 * h + 2]);
          mma1688(s1, qc0, qc1, kf[11 + 2 * h]);
          mma1688(sm, qc0, qc1, kh[2 * h + 2]);
          if (nohalo) sm[0] = sm[1] = -3e38f;
          l[4 * h] = le0 ? s0[0] : sm[0]; l[4 * h + 1] = le1 ? s0[1] : sm[1];
          l[4 * h + 2] = le0 ? s1[2] : s0[2]; l[4 * h + 3] = le1 ? s1[3] : s0[3];
        }
#pragma unroll
        for (int i = 0; i < 8; i++) t[i] = fmaxf(l[2 * i], l[2 * i + 1]);
        TS(14 + L * 20);
#pragma unroll
        for (int i = 0; i < 8; i++) t[i] = fmaxf(t[i], __shfl_xor_sync(0xffffffffu, t[i], 1));
#pragma unroll
        for (int i = 0; i < 8; i++) t[i] = fmaxf(t[i], __shfl_xor_sync(0xffffffffu, t[i], 2)) * ((i & 1) ? sc1 : sc0);
#pragma unroll
        for (int i = 0; i < 8; i++) {
          const float sc = (i & 1) ? sc1 : sc0;
          l[2 * i] = ex2(fmaf(l[2 * i], sc, -t[i])); l[2 * i + 1] = ex2(fmaf(l[2 * i + 1], sc, -t[i])); t[i] = l[2 * i] + l[2 * i + 1];
        }
#pragma unroll
        for (int i = 0; i < 8; i++) t[i] += __shfl_xor_sync(0xffffffffu, t[i], 1);
#pragma unroll
        for (int i = 0; i < 8; i++) t[i] += __shfl_xor_sync(0xffffffffu, t[i], 2);
        uint32_t pf[16], pz[8];
#pragma unroll
        for (int i = 0; i < 8; i++) {
          float r; asm("rcp.approx.ftz.f32 %0, %1;" : "=f"(r) : "f"(t[i]));
          const uint32_t p = pack_bf16(l[2 * i] * r, l[2 * i + 1] * r);
          pf[2 * i] = p & ~M; pf[2 * i + 1] = p & M; pz[i] = p & P.zero;
        }
#pragma unroll
        for (int c = 0; c < 9; c++) {
          const int h = c == 8 ? 3 : c >> 1;
          float o[4] = {0, 0, 0, 0};
          mma16816(o, pf[4 * h], pz[2 * h], pf[4 * h + 1], pf[4 * h + 2], vp[2 * c], vp[2 * c + 1]);
          mma1688(o, pz[2 * h + 1], pf[4 * h + 3], v1[c]);
          if (c == 2 || c == 4 || c == 6) {
            float e[4] = {0, 0, 0, 0};
            mma16816(e, pf[4 * h - 4], pz[2 * h - 2], pf[4 * h - 3], pf[4 * h - 2], vp[2 * c], vp[2 * c + 1]);
            mma1688(e, pz[2 * h - 1], pf[4 * h - 1], v1[c]);
            const uint32_t u = pack_bf16(e[0], e[1]), v = pack_bf16(e[2], e[3]);
            qf[2 * c] = q < h ? u : pack_bf16(o[0], o[1]); qf[2 * c + 1] = q < h ? v : pack_bf16(o[2], o[3]);
          } else {
            qf[2 * c] = pack_bf16(o[0], o[1]); qf[2 * c + 1] = pack_bf16(o[2], o[3]);
          }
        }
        {
          uint32_t x = 0;
#pragma unroll
          for (int i = 0; i < 18; i += 2) x |= qf[i];
          bar_arrive(NB_ORD1 - wg + (x & P.zero), 256);
        }
        store_own(qf, sb, OFF_O, j, tid);
        hint_post(hint);
        if (L) load_own(xr, sb, OFF_X2, j);
        else {
          bar_arrive(NB_FREE + wg, 160);
#pragma unroll
          for (int i = 0; i < 18; i++) xr[i] = 0;
        }
      }
      TS(4 + L * 20);
      {
        hint_wait(hint, hint_target(L * 7));
        TS(5 + L * 20);
        load_frags<N_WO>(a, sb, OFF_O, tid_());
        float acc[36];
        if (wg == 0) bar_sync(NB_ORD0, 256);
        load_frags<N_UP, N_WO>(a, sb, OFF_O, tid_());
        TS(19 + L * 20);
        mma_pass<72, PS_WO, 6, 256, D_WO, false, false>(acc, a, DESC_Q, 0, rel, -1, sb, OFF_O, 0, 0, 0, 0, [&]() {
          if (L == 0) {
            const uint32_t l = tid_() & 31, ra = slot_addr(12) + wg * SLOT + (w * 16 + (l & 15)) * 128;
            uint32_t z[4];
            mbar_wait(BAR_X + wg * 8, 0);
#pragma unroll
            for (int i = 0; i < 4; i++) ldsm4(&xr[4 * i], ra + (((i * 2 + (l >> 4)) ^ (l & 7)) << 4));
            ldsm4(z, ra + 8192 + ((j ^ (l & 7)) << 4));
            xr[16] = z[0]; xr[17] = z[1];
          }
        });
        TS(6 + L * 20);
#pragma unroll
        for (int c = 0; c < 9; c++) {
          xr[2 * c] = bf2_add(xr[2 * c], pack_bf16(acc[4 * c], acc[4 * c + 1]));
          xr[2 * c + 1] = bf2_add(xr[2 * c + 1], pack_bf16(acc[4 * c + 2], acc[4 * c + 3]));
        }
        store_own(xr, sb, L * 3 * TILE, j, tid_());
        RowStats rs;
        rs.add<18>(xr);
        rs.store(sb, L * 4096 + j * 128, tid_());
        hint_post(hint);
      }
      TS(16 + L * 20);
      hint_wait(hint, hint_target(L * 7 + 1));
      TS(15 + L * 20);
      gather_ln<4 * D_T0>(a, sb, L * 3 * TILE, L * 4096, m0, m1, r0, r1, P.zero);
      TS(7 + L * 20);
      const uint32_t hb = OFF_H + j * 24576;
      {
        float ka0, kb0, kc0, ka1, kb1, kc1;
        float acc[64];
        uint32_t hf[16];
        auto geglu = [&](auto chains, uint32_t hsm) {
          constexpr int CH = decltype(chains)::value & 15;
          float r[32];
#pragma unroll
          for (int e = 0; e < 32; e++) {
            float x = acc[e];
            if (e >= CH) x = __uint_as_float(__float_as_uint(x) ^ (__float_as_uint(r[e - CH]) & P.zero));
            if (decltype(chains)::value > 15 && e < 20) {
              const uint32_t ad = (e < 8 ? slot_addr(12) + e * 2048 + wg * 8192 : slot_addr(7 + (e >> 2)) + (e & 3) * 2048) + hsm;
              lds128(&a[48 + 4 * e], e >= CH ? ad ^ (__float_as_uint(r[e - CH]) & P.zero) : ad);
            }
            const bool hi = e & 2;
            float t = x * fmaf(x * x, hi ? kb1 : kb0, hi ? ka1 : ka0);
            asm("tanh.approx.f32 %0, %0;" : "+f"(t));
            const float u = x * acc[32 + e] * (hi ? kc1 : kc0);
            r[e] = fmaf(u, t, u);
            if (e & 1) hf[e >> 1] = pack_bf16(r[e - 1], r[e]);
          }
        };
        if (wg == 1) bar_sync(NB_ORD1, 256);
        mma_pass<128, PS_FF, 4, 2048, D_T0, true>(acc, a, DESC_SW128, 1, rel, NB_ORD1 - wg, sb, L * 3 * TILE, 0, m0, m1);
        if (tid_() == 0) mbar_arrive(bar_empty(13));
        TS(8 + L * 20);
        r0 = ln_rstd(r0, acc[0], P.zero); r1 = ln_rstd(r1, acc[0], P.zero);
        ka0 = 0.7978845608028654f * r0; kb0 = 0.035677408136300125f * r0 * r0 * r0; kc0 = 0.5f * r0 * r0;
        ka1 = 0.7978845608028654f * r1; kb1 = 0.035677408136300125f * r1 * r1 * r1; kc1 = 0.5f * r1 * r1;
#pragma unroll 1
        for (int t = 0; t < 8; t++) {
          geglu(IntC<2>(), 0);
          const uint32_t t16 = tid_() * 16;
          if (t < 5) {
            const uint32_t d = (t < 2 ? slot_addr(12) + wg * SLOT + t * 8192 : slot_addr(7) + t * SLOT + wg * 8192) + t16;
#pragma unroll
            for (int i = 0; i < 4; i++)
              sts128(d + i * 2048, hf[4 * i], hf[4 * i + 1], hf[4 * i + 2], hf[4 * i + 3]);
            if (t == 4) asm volatile("fence.proxy.async.shared::cta;" ::: "memory");
          } else {
#pragma unroll
            for (int i = 0; i < 4; i++) st16(sb, hb + (t - 5) * 8192 + t16, i * 2048, hf[4 * i], hf[4 * i + 1], hf[4 * i + 2], hf[4 * i + 3]);
          }
          bar_sync(NB_ORD0 + wg, 256);
          mma_pass<128, PS_FF, 4, 2048, 0, false, true>(acc, a, DESC_SW128, t & 1, rel, NB_ORD1 - wg, sb, hb + t16, t == 7);
        }
        TS(9 + L * 20);
        const uint32_t hsm = wg * 8192 + tid_() * 16;
        geglu(IntC<16 + CH_LAST>(), hsm);
#pragma unroll
        for (int i = 0; i < 16; i++) a[128 + i] = hf[i];
      }
      TS(10 + L * 20);
      {
        const uint32_t xs = slot_addr(12) + wg * SLOT;
        auto verify = [&](int p, uint32_t t16) {
          mbar_wait(bar_full(12) + wg * 8, p & 1);
          TS(71 + L * 32 + p * 5);
          const uint32_t ta = p < 2, tb = (p & 1) ? ta : L ^ 1, nb = p ? 4 : 7, sh = p == 0;
          uint32_t m = 0;
#pragma unroll
          for (int s = 0; s < 4; s++) m |= (lds32(xs + s * 2048 + t16) ^ ta) | (lds32(xs + 8192 + ((s * 2048 + t16) >> sh)) ^ tb);
          if (p == 0) {
#pragma unroll
            for (int s = 4; s < 7; s++) m |= lds32(xs + 8192 + s * 1024 + t16 / 2) ^ tb;
          }
          if (__any_sync(0xffffffffu, m & 1)) {
#pragma unroll 1
            for (int s = 0; s < 4 + nb; s++) {
              const bool nar = sh && s >= 4;
              const uint32_t o = nar ? 4096 + s * 1024 + t16 / 2 : s * 2048 + t16;
              uint32_t v[4] = {0, 0, 0, 0};
              do {
                if (nar) ld8(v, sb, j * PSRC + o, OFF_P + 32768 - 8192);
                else ld16(v, sb, j * PSRC + (p & 1) * 16384 + o, OFF_P);
              } while (__any_sync(0xffffffffu, (v[0] ^ (s < 4 ? ta : tb)) & 1));
              sts64(xs + o, v[0], v[1]);
              if (!nar) sts64(xs + o + 8, v[2], v[3]);
            }
            asm volatile("fence.proxy.async.shared::cta;" ::: "memory");
          }
        };
        uint32_t t16 = (a[142] | a[143]) & P.zero;
#pragma unroll 1
        for (int p = 0; p < 4; p++) {
          float acc[64];
          bar_sync(NB_ORD0 + wg + (p ? 0 : t16), 256);
          TS(64 + L * 32 + p * 5);
          if (p == 0) { rel(9); rel(10); rel(11); }
          mma_pass<128, PS_FF, 4, 2048, 0, false, false>(acc, a, DESC_SW128, p & 1, rel, NB_ORD1 - wg, nullptr, 0, 0, 0, 0, 0, [&]() {
            t16 = tid_() * 16;
            if (p) verify(p - 1, t16);
          });
          TS(65 + L * 32 + p * 5);
          if (p == 1 || p == 2) add_piece<false>(acc, xs + t16);
          const uint32_t oa = ((j + (p < 3 ? 1 : 4)) & 7) * PSRC + (p & 1) * 16384 + t16;
#pragma unroll
          for (int i = 0; i < 4; i++)
            st16(sb, oa, OFF_P + i * 2048, (pack_bf16(acc[8 * i], acc[8 * i + 1]) & ~1u) | (p < 2), pack_bf16(acc[8 * i + 2], acc[8 * i + 3]),
                 pack_bf16(acc[8 * i + 4], acc[8 * i + 5]), pack_bf16(acc[8 * i + 6], acc[8 * i + 7]));
          if (p == 0) {
#pragma unroll
            for (int i = 0; i < 8; i++)
              send8(sb, j * 1024 + t16 / 2, OFF_P + 32768 + i * PSRC, xs + 15360 + t16 / 2, i, j,
                    (pack_bf16(acc[32 + 4 * i], acc[33 + 4 * i]) & ~1u) | (L ^ 1), pack_bf16(acc[34 + 4 * i], acc[35 + 4 * i]));
          } else {
            if (p == 2) add_piece<false>(acc + 32, xs + 8192 + t16);
            const uint32_t ob = ((j + (p < 3 ? 7 : 5)) & 7) * PSRC + (p & 1) * 16384 + t16, tb = p == 2 ? L ^ 1 : p < 2;
#pragma unroll
            for (int i = 4; i < 8; i++)
              st16(sb, ob, OFF_P + i * 2048, (pack_bf16(acc[8 * i], acc[8 * i + 1]) & ~1u) | tb, pack_bf16(acc[8 * i + 2], acc[8 * i + 3]),
                   pack_bf16(acc[8 * i + 4], acc[8 * i + 5]), pack_bf16(acc[8 * i + 6], acc[8 * i + 7]));
          }
          hint_post(hint);
          TS(68 + L * 32 + p * 5);
          if (p == 1) {
            float s0 = 0.f, s1 = 0.f, s2 = 0.f, s3 = 0.f;
#pragma unroll
            for (int s = 0; s < 8; s++) {
              uint32_t u, v;
              lds64(u, v, xs + 8192 + s * 1024 + t16 / 2);
              s0 += bf_lo(u); s1 += bf_hi(u); s2 += bf_lo(v); s3 += bf_hi(v);
            }
            sts64(ytail(wg * 2) + t16, pack_bf16(s0, s1), pack_bf16(s2, s3));
          }
          if (p < 3) bar_arrive(NB_FREE + wg, 160);
          TS(67 + L * 32 + p * 5);
        }
        float acc[32];
        add_piece<true>(acc, xs + t16);
        add_piece<false>(acc, xs + 8192 + t16);
        bar_arrive(NB_FREE + wg + ((__float_as_uint(acc[0]) | __float_as_uint(acc[8]) | __float_as_uint(acc[16]) | __float_as_uint(acc[24])) & P.zero), 160);
        load_own(xr, sb, L * 3 * TILE, j);
        bar_sync(NB_ORD0 + wg, 256);
        TS(84 + L * 32);
        uint32_t t, yn[2];
        mma_pass<64, PS_FFA, 4, 2048, 0, false, false>(acc, a, DESC_SW128, 0, rel, wg ? -1 : NB_ORD1, nullptr, 0, 0, 0, 0, 0, [&]() {
          t = tid_();
          lds64(yn[0], yn[1], ytail(wg * 2) + t * 16);
          mbar_wait(bar_full(12) + wg * 8, 1);
#pragma unroll
          for (int i = 0; i < 8; i++) lds128(&a[4 * i], xs + i * 2048 + t * 16);
        });
        TS(11 + L * 20);
        while (true) {
          uint32_t m = 0;
#pragma unroll
          for (int i = 0; i < 8; i++) m |= a[4 * i];
          if (!__any_sync(0xffffffffu, m & 1)) break;
#pragma unroll
          for (int i = 0; i < 8; i++) ld16(&a[4 * i], sb, j * PSRC + t * 16, OFF_P + 16384 + i * 2048);
        }
        TS(12 + L * 20);
#pragma unroll
        for (int i = 0; i < 18; i++)
          xr[i] = bf2_add(xr[i], i < 16 ? pack_bf16(acc[2 * i] + (bf_lo(a[i]) + bf_lo(a[16 + i])), acc[2 * i + 1] + (bf_hi(a[i]) + bf_hi(a[16 + i]))) : yn[i - 16]);
        TS(18 + L * 20);
        if (L == 0) {
          store_own(xr, sb, OFF_X2, j, t);
          RowStats rs;
          rs.add<18>(xr);
          rs.store(sb, 8192 + j * 128, t);
          hint_post(hint);
        } else {
          const uint32_t l = t & 31, wb = xs + w * 512;
          if (l == 0) mbar_arrive(bar_empty(12));
          __syncwarp();
          asm volatile("barrier.cluster.arrive.relaxed.aligned;" ::: "memory");
#pragma unroll
          for (int i = 0; i < 4; i++) stsm4(wb + i * 2048 + (l & 24) * 16 + (((l & 7) ^ (i * 2 + (l >> 4))) << 4), xr[4 * i], xr[4 * i + 1], xr[4 * i + 2], xr[4 * i + 3]);
          stsm4(wb + 8192 + l * 16, xr[16], xr[17], 0, 0);
          __syncwarp();
          uint8_t* op = (uint8_t*)P.out + row_off(rb, wg, w * 32 + (l >> 3)) + j * 128 + (l & 7) * 16;
#pragma unroll
          for (int i = 0; i < 4; i++) {
            uint32_t r[4];
            lds128(r, wb + ((l & 6) << 10) + ((l & 1) * 2 + (i >> 1)) * 128 + (((((i & 1) * 4 + (l >> 3)) ^ l) & 7) << 4));
            *(uint4*)(op + i * 16 * DM) = make_uint4(r[0], r[1], r[2], r[3]);
          }
          uint32_t r[4];
          lds128(r, wb + 8192 + l * 16);
          if (l < 16) *(uint4*)((uint8_t*)P.out + row_off(rb, wg, t) + 1024 + j * 16) = make_uint4(r[0], r[1], r[2], r[3]);
        }
      }
      TS(13 + L * 20);
    }
  }
}

typedef CUresult (*EncodeFn)(CUtensorMap*, CUtensorMapDataType, cuuint32_t, void*, const cuuint64_t*, const cuuint64_t*, const cuuint32_t*,
                             const cuuint32_t*, CUtensorMapInterleave, CUtensorMapSwizzle, CUtensorMapL2promotion, CUtensorMapFloatOOBfill);

void encode(EncodeFn fn, CUtensorMap* m, const void* p, int rank, const cuuint64_t* dims, const cuuint64_t* str, const cuuint32_t* box) {
  const cuuint32_t es[3] = {1, 1, 1};
  fn(m, CU_TENSOR_MAP_DATA_TYPE_BFLOAT16, rank, const_cast<void*>(p), dims, str, box, es, CU_TENSOR_MAP_INTERLEAVE_NONE,
     CU_TENSOR_MAP_SWIZZLE_128B, CU_TENSOR_MAP_L2_PROMOTION_L2_256B, CU_TENSOR_MAP_FLOAT_OOB_FILL_NONE);
}

__global__ void probe_kernel() {}

void make_roles(uint8_t* role) {
  int cnt[8];
  cudaFuncSetAttribute(probe_kernel, cudaFuncAttributeMaxDynamicSharedMemorySize, SMEM_BYTES);
  cudaFuncSetAttribute(probe_kernel, cudaFuncAttributeNonPortableClusterSizeAllowed, 1);
  for (int r = 7; r >= 0; r--) {
    int n = 0;
    cudaLaunchConfig_t cfg = {};
    cudaLaunchAttribute at;
    at.id = cudaLaunchAttributeClusterDimension; at.val.clusterDim.x = 2 * (r < 3 ? 4 : r + 1); at.val.clusterDim.y = at.val.clusterDim.z = 1;
    cfg.gridDim = dim3(at.val.clusterDim.x); cfg.blockDim = dim3(384); cfg.dynamicSmemBytes = SMEM_BYTES; cfg.attrs = &at; cfg.numAttrs = 1;
    if (cudaOccupancyMaxActiveClusters(&n, probe_kernel, &cfg) != cudaSuccess) { cudaGetLastError(); n = r > 3 ? 8 : 8 + cnt[7]; }
    cnt[r] = r > 3 ? n : n - cnt[7];
  }
  int key[64], c = 0, total = 0, seg = 0;
  for (int r = 0; r < 8; r++) total += cnt[r];
  for (; c < 64 - total; c++) key[c] = -1;
  for (int r = 0; r < 8; r++) {
    if (r && cnt[r] != cnt[r - 1]) seg++;
    for (int i = 0; i < cnt[r] && c < 64; i++) key[c++] = seg * 16 + i;
  }
  int order[64], n = 0;
  bool used[64] = {};
  for (int pass = 0; pass < 2; pass++)
    for (int i = 0; i < 64; i++) {
      if (used[i]) continue;
      int m[4], k = 0;
      for (int q = i; q < 64 && k < 4; q++) if (!used[q] && (pass || (key[q] == key[i] && key[i] >= 0))) m[k++] = q;
      if (k == 4) for (int q = 0; q < 4; q++) { used[m[q]] = true; order[n++] = m[q]; }
    }
  for (int i = 0; i < 64; i++) role[order[i]] = (uint8_t)(((i >> 2) & 7) << 3 | (i >> 5) << 2 | (i & 3));
}

}

extern "C" void kernel_launch(void* const* d_in, const int* in_sizes, int n_in, void* d_out, int out_size) {
  (void)in_sizes; (void)n_in; (void)out_size;
  Params P = {};
  P.wqkv = (const __nv_bfloat16*)d_in[1]; P.wo = (const __nv_bfloat16*)d_in[2];
  P.out = (__nv_bfloat16*)d_out; P.zero = 0;
  cudaGetSymbolAddress((void**)&P.scr, g_scr);
  make_roles(P.role);
  void* fnp = nullptr; cudaDriverEntryPointQueryResult qr;
  cudaGetDriverEntryPoint("cuTensorMapEncodeTiled", &fnp, cudaEnableDefault, &qr);
  EncodeFn fn = (EncodeFn)fnp;
  CUtensorMap mx, m1, mg, mu, md;
  { const cuuint64_t dims[3] = {DM, SEQ / 2, 2}, str[2] = {DM * 4, DM * 2}; const cuuint32_t box[3] = {64, 64, 2}, box1[3] = {64, 64, 1};
    encode(fn, &mx, d_in[0], 3, dims, str, box); encode(fn, &m1, d_in[0], 3, dims, str, box1); }
  { const cuuint64_t dims[2] = {DFF, DM}, str[1] = {DFF * 2}; const cuuint32_t box[2] = {64, 64}; encode(fn, &mg, d_in[4], 2, dims, str, box); encode(fn, &mu, d_in[5], 2, dims, str, box); }
  { const cuuint64_t dims[2] = {DM, DFF}, str[1] = {DM * 2}; const cuuint32_t box[2] = {64, 64}; encode(fn, &md, d_in[6], 2, dims, str, box); }
  cudaFuncSetAttribute(fused_kernel, cudaFuncAttributeMaxDynamicSharedMemorySize, SMEM_BYTES);
  fused_kernel<<<128, 384, SMEM_BYTES, cudaStreamPerThread>>>(P, mx, m1, mg, mu, md);
}
```
